```python
import torch

def _softmax(x, axis=-1):
    return torch.softmax(x, dim=axis)
def _gelu(x):
    return torch.nn.functional.gelu(x, approximate="tanh")
def _silu(x):
    return torch.nn.functional.silu(x)
def _sigmoid(x):
    return torch.sigmoid(x)
def _layernorm(x, axis=-1, eps=1e-5):
    m = x.mean(dim=axis, keepdim=True)
    v = x.var(dim=axis, keepdim=True, unbiased=False)
    return (x - m) / torch.sqrt(v + eps)
def _scatter_add(tgt, idx, src, axis=0):
    return tgt.clone().index_add_(axis, idx, src)
def _segment_sum(src, seg, n):
    out = torch.zeros((n,) + src.shape[1:], dtype=src.dtype)
    return out.index_add_(0, seg, src)
def _pad(x, pw):
    flat = tuple(v for pair in reversed(pw) for v in pair)
    return torch.nn.functional.pad(x, flat)

kernel_name = 'recurrent_scan__ssm_conv_s4__moe_arch_mod__prompt'

def setup_inputs():

    _w = (lambda a: (lambda t: t.to(torch.bfloat16) if t.is_floating_point() else t)(torch.as_tensor(a)))
    def _A_setup():
        B, L, D, N = 1, 2048, 576, 128
        A_re = -(lambda _x: torch.exp(torch.as_tensor(_x)))((lambda *s: torch.randn(*s, dtype=torch.bfloat16) * 6.4)(D, N))
        A_im = torch.pi * (lambda *s: torch.randn(*s, dtype=torch.bfloat16) * 0.05)(D, N)
        B_re = (lambda *s: torch.randn(*s, dtype=torch.bfloat16) * 0.1)(D, N)
        B_im = (lambda *s: torch.randn(*s, dtype=torch.bfloat16) * 0.1)(D, N)
        C_re = (lambda *s: torch.randn(*s, dtype=torch.bfloat16) * 0.1)(D, N)
        C_im = (lambda *s: torch.randn(*s, dtype=torch.bfloat16) * 0.1)(D, N)
        log_dt = (lambda *s: torch.randn(*s, dtype=torch.bfloat16) * 0.05)(D) * 0.5 - 4.0
        Dskip = (lambda *s: torch.randn(*s, dtype=torch.bfloat16) * 0.05)(D)
        return {
            "u": _w((lambda *s: torch.randn(*s, dtype=torch.bfloat16) * 0.05)(B, L, D)),
            "A_re": _w(A_re),
            "A_im": _w(A_im),
            "B_re": _w(B_re),
            "B_im": _w(B_im),
            "C_re": _w(C_re),
            "C_im": _w(C_im),
            "log_dt": _w(log_dt),
            "Dskip": _w(Dskip),
        }
    _A_in = _A_setup()

    def _B_setup():
        B, S, D, F, C = 1, 2048, 576, 4608, 8
        return {
            "x": _w((lambda *s: torch.randn(*s, dtype=torch.bfloat16) * 0.05)(B, S, D)),
            "w_r": _w((lambda *s: torch.randn(*s, dtype=torch.bfloat16) * 0.05)(D)),
            "w_gate": _w((lambda *s: torch.randn(*s, dtype=torch.bfloat16) * 0.05)(D, F)),
            "w_up": _w((lambda *s: torch.randn(*s, dtype=torch.bfloat16) * 0.05)(D, F)),
            "w_down": _w((lambda *s: torch.randn(*s, dtype=torch.bfloat16) * 0.05)(F, D)),
        }
    _B_in = _B_setup()

    return {
        "A_u": _A_in["u"],
        "A_A_re": _A_in["A_re"],
        "A_A_im": _A_in["A_im"],
        "A_B_re": _A_in["B_re"],
        "A_B_im": _A_in["B_im"],
        "A_C_re": _A_in["C_re"],
        "A_C_im": _A_in["C_im"],
        "A_log_dt": _A_in["log_dt"],
        "A_Dskip": _A_in["Dskip"],
        "B_x": _B_in["x"],
        "B_w_r": _B_in["w_r"],
        "B_w_gate": _B_in["w_gate"],
        "B_w_up": _B_in["w_up"],
        "B_w_down": _B_in["w_down"],
    }

def reference(A_u, A_A_re, A_A_im, A_B_re, A_B_im, A_C_re, A_C_im, A_log_dt, A_Dskip, B_x, B_w_r, B_w_gate, B_w_up, B_w_down):
    def _A_ref(u, A_re, A_im, B_re, B_im, C_re, C_im, log_dt, Dskip):
        Bsz, L, D = u.shape
        dt = torch.exp(log_dt)[:, None]
        A = A_re + 1j * A_im
        Bc = B_re + 1j * B_im
        Cc = C_re + 1j * C_im
        logdA = dt * A
        dB = dt * Bc
        l = (lambda x, dt: x.to(dt))(torch.arange(L), A_re.dtype)
        P = torch.exp(logdA[:, :, None] * l[None, None, :])
        K = torch.einsum("dn,dnl,dn->dl", Cc, P, dB).real
        L2 = 2 * L
        Kp = _pad(K, ((0, 0), (0, L)))
        up = (lambda x, *d: x.permute(*d))(u, 0, 2, 1)
        up = _pad(up, ((0, 0), (0, 0), (0, L)))
        Kf = (lambda x, axes=(-2,-1): torch.fft.rfft2(x.float(), dim=axes))(Kp[:, None, :], axes=(-2, -1))
        Uf = (lambda x, axes=(-2,-1): torch.fft.rfft2(x.float(), dim=axes))(up[:, :, None, :], axes=(-2, -1))
        Yf = Uf * Kf[None, :, :, :]
        y = (lambda x, s, axes=(-2,-1): torch.fft.irfft2(x, s=s, dim=axes).to(torch.bfloat16))(Yf, (1, L2), axes=(-2, -1))[:, :, 0, :L]
        y = (lambda x, *d: x.permute(*d))(y, 0, 2, 1) + u * Dskip[None, None, :]
        return y

    def _B_ref(x, w_r, w_gate, w_up, w_down):
        B, S, D = x.shape
        C = 8
        r = x @ w_r
        idx = torch.argsort(-r, axis=-1)[:, :C]
        idx_e = (lambda x, n, axis: torch.repeat_interleave(x, n, dim=axis))(idx.reshape(B, C, 1), D, axis=2)
        x_sel = (lambda x, i, axis: torch.take_along_dim(x, i, dim=axis))(x, idx_e, axis=1)
        g = _silu(x_sel @ w_gate)
        u = x_sel @ w_up
        y = (g * u) @ w_down
        r_sel = _sigmoid((lambda x, i, axis: torch.take_along_dim(x, i, dim=axis))(r, idx, axis=1))
        y = y * r_sel.reshape(B, C, 1)
        b_off = (torch.arange(B) * S).reshape(B, 1)
        flat_idx = (idx + b_off).reshape(B * C)
        zero = (x * 0.0).reshape(B * S, D)
        upd = _scatter_add(zero, flat_idx, y.reshape(B * C, D), axis=0)
        return x + upd.reshape(B, S, D)

    x = A_u
    xn = _layernorm(x, axis=-1)
    s = _A_ref(xn, A_A_re, A_A_im, A_B_re, A_B_im, A_C_re, A_C_im, A_log_dt, A_Dskip)
    g = _silu(_B_ref(xn, B_w_r, B_w_gate, B_w_up, B_w_down))
    return x + s * g
```

```cpp
#include <cuda_runtime.h>
#include <cuda_bf16.h>
#include <cuda_fp16.h>
#include <cuda.h>
#include <stdint.h>
#include <stddef.h>
#include <type_traits>


namespace v3 {

constexpr int D_ = 576, F_ = 4608;
constexpr int NCTA = 120, NTHREADS = 512;
constexpr int SPIN_LIMIT = 1 << 16;

enum { B_Y = 0, B_X = 8, B_FIN = 10, B_TOP = 11, B_RAW = 13, B_SEL = 14, B_FULL = 16, B_EMPTY = 36  , B_WR = 67 };
constexpr int SM_PROG = 512, SM_SKIP = 544, SM_SEL = 576;
constexpr int SM_ST = 640;
constexpr int SM_RAW = 2688, PITCH = 80;
constexpr int SM_CH = SM_RAW + 256 * PITCH, CH = 18304;
constexpr int TAB = 0, FT = 3072, XX = 3712, BOX = 8064, YIN = 14208;
constexpr int SM_B = SM_CH + 5 * CH;
constexpr int NRING = 12, SM_W = SM_B + 9216, SM_FIN = SM_W + 13 * 8192, SM_TOTAL = 232448;
static_assert(SM_W % 1024 == 0 && SM_W + NRING * 8192 <= SM_TOTAL && SM_TOTAL - 18432 >= SM_W + 11 * 8192 && SM_TOTAL - 36864 >= SM_W + 8 * 8192, "smem");

struct Tune { int t_w, win, t_tile, split, stag, tail, win0, s0, t_d, hslp, zero; };

struct Scratch {
    uint32_t h[8 * 2304];
    uint32_t gt[8 * D_];
    uint2 stat[2048];
    uint32_t ep[NCTA * 8];
};
__device__ __align__(1024) Scratch g_s;

struct Hot {
    const __nv_bfloat16 *u, *wr;
    Scratch* s;
    const __nv_bfloat16 *are, *aim, *bre, *bim, *cre, *cim, *logdt, *dskip;
    __nv_bfloat16* out;
    Tune tn;
};
struct Maps { CUtensorMap w[3], u; };

__device__ __forceinline__ uint32_t smem_u32(const void* p) { return (uint32_t)__cvta_generic_to_shared(p); }
__device__ __forceinline__ void mbar_init(uint32_t b, int c) { asm volatile("mbarrier.init.shared::cta.b64 [%0], %1;" ::"r"(b), "r"(c) : "memory"); }
__device__ __forceinline__ void mbar_expect(uint32_t b, int bytes) { asm volatile("mbarrier.arrive.expect_tx.shared::cta.b64 _, [%0], %1;" ::"r"(b), "r"(bytes) : "memory"); }
__device__ __forceinline__ void mbar_arrive(uint32_t b) { asm volatile("mbarrier.arrive.shared::cta.b64 _, [%0];" ::"r"(b) : "memory"); }
__device__ __forceinline__ bool elect() { uint32_t d; asm volatile("{.reg .pred p; elect.sync _|p, 0xffffffff; selp.u32 %0,1,0,p;}" : "=r"(d)); return d; }
__device__ __forceinline__ void mbar_wait(uint32_t b, int par) {
    asm volatile("{\n.reg .pred p;\nLW:\nmbarrier.try_wait.parity.shared::cta.b64 p, [%0], %1, 2000;\n@!p bra LW;\n}" ::"r"(b), "r"(par) : "memory");
}
__device__ __forceinline__ uint32_t mapa(uint32_t a, uint32_t rank) { uint32_t d; asm("mapa.shared::cluster.u32 %0, %1, %2;" : "=r"(d) : "r"(a), "r"(rank)); return d; }
__device__ __forceinline__ void tma2d(uint32_t dst, const CUtensorMap* m, int c0, int c1, uint32_t bar) {
    asm volatile("cp.async.bulk.tensor.2d.shared::cluster.global.mbarrier::complete_tx::bytes [%0], [%1, {%3, %4}], [%2];" ::"r"(dst), "l"(m), "r"(bar), "r"(c0), "r"(c1) : "memory");
}
__device__ __forceinline__ void bulk_g2s(uint32_t dst, const void* src, int bytes, uint32_t bar) {
    asm volatile("cp.async.bulk.shared::cluster.global.mbarrier::complete_tx::bytes [%0], [%1], %2, [%3];" ::"r"(dst), "l"(src), "r"(bytes), "r"(bar) : "memory");
}
__device__ __forceinline__ void bar_sync(int id, int n) { asm volatile("bar.sync %0, %1;" ::"r"(id), "r"(n) : "memory"); }
__device__ __forceinline__ void bar_arrive(int id, int n) { asm volatile("bar.arrive %0, %1;" ::"r"(id), "r"(n) : "memory"); }
__device__ __forceinline__ uint4 ld_rlx4(const void* p) { uint4 v; asm volatile("ld.relaxed.gpu.global.v4.u32 {%0,%1,%2,%3}, [%4];" : "=r"(v.x), "=r"(v.y), "=r"(v.z), "=r"(v.w) : "l"(p) : "memory"); return v; }
__device__ __forceinline__ uint2 ld_rlx2(const void* p) { uint2 v; asm volatile("ld.relaxed.gpu.global.v2.u32 {%0,%1}, [%2];" : "=r"(v.x), "=r"(v.y) : "l"(p) : "memory"); return v; }
__device__ __forceinline__ uint32_t ld_rlx(const void* p) { uint32_t v; asm volatile("ld.relaxed.gpu.global.u32 %0, [%1];" : "=r"(v) : "l"(p) : "memory"); return v; }
__device__ __forceinline__ void st_rlx(void* p, uint32_t v) { asm volatile("st.relaxed.gpu.global.u32 [%0], %1;" ::"l"(p), "r"(v) : "memory"); }
__device__ __forceinline__ void st_rlx2(void* p, uint32_t x, uint32_t y) { asm volatile("st.relaxed.gpu.global.v2.u32 [%0], {%1,%2};" ::"l"(p), "r"(x), "r"(y) : "memory"); }
__device__ __forceinline__ uint4 ldg4(const void* p) { uint4 v; asm volatile("ld.global.nc.v4.u32 {%0,%1,%2,%3}, [%4];" : "=r"(v.x), "=r"(v.y), "=r"(v.z), "=r"(v.w) : "l"(p)); return v; }
__device__ __forceinline__ uint32_t ldg1(const void* p) { uint32_t v; asm volatile("ld.global.nc.u32 %0, [%1];" : "=r"(v) : "l"(p)); return v; }
__device__ __forceinline__ uint32_t ldg16(const void* p) { uint16_t v; asm volatile("ld.global.nc.u16 %0, [%1];" : "=h"(v) : "l"(p)); return v; }
__device__ __forceinline__ uint32_t lds32(uint32_t a) { uint32_t v; asm volatile("ld.shared.u32 %0, [%1];" : "=r"(v) : "r"(a) : "memory"); return v; }
__device__ __forceinline__ uint32_t lds32v(uint32_t a) { uint32_t v; asm volatile("ld.volatile.shared.u32 %0, [%1];" : "=r"(v) : "r"(a) : "memory"); return v; }
__device__ __forceinline__ uint32_t lds16(uint32_t a) { uint16_t v; asm volatile("ld.shared.u16 %0, [%1];" : "=h"(v) : "r"(a) : "memory"); return v; }
__device__ __forceinline__ uint2 lds64(uint32_t a) { uint2 v; asm volatile("ld.shared.v2.u32 {%0,%1}, [%2];" : "=r"(v.x), "=r"(v.y) : "r"(a) : "memory"); return v; }
__device__ __forceinline__ uint4 lds128(uint32_t a) { uint4 v; asm volatile("ld.shared.v4.u32 {%0,%1,%2,%3}, [%4];" : "=r"(v.x), "=r"(v.y), "=r"(v.z), "=r"(v.w) : "r"(a) : "memory"); return v; }
__device__ __forceinline__ void sts16(uint32_t a, uint32_t v) { asm volatile("st.shared.u16 [%0], %1;" ::"r"(a), "h"((uint16_t)v) : "memory"); }
__device__ __forceinline__ void sts32(uint32_t a, uint32_t v) { asm volatile("st.shared.u32 [%0], %1;" ::"r"(a), "r"(v) : "memory"); }
__device__ __forceinline__ void sts32v(uint32_t a, uint32_t v) { asm volatile("st.volatile.shared.u32 [%0], %1;" ::"r"(a), "r"(v) : "memory"); }
__device__ __forceinline__ void sts64(uint32_t a, uint32_t x, uint32_t y) { asm volatile("st.shared.v2.u32 [%0], {%1,%2};" ::"r"(a), "r"(x), "r"(y) : "memory"); }
__device__ __forceinline__ void sts128(uint32_t a, uint32_t x, uint32_t y, uint32_t z, uint32_t w) { asm volatile("st.shared.v4.u32 [%0], {%1,%2,%3,%4};" ::"r"(a), "r"(x), "r"(y), "r"(z), "r"(w) : "memory"); }
__device__ __forceinline__ void sts128f(uint32_t a, float x, float y, float z, float w) { asm volatile("st.shared.v4.f32 [%0], {%1,%2,%3,%4};" ::"r"(a), "f"(x), "f"(y), "f"(z), "f"(w) : "memory"); }
__device__ __forceinline__ void st_async4(uint32_t a, uint32_t x, uint32_t y, uint32_t z, uint32_t w, uint32_t bar) {
    asm volatile("st.async.shared::cluster.mbarrier::complete_tx::bytes.v4.b32 [%0], {%1,%2,%3,%4}, [%5];" ::"r"(a), "r"(x), "r"(y), "r"(z), "r"(w), "r"(bar) : "memory");
}
__device__ __forceinline__ void st_async2(uint32_t a, uint32_t x, uint32_t y, uint32_t bar) {
    asm volatile("st.async.shared::cluster.mbarrier::complete_tx::bytes.v2.b32 [%0], {%1,%2}, [%3];" ::"r"(a), "r"(x), "r"(y), "r"(bar) : "memory");
}
__device__ __forceinline__ void st_async2f(uint32_t a, float x, float y, uint32_t bar) {
    asm volatile("st.async.shared::cluster.mbarrier::complete_tx::bytes.v2.f32 [%0], {%1,%2}, [%3];" ::"r"(a), "f"(x), "f"(y), "r"(bar) : "memory");
}
__device__ __forceinline__ void ldm4(uint32_t a, uint32_t& r0, uint32_t& r1, uint32_t& r2, uint32_t& r3) {
    asm volatile("ldmatrix.sync.aligned.m8n8.x4.shared.b16 {%0,%1,%2,%3}, [%4];" : "=r"(r0), "=r"(r1), "=r"(r2), "=r"(r3) : "r"(a) : "memory");
}
__device__ __forceinline__ void ldm4t(uint32_t a, uint32_t (&r)[4]) {
    asm volatile("ldmatrix.sync.aligned.m8n8.x4.trans.shared.b16 {%0,%1,%2,%3}, [%4];" : "=r"(r[0]), "=r"(r[1]), "=r"(r[2]), "=r"(r[3]) : "r"(a) : "memory");
}
__device__ __forceinline__ void ldm2(uint32_t a, uint32_t& r0, uint32_t& r1) {
    asm volatile("ldmatrix.sync.aligned.m8n8.x2.shared.b16 {%0,%1}, [%2];" : "=r"(r0), "=r"(r1) : "r"(a) : "memory");
}
__device__ __forceinline__ void ldm2t(uint32_t a, uint32_t& r0, uint32_t& r1) {
    asm volatile("ldmatrix.sync.aligned.m8n8.x2.trans.shared.b16 {%0,%1}, [%2];" : "=r"(r0), "=r"(r1) : "r"(a) : "memory");
}
__device__ __forceinline__ void stm4(uint32_t a, uint32_t r0, uint32_t r1, uint32_t r2, uint32_t r3) {
    asm volatile("stmatrix.sync.aligned.m8n8.x4.shared.b16 [%0], {%1,%2,%3,%4};" ::"r"(a), "r"(r0), "r"(r1), "r"(r2), "r"(r3) : "memory");
}
__device__ __forceinline__ void stm4t(uint32_t a, uint32_t r0, uint32_t r1, uint32_t r2, uint32_t r3) {
    asm volatile("stmatrix.sync.aligned.m8n8.x4.trans.shared.b16 [%0], {%1,%2,%3,%4};" ::"r"(a), "r"(r0), "r"(r1), "r"(r2), "r"(r3) : "memory");
}
__device__ __forceinline__ void stm2t(uint32_t a, uint32_t r0, uint32_t r1) {
    asm volatile("stmatrix.sync.aligned.m8n8.x2.trans.shared.b16 [%0], {%1,%2};" ::"r"(a), "r"(r0), "r"(r1) : "memory");
}
__device__ __forceinline__ uint32_t movm(uint32_t a) { uint32_t d; asm volatile("movmatrix.sync.aligned.m8n8.trans.b16 %0, %1;" : "=r"(d) : "r"(a)); return d; }
__device__ __forceinline__ void mma_bf(float (&c)[4], uint32_t a0, uint32_t a1, uint32_t a2, uint32_t a3, uint32_t b0, uint32_t b1) {
    asm volatile("mma.sync.aligned.m16n8k16.row.col.f32.bf16.bf16.f32 {%0,%1,%2,%3},{%4,%5,%6,%7},{%8,%9},{%0,%1,%2,%3};"
                 : "+f"(c[0]), "+f"(c[1]), "+f"(c[2]), "+f"(c[3]) : "r"(a0), "r"(a1), "r"(a2), "r"(a3), "r"(b0), "r"(b1));
}
__device__ __forceinline__ void mma_bf8(float (&c)[4], uint32_t a0, uint32_t a1, uint32_t b0) {
    asm volatile("mma.sync.aligned.m16n8k8.row.col.f32.bf16.bf16.f32 {%0,%1,%2,%3},{%4,%5},{%6},{%0,%1,%2,%3};"
                 : "+f"(c[0]), "+f"(c[1]), "+f"(c[2]), "+f"(c[3]) : "r"(a0), "r"(a1), "r"(b0));
}
__device__ __forceinline__ void mma_h(float (&c)[4], uint32_t a0, uint32_t a1, uint32_t a2, uint32_t a3, uint32_t b0, uint32_t b1) {
    asm volatile("mma.sync.aligned.m16n8k16.row.col.f32.f16.f16.f32 {%0,%1,%2,%3},{%4,%5,%6,%7},{%8,%9},{%0,%1,%2,%3};"
                 : "+f"(c[0]), "+f"(c[1]), "+f"(c[2]), "+f"(c[3]) : "r"(a0), "r"(a1), "r"(a2), "r"(a3), "r"(b0), "r"(b1));
}
__device__ __forceinline__ void mma_h8(float (&c)[4], uint32_t a0, uint32_t a1, uint32_t b0) {
    asm volatile("mma.sync.aligned.m16n8k8.row.col.f32.f16.f16.f32 {%0,%1,%2,%3},{%4,%5},{%6},{%0,%1,%2,%3};"
                 : "+f"(c[0]), "+f"(c[1]), "+f"(c[2]), "+f"(c[3]) : "r"(a0), "r"(a1), "r"(b0));
}
template <int LIM>
__device__ __forceinline__ void mma_hp(int n, float (&d)[4], const float (&c)[4], uint32_t a0, uint32_t a1, uint32_t a2, uint32_t a3, uint32_t b0, uint32_t b1) {
    asm volatile("{.reg .pred p; setp.gt.s32 p, %14, %15;\n"
                 "@p mma.sync.aligned.m16n8k16.row.col.f32.f16.f16.f32 {%0,%1,%2,%3},{%4,%5,%6,%7},{%8,%9},{%10,%11,%12,%13};}"
                 : "+f"(d[0]), "+f"(d[1]), "+f"(d[2]), "+f"(d[3])
                 : "r"(a0), "r"(a1), "r"(a2), "r"(a3), "r"(b0), "r"(b1), "f"(c[0]), "f"(c[1]), "f"(c[2]), "f"(c[3]), "r"(n), "n"(LIM));
}
template <int LIM>
__device__ __forceinline__ void mma_hq(int n, float (&d)[4], uint32_t a0, uint32_t a1, uint32_t a2, uint32_t a3, uint32_t b0, uint32_t b1) {
    asm volatile("{.reg .pred p; setp.gt.s32 p, %10, %11;\n"
                 "@p mma.sync.aligned.m16n8k16.row.col.f32.f16.f16.f32 {%0,%1,%2,%3},{%4,%5,%6,%7},{%8,%9},{%0,%1,%2,%3};}"
                 : "+f"(d[0]), "+f"(d[1]), "+f"(d[2]), "+f"(d[3]) : "r"(a0), "r"(a1), "r"(a2), "r"(a3), "r"(b0), "r"(b1), "r"(n), "n"(LIM));
}
__device__ __forceinline__ void mma_hc(float (&d)[4], const float (&c)[4], uint32_t a0, uint32_t a1, uint32_t a2, uint32_t a3, uint32_t b0, uint32_t b1) {
    asm volatile("mma.sync.aligned.m16n8k16.row.col.f32.f16.f16.f32 {%0,%1,%2,%3},{%4,%5,%6,%7},{%8,%9},{%10,%11,%12,%13};"
                 : "=f"(d[0]), "=f"(d[1]), "=f"(d[2]), "=f"(d[3]) : "r"(a0), "r"(a1), "r"(a2), "r"(a3), "r"(b0), "r"(b1), "f"(c[0]), "f"(c[1]), "f"(c[2]), "f"(c[3]));
}
__device__ __forceinline__ uint32_t pack_bf(float lo, float hi) { uint32_t r; asm("cvt.rn.bf16x2.f32 %0, %1, %2;" : "=r"(r) : "f"(hi), "f"(lo)); return r; }
__device__ __forceinline__ uint32_t pack_h(float lo, float hi) { uint32_t r; asm("cvt.rn.f16x2.f32 %0, %1, %2;" : "=r"(r) : "f"(hi), "f"(lo)); return r; }
__device__ __forceinline__ float bf_lo(uint32_t w) { return __uint_as_float(w << 16); }
__device__ __forceinline__ float bf_hi(uint32_t w) { return __uint_as_float(w & 0xFFFF0000u); }
__device__ __forceinline__ float bf_round(float x) { return __uint_as_float(pack_bf(0.f, x)); }
__device__ __forceinline__ uint32_t bsub(uint32_t a, uint32_t b) { uint32_t r; asm("sub.rn.bf16x2 %0, %1, %2;" : "=r"(r) : "r"(a), "r"(b)); return r; }
__device__ __forceinline__ uint32_t bmul(uint32_t a, uint32_t b) { uint32_t r; asm("mul.rn.bf16x2 %0, %1, %2;" : "=r"(r) : "r"(a), "r"(b)); return r; }
__device__ __forceinline__ uint32_t bfma(uint32_t a, uint32_t b, uint32_t c) { uint32_t r; asm("fma.rn.bf16x2 %0, %1, %2, %3;" : "=r"(r) : "r"(a), "r"(b), "r"(c)); return r; }
__device__ __forceinline__ uint32_t hadd(uint32_t a, uint32_t b) { uint32_t r; asm("add.rn.f16x2 %0, %1, %2;" : "=r"(r) : "r"(a), "r"(b)); return r; }
__device__ __forceinline__ uint32_t prmt(uint32_t a, uint32_t b, uint32_t s) { uint32_t r; asm("prmt.b32 %0, %1, %2, %3;" : "=r"(r) : "r"(a), "r"(b), "r"(s)); return r; }
__device__ __forceinline__ float ex2f(float x) { float r; asm("ex2.approx.ftz.f32 %0, %1;" : "=f"(r) : "f"(x)); return r; }
__device__ __forceinline__ float rcpf(float x) { float r; asm("rcp.approx.ftz.f32 %0, %1;" : "=f"(r) : "f"(x)); return r; }
__device__ __forceinline__ float sqrt_ap(float x) { float r; asm("sqrt.approx.ftz.f32 %0, %1;" : "=f"(r) : "f"(x)); return r; }
__device__ __forceinline__ float tanh_ap(float x) { float r; asm("tanh.approx.f32 %0, %1;" : "=f"(r) : "f"(x)); return r; }
__device__ __forceinline__ float sigm(float x) { return rcpf(1.f + ex2f(-1.4426950408889634f * x)); }
__device__ __forceinline__ float silu_half(float h) { return fmaf(h, tanh_ap(h), h); }
__device__ __forceinline__ uint32_t clk32() { uint32_t c; asm volatile("mov.u32 %0, %%clock;" : "=r"(c)); return c; }
__device__ __forceinline__ void spin_until(uint32_t t0, int dt) {
#pragma unroll 1
    while ((int)(clk32() - t0) < dt) __nanosleep(32);
}
__device__ __forceinline__ void cp16(uint32_t dst, const void* src) { asm volatile("cp.async.cg.shared.global [%0], [%1], 16;" ::"r"(dst), "l"(src) : "memory"); }

__device__ __forceinline__ uint32_t xslot(int s, int h) { return XX + 32 * (s & ~1) + 16 * ((2 * h + (s & 1)) ^ ((s >> 1) & 2)); }

struct cf { float x, y; };
__device__ __forceinline__ cf cmul(cf a, cf b) { return {a.x * b.x - a.y * b.y, a.x * b.y + a.y * b.x}; }
__device__ __forceinline__ cf csq(cf a) { return {a.x * a.x - a.y * a.y, (a.x + a.x) * a.y}; }
__device__ __forceinline__ cf cpow_direct(float zr2, float zi, float l) {
    const float mag = ex2f(zr2 * l), th = zi * l;
    return {mag * __cosf(th), mag * __sinf(th)};
}
struct hp { uint32_t re, im; };
__device__ __forceinline__ hp mk2(cf a, cf b) { return {pack_h(a.x, b.x), pack_h(a.y, b.y)}; }
__device__ __forceinline__ hp his(hp a, hp b) { return {prmt(a.re, b.re, 0x7632), prmt(a.im, b.im, 0x7632)}; }
__device__ __forceinline__ hp operator*(hp a, hp b) {
    hp r;
    asm("{.reg .b32 t, u;\nmul.rn.f16x2 t, %3, %5;\nneg.f16x2 t, t;\nfma.rn.f16x2 %0, %2, %4, t;\nmul.rn.f16x2 u, %3, %4;\nfma.rn.f16x2 %1, %2, %5, u;}"
        : "=&r"(r.re), "=r"(r.im) : "r"(a.re), "r"(a.im), "r"(b.re), "r"(b.im));
    return r;
}
struct KParams { uint32_t are, aim, bre, bim, cre, cim, ldt, dsk; };

__device__ __forceinline__ uint32_t kgen(KParams kp, uint32_t scr, uint32_t oth, int bar, int lane, float (&d)[5][4], float& k0, int nc, uint32_t pause) {
    const float dt = bf_round(ex2f(bf_lo(kp.ldt) * 1.4426950408889634f));
    cf w = cmul({bf_lo(kp.cre), bf_lo(kp.cim)}, {dt * bf_lo(kp.bre), dt * bf_lo(kp.bim)});
    cf w1 = cmul({bf_hi(kp.cre), bf_hi(kp.cim)}, {dt * bf_hi(kp.bre), dt * bf_hi(kp.bim)});
    const float dk = bf_lo(kp.dsk);
    uint32_t z = prmt(kp.are, kp.aim, 0x5410), z1 = prmt(kp.are, kp.aim, 0x7632);
    uint32_t eb = __reduce_max_sync(~0u, __float_as_uint(fmaxf(fmaxf(fmaxf(fabsf(w.x), fabsf(w.y)), fmaxf(fabsf(w1.x), fabsf(w1.y))), fabsf(dk) * 0x1p-20f)));
    k0 = fmaf(dk, 1.f / 64.f, w.x + w1.x);
#pragma unroll
    for (int o = 16; o > 0; o >>= 1) k0 += __shfl_xor_sync(~0u, k0, o);
    const uint32_t sa = scr + 16 * lane;
    sts128(oth + 2048 + 16 * lane, __float_as_uint(w1.x), __float_as_uint(w1.y), z1, __float_as_uint(k0));
    sts32(oth + 2560, eb);
    bar_sync(bar, 64);
    const uint4 ov = lds128(sa + 2048);
    eb = min(max(max(eb, lds32(scr + 2560)) & 0x7F800000u, 0x00800000u), 0x7A000000u);
    const float sc = __uint_as_float(0x7B000000u - eb);
    k0 = (k0 + __uint_as_float(ov.w)) * sc;
#pragma unroll
    for (int i = 0; i < 5; i++) d[i][0] = d[i][1] = d[i][2] = d[i][3] = 0.f;
    const int mi = lane >> 3, j = lane & 7;
    const uint32_t la = scr + 1024 * (mi & 1) + 512 * (mi >> 1) + 16 * j, lb = scr + 512 * (mi & 1) + 128 * (mi >> 1) + 16 * j;
    auto st = [&](int grp, hp a, hp b, hp c, hp e) { sts128(sa + 1024 * grp, a.re, b.re, c.re, e.re); sts128(sa + 1024 * grp + 512, a.im, b.im, c.im, e.im); };
#pragma unroll 1
    do {
        const float zr2 = dt * bf_lo(z) * 1.4426950408889634f, zi = dt * bf_hi(z);
        const cf ws = {w.x * sc, w.y * sc};
        z = z1; w = w1;
        z1 = ov.z; w1 = {__uint_as_float(ov.x), __uint_as_float(ov.y)};
        const cf a1 = cpow_direct(zr2, zi, 1.f), a256 = cpow_direct(zr2, zi, 256.f);
        uint32_t a[4][4];
        {
            const cf b1 = cpow_direct(-zr2, zi, -16.f), b2 = csq(b1), b4 = csq(b2), b8 = csq(b4);
            const hp m2 = mk2(b2, b2), m4 = mk2(b4, b4), m8 = mk2(b8, b8);
            const hp u0 = mk2({1.f, 0.f}, b1), u1 = u0 * m2, u2 = u0 * m4, u3 = u1 * m4;
            __syncwarp();
            st(0, u0, u1, u2, u3);
            st(1, u0 * m8, u1 * m8, u2 * m8, u3 * m8);
            __syncwarp();
#pragma unroll
            for (int k = 0; k < 4; k++) ldm4t(la + 128 * k, a[k]);
        }
        auto tile = [&](int T, int grp) {
#pragma unroll
            for (int e = 0; e < 2; e++) {
                uint32_t b[4];
                ldm4t(lb + 1024 * grp + 256 * e, b);
                mma_h(d[T], a[2 * e][0], a[2 * e][1], a[2 * e][2], a[2 * e][3], b[0], b[1]);
                mma_h(d[T], a[2 * e + 1][0], a[2 * e + 1][1], a[2 * e + 1][2], a[2 * e + 1][3], b[2], b[3]);
            }
        };
        const cf a2 = csq(a1), a4 = csq(a2), a8 = csq(a4), a512 = csq(a256), a1024 = csq(a512);
        const hp m2 = mk2(a2, a2), m4 = mk2(a4, a4), m8 = mk2(a8, a8), m256 = mk2(a256, a256), m512 = mk2(a512, a512);
        const hp v1 = mk2(cmul(ws, a1), cmul(ws, a2)), v3 = v1 * m2, v5 = v1 * m4, v7 = v3 * m4, v15 = v7 * m8;
        const hp e1 = his(v1, v3) * m256, e2 = e1 * m4;
        __syncwarp();
        st(0, v1, v5, v1 * m8, v5 * m8);
        st(1, v3, v7, v3 * m8, v15);
        st(2, e1, e2, e1 * m8, e2 * m8);
        __syncwarp();
        tile(0, 0); tile(1, 1); tile(2, 2);
        const hp f1 = his(v3, v7) * m512, f2 = f1 * m8, g1 = his(v7, v15) * mk2(a1024, a1024), g2 = g1 * m256;
        __syncwarp();
        st(0, f1, f2, f1 * m256, f2 * m256);
        st(1, g1, g2, g1 * m512, g2 * m512);
        __syncwarp();
        tile(3, 0); tile(4, 1);
        if (pause) mbar_wait(pause, 0);
    } while (--nc);
    return eb;
}

__global__ void __cluster_dims__(8, 1, 1) __launch_bounds__(NTHREADS, 1) fused_kernel(const Hot p, const __grid_constant__ Maps m) {
    extern __shared__ __align__(1024) char smem[];
    const uint32_t t0 = clk32();
    const int tid = threadIdx.x, lane = tid & 31, warp = __shfl_sync(~0u, tid >> 5, 0), bid = blockIdx.x;
    const int g = lane >> 2, t = lane & 3, mi = lane >> 3, j = lane & 7;
    const int r = bid & 7, cl = bid >> 3;
    const int ph0 = (cl < 3 || cl > 8) ? 0 : 2, ph1 = cl < 9 ? 3 : 2, cu = cl < 3 ? cl : cl - 6;
    const int nch = cl < 3 ? 4 : 5, cbase = max(32 * cl, 40 * cl - 24);
    uint32_t S = smem_u32(smem);
    asm volatile("" : "+r"(S));

    const int half = warp > 4, k = (int)(0x5436666621043210ull >> (4 * warp)) & 15;
    const bool extra = cl == 2 && warp < 4, svcwarp = (warp >> 2) == 2;
    KParams kp;
    uint32_t epoch;
    if (k > 4 || extra) epoch = ld_rlx(&p.s->ep[bid * 8]);
    if (k < nch) {
        const uint32_t ch = cbase + 8 * k + r, po = ch * 64 + half * 32 + lane;
        kp.bre = ldg1((const uint32_t*)p.bre + po); kp.bim = ldg1((const uint32_t*)p.bim + po);
        kp.cre = ldg1((const uint32_t*)p.cre + po); kp.cim = ldg1((const uint32_t*)p.cim + po);
        kp.are = ldg1((const uint32_t*)p.are + po); kp.aim = ldg1((const uint32_t*)p.aim + po);
        kp.ldt = ldg16((lane & 1 ? p.dskip : p.logdt) + ch);
        sts128(S + SM_CH + k * CH + 16 * lane + (half ? FT : (lane < 2 ? TAB : (lane < 8 ? TAB + 2048 : FT + 384))), 0u, 0u, 0u, 0u);
        sts32(S + SM_PROG + 4 * k, 14);
    } else if (warp == 12) {
        if (elect()) {
            mbar_init(S + B_WR * 8, 1);
            mbar_expect(S + B_WR * 8, cl == 2 ? 38016 : 19584);
            const __nv_bfloat16* src = p.u + (8 * (cl & 14) + 2 * r + (cl & 1)) * 9216;
            bulk_g2s(S + SM_TOTAL - 18432, src, 18432, S + B_WR * 8);
            if (cl == 2) bulk_g2s(S + SM_TOTAL - 36864, src + 97 * 9216, 18432, S + B_WR * 8);
            bulk_g2s(S + SM_ST, p.wr, 1152, S + B_WR * 8);
        }
    } else if (svcwarp) {
        if (elect()) {
#pragma unroll
            for (int i = 0; i < 16; i++) mbar_init(S + (warp & 3) * 128 + i * 8, warp > (i < 12 ? 10 : 9) ? 4 : 1);
            asm volatile("fence.mbarrier_init.release.cluster;" ::: "memory");
        }
        __syncwarp();
        if (tid <= 256 + B_TOP) mbar_expect(S + lane * 8, lane >= B_FIN ? (lane > B_FIN ? 256 : 2048) : (lane > B_X ? 3072 : (512 << mi)) * nch);
    }
    __syncthreads();
    asm volatile("barrier.cluster.arrive.relaxed.aligned;" ::: "memory");
    const uint2* sp = &p.s->stat[256 * r + 2 * (tid & 127)];
    if (svcwarp || extra) {
        const uint32_t tag = ~epoch & 1;
        const int tile = extra ? 15 : cl;
        float d1[4] = {0, 0, 0, 0}, d2[4] = {0, 0, 0, 0}, d3[4] = {0, 0, 0, 0}, d4[4] = {0, 0, 0, 0}, d5[4] = {0, 0, 0, 0}, d6[4] = {0, 0, 0, 0}, d7[4] = {0, 0, 0, 0};
        uint32_t o0 = 0x3F803F80u, o1 = o0, o2 = o0, o3 = o0;
        asm volatile("" : "+r"(o0), "+r"(o1), "+r"(o2), "+r"(o3));
        const uint32_t xa = S + SM_TOTAL - (extra ? 36864 : 18432) + (8 * (mi >> 1) + 2 * (warp & 3) + (mi & 1)) * 1152 + 16 * j;
        const uint32_t wa = S + SM_ST + 64 * (g >> 2) + 16 * t + 2 * (g & 2);
        mbar_wait(S + B_WR * 8, 0);
#pragma unroll 3
        for (int i = 0; i < 1152; i += 128) {
            const uint4 x = lds128(xa + i);
            const uint32_t w0 = lds32(wa + i), w1 = lds32(wa + i + 8);
            mma_bf8(d3, x.x, x.y, x.x);
            mma_bf8(d4, x.x, x.y, x.y);
            mma_bf(d1, x.x, x.y, x.z, x.w, o0, o1);
            mma_bf(d5, o0, o1, o2, o3, w0, w1);
            mma_bf8(d6, x.z, x.w, x.z);
            mma_bf8(d7, x.z, x.w, x.w);
            mma_bf(d2, x.x, x.y, x.z, x.w, w0, w1);
        }
        float sx = d1[0] + d1[2], sq = (g & 1) ? (d3[1] + d4[3]) + (d6[1] + d7[3]) : (d3[0] + d4[2]) + (d6[0] + d7[2]);
        sq = t == mi ? sq : 0.f;
        float dot = (t >> 1) == (g & 1) ? ((t & 1) ? d2[2] : d2[0]) : 0.f, wsum = d5[0];
        sx += __shfl_xor_sync(~0u, sx, 4);
#pragma unroll
        for (int o = 1; o < 8; o *= 2) {
            sq += __shfl_xor_sync(~0u, sq, o);
            dot += __shfl_xor_sync(~0u, dot, o);
            if (o < 4) wsum += __shfl_xor_sync(~0u, wsum, o);
        }
        const float mean = sx * (1.f / 576.f), var = fmaxf(sq * (1.f / 576.f) - mean * mean, 0.f);
        const float mu = bf_round(mean), sd = bf_round(sqrt_ap(bf_round(bf_round(var) + 1e-5f)));
        const uint32_t idx = 256 * r + 16 * tile + 4 * (warp & 3) + mi;
        const uint32_t rb = pack_bf(0.f, (dot - mu * wsum) * rcpf(sd));
        const uint32_t ga = S + SM_ST + 1152 + 32 * warp;
        sts64(ga + 8 * mi, (__float_as_uint(mu) >> 16) | __float_as_uint(sd), ((rb ^ (((int)rb >> 31) | 0x80000000u)) & 0xFFFF0000u) | (tag << 15) | idx);
        bar_sync(extra ? 14 : 15, 128);
        if ((tid & 127) < 16) {
            const uint2 v = lds64(ga + 8 * lane);
            st_rlx2(&p.s->stat[256 * r + 16 * tile + lane], v.x, v.y);
        }
        if (lane == 0) mbar_arrive(S + (B_EMPTY + (extra ? 8 : 11)) * 8);
    }

    if (k < nch) {
        const uint32_t cb = S + SM_CH + k * CH, scr = cb + BOX + 3072 * half, oth = cb + BOX + 3072 - 3072 * half;
        float d[5][4], k0;
        kp.dsk = __shfl_sync(~0u, kp.ldt, 1);
        kp.ldt = __shfl_sync(~0u, kp.ldt, 0);
        const uint32_t eb = kgen(kp, scr, oth, 1 + k, lane, d, k0, k > 2 ? 3 - 2 * half : 2, p.tn.stag ? S + (B_EMPTY + 11) * 8 : 0);
        __syncwarp();
#pragma unroll
        for (int i = 0; i < 5; i++)
            if (half == (i < 3)) sts128f(scr + i * 512 + lane * 16, d[i][0], d[i][1], d[i][2], d[i][3]);
        bar_sync(1 + k, 64);
        auto both = [&](int i, uint32_t& w0, uint32_t& w1) {
            const uint4 v = lds128(oth + i * 512 + lane * 16);
            w0 = pack_h(d[i][0] + __uint_as_float(v.x), d[i][1] + __uint_as_float(v.y));
            w1 = pack_h(d[i][2] + __uint_as_float(v.z), d[i][3] + __uint_as_float(v.w));
        };
        if (half) {
            uint32_t a0, a1, b0, b1;
            both(3, a0, a1); both(4, b0, b1);
            const uint32_t o = cb + FT + 56 + 128 * (t >> 1) + 8 * g + 4 * (t & 1), q = cb + FT + 376 + 64 * t + 4 * g;
            sts32(o, a0); sts32(o + 64, a1); sts32(q, b0); sts32(q + 32, b1);
        } else {
            {
                uint32_t a[2], b[2], c[2], last = pack_h(k0, k0);
                both(0, a[0], a[1]); both(1, b[0], b[1]); both(2, c[0], c[1]);
                const uint32_t o = cb + TAB + 32 + 16 * lane;
                sts16(cb + TAB + 28, last);
#pragma unroll
                for (int h = 0; h < 4; h++) {
                    const uint32_t e = h < 2 ? b[h] : c[h - 2], pv = __shfl_sync(~0u, lane == 31 ? last : e, lane - 1);
                    if (h < 2) sts128(o + 512 * h, prmt(a[h], pv, 0x7610), prmt(a[h], 0, 0x1032), prmt(e, a[h], 0x7610), prmt(e, 0, 0x1032));
                    else sts128(o + 512 * h, prmt(pv, 0, 0x3232), prmt(e, pv, 0x7610), prmt(e, 0, 0x1032), prmt(e, 0, 0x3232));
                    last = e;
                }
                if (lane == 31) sts128(o + 1552, prmt(last, 0, 0x3232), prmt(last, 0, 0x3232), last & 0xFFFF0000u, 0u);
                __syncwarp();
            }
            uint32_t R[66], x[5];
#pragma unroll
            for (int i = 0; i < 66; i++) R[i] = lds32(cb + TAB + 4 * (7 + g - 2 * t) + 32 * i);
            bar_arrive(1 + k, 64);
            float w[5][4];
#pragma unroll
            for (int i = 0; i < 5; i++) w[i][0] = w[i][1] = w[i][2] = w[i][3] = 0.f;
            uint32_t xa[8], xo = cb, fa = cb + XX + 16 * j;
#pragma unroll
            for (int i = 0; i < 8; i++) xa[i] = xslot(j + i, mi & 1);
            const uint32_t fb = cb + TAB + 3328 + 16 * (lane & 15);
            uint32_t ybar = mapa(S, 4 + (g >> 1)), dy = ybar - mapa(S, g >> 1), db = dy;
            uint32_t ya = ybar + SM_CH + k * CH + YIN + 64 * r + 16 * (((lane >> 1) ^ (2 * k + (cbase >> 2) + (r >> 2))) & 3) + 8 * (t & 1) - 512;
            ybar -= 8 - 8 * B_Y;
            const uint32_t sc = prmt(eb + 0x04800000u, 0, 0x3232), idm = g == 2 * t ? 0x3C00u : (g == 2 * t + 1 ? 0x3C000000u : 0u);
            uint32_t z = p.tn.zero;
            int lim = 14, n = 16;
            mbar_wait(S + B_X * 8, 0);
            ldm2(xo + xa[0], x[1], x[0]);
            ldm2(xo + xa[1], x[1], x[2]);
            ldm2(xo + xa[2], x[3], x[4]);
            auto tile = [&](auto nj) {
                constexpr int NJ = decltype(nj)::value;
                asm volatile("" : "+r"(z), "+r"(n));
#pragma unroll 1
                while (n < lim) { lim = lds32v(S + SM_PROG + 4 * k); if (n < lim) __nanosleep(40); }
                uint32_t f0, f1;
                ldm2(fa, f0, f1);
#pragma unroll
                for (int q = 1; q <= 8; q++) {
                    uint32_t n0, n1;
                    ldm2(xo + xa[(q + 2) & 7] + 32 * ((q + 2) & 8), n0, n1);
                    const uint32_t a2 = x[0] | z, a3 = x[1] | z;
#pragma unroll
                    for (int i = 0; i < NJ; i++) {
                        const int s = 16 * i + 16 - 2 * q;
                        if (q == 1) mma_hc(w[i], w[i + 1], x[1], x[2], a2, a3, R[s], R[s + 1]);
                        else mma_h(w[i], x[1], x[2], a2, a3, R[s], R[s + 1]);
                    }
                    if (q == 4) mma_h8(w[0], f0, f1, idm);
                    if (q == 8 && NJ == 4) {
                        const float zero[4] = {0.f, 0.f, 0.f, 0.f};
                        mma_hc(w[4], zero, x[1], x[2], a2, a3, R[64], R[65]);
                    }
                    x[0] = x[2]; x[1] = x[3]; x[2] = x[4]; x[3] = n0; x[4] = n1;
                }
                dy = 512 - dy; db = 8 - db; ya += dy; ybar += db;
                st_async2(ya, bmul(pack_bf(w[0][0], w[0][1]), sc), bmul(pack_bf(w[0][2], w[0][3]), sc), ybar);
                xo += 256;
                fa = n <= 13 ? fb - 256 * n : fa;
                n--;
            };
            const int n1 = p.tn.tail;
#pragma unroll 1
            do tile(std::integral_constant<int, 4>()); while (n > n1);
#pragma unroll 1
            while (n > 0) tile(std::integral_constant<int, 2>());
            return;
        }
    }

    if (warp == 12) {
        if (elect()) {
            asm volatile("prefetch.tensormap [%0];" ::"l"(&m.u) : "memory");
            spin_until(t0, p.tn.t_tile);
            mbar_expect(S + B_RAW * 8, 256 * PITCH);
            asm volatile("cp.async.bulk.tensor.5d.shared::cluster.global.mbarrier::complete_tx::bytes [%0], [%1, {%3, 0, %4, 0, 0}], [%2];"
                         ::"r"(S + SM_RAW), "l"(&m.u), "r"(S + B_RAW * 8), "r"(cbase), "r"(4 * r) : "memory");
            spin_until(t0, ph0 ? p.tn.t_d : p.tn.t_w);
            uint32_t bar = S + B_FULL * 8, dst = S + SM_W, em = cl == 2 ? 0x1249900u : 0x1249800u;
            int s = 0;
#pragma unroll 1
            for (int ph = ph0; ph < ph1; ph++) {
                const int c0 = ph < 2 ? 64 * cu + 576 * r : 64 * cl;
                int c1 = ph < 2 ? 0 : 576 * r;
#pragma unroll 1
                for (int n = 0; n < 9; n++, s++) {
                    const int w = s < p.tn.s0 ? p.tn.win0 : p.tn.win;
                    if (s >= w) mbar_wait(bar - 8 * w, 0);
                    if (em & 1) mbar_wait(bar + 8 * (B_EMPTY - B_FULL), 0);
                    mbar_expect(bar, 8192);
                    tma2d(dst, m.w + ph, c0, c1, bar);
                    bar += 8; em >>= 1; c1 += 64;
                    dst = dst == S + SM_W + (NRING - 1) * 8192 ? S + SM_W : dst + 8192;
                }
            }
        }
        __syncwarp();
    }

    if (warp == 15) {
        uint32_t kk[8];
#pragma unroll 1
        for (int it = 0; it < SPIN_LIMIT; it++) {
            uint32_t bad = 0;
#pragma unroll
            for (int q = 0; q < 4; q++) {
                const uint4 v = ld_rlx4(sp - 64 * q);
                kk[2 * q] = ~v.y; kk[2 * q + 1] = ~v.w;
            }
#pragma unroll
            for (int q = 0; q < 8; q++) bad |= kk[q] ^ (epoch << 15);
            if (!(bad & 0x8000u)) break;
            __nanosleep(64);
        }
        asm volatile("barrier.cluster.wait.aligned;" ::: "memory");
        uint32_t mine = 0;
#pragma unroll 1
        for (int pass = 0; pass < 2; pass++) {
            uint32_t c = 0;
#pragma unroll 1
            for (int n = 0; n < 8; n++) {
                const uint32_t a = __viaddmin_u32(kk[0], c, __viaddmin_u32(kk[1], c, kk[2] + c)), b = __viaddmin_u32(kk[3], c, __viaddmin_u32(kk[4], c, kk[5] + c));
                c += ~__reduce_min_sync(~0u, __vimin3_u32(a, b, __viaddmin_u32(kk[6], c, kk[7] + c)));
                if (j == n) mine = c;
            }
            if (pass) break;
#pragma unroll
            for (int e = 0; e < 2; e++) {
                const uint32_t ob = mapa(S, 2 * mi + e);
                asm volatile("st.async.shared::cluster.mbarrier::complete_tx::bytes.b32 [%0], %1, [%2];" ::"r"(ob + SM_B + 32 * r + 4 * j), "r"(~mine), "r"(ob + B_TOP * 8) : "memory");
            }
            mbar_wait(S + B_TOP * 8, 0);
            const uint2 v = lds64(S + SM_B + 8 * lane);
            kk[0] = v.x; kk[1] = v.y;
        }
        const uint32_t rb = (mine ^ ((~(int)mine >> 31) | 0x80000000u)) & 0xFFFF0000u;
        const int row = (mine & 0xE0) * 8 + ((mine >> 3) & 0xE0) + (mine & 0x11) + (mine & 2) * 4 + ((mine >> 1) & 6);
        sts64(S + SM_SEL + 8 * j, (mine & 0xFFFFu) | pack_bf(0.f, sigm(__uint_as_float(rb))), row);
        sts32(S + SM_SKIP + 4 * j, 0u);
        __syncwarp();
        if (((mine >> 8) & 7) == r) asm volatile("red.shared.or.b32 [%0], %1;" ::"r"(S + SM_SKIP + 4 * (mine & 7)), "r"(1u << ((mine >> 3) & 31)) : "memory");
        __syncwarp();
        if (elect()) mbar_arrive(S + B_SEL * 8);
    }

    if (svcwarp) {
        const uint32_t tag = ~epoch & 1;
        const int fw = warp & 3, i = tid & 127;
        uint4 sw;
#pragma unroll 1
        for (int it = 0; it < SPIN_LIMIT; it++) {
            sw = ld_rlx4(sp);
            if (!(((sw.y ^ -tag) | (sw.w ^ -tag)) & 0x8000u)) break;
        }
        bar_sync(15, 128);
        {
            const float r0 = 0.5f * rcpf(bf_hi(sw.x)), r1 = 0.5f * rcpf(bf_hi(sw.z));
            sts128f(S + SM_ST + 16 * i, r0, -bf_lo(sw.x) * r0, r1, -bf_lo(sw.z) * r1);
        }
        asm volatile("barrier.cluster.wait.aligned;" ::: "memory");
        mbar_wait(S + B_RAW * 8, 0);
        bar_sync(15, 128);
        {
            const uint32_t xb = mapa(S, g);
            uint32_t xd = xb + SM_CH + xslot(8 + 2 * r + (t >> 1), t & 1) + (fw & 1) * CH + 256 * (fw & 2), xbar = xb + B_X * 8;
            uint32_t ra = S + SM_RAW + (64 * mi + j + 4 * (fw & 2)) * PITCH + 16 * (fw & 1), sa = S + SM_ST + 64 * (t & 2) + 16 * (t & 1) + 128 * (fw & 2);
#pragma unroll 1
            for (int u = 0; u < 4; u++) {
                uint32_t a[3][4];
                uint4 s[4];
#pragma unroll
                for (int e = 0; e < 3; e++) ldm4t(ra + 32 * e, a[e]);
#pragma unroll
                for (int e = 0; e < 4; e++) s[e] = lds128(sa + 32 * e);
#pragma unroll
                for (int n = 0; n < 3; n++) {
                    if (n == 2 && 4 + (fw & 1) >= nch) break;
#pragma unroll
                    for (int e = 0; e < 4; e++)
                        a[n][e] = pack_h(fmaf(bf_lo(a[n][e]), __uint_as_float(s[e].x), __uint_as_float(s[e].y)), fmaf(bf_hi(a[n][e]), __uint_as_float(s[e].z), __uint_as_float(s[e].w)));
                    st_async4(xd + 2 * n * CH, a[n][0], a[n][1], a[n][2], a[n][3], xbar);
                }
                xd += 1024; ra += 16 * PITCH; sa += 512; xbar |= 8;
            }
        }
        mbar_wait(S + B_SEL * 8, 0);
        const int col = 64 * cl + (i & 48) + ((i >> 1) & 7) + 8 * (i & 1);
        const uint2 sr = lds64(S + SM_SEL + 8 * r);
        uint32_t xr, s2;
        if (ph1 == 3) { xr = ldg16(p.u + sr.y * D_ + col); s2 = ld_rlx(&p.s->stat[sr.x & 2047]); }
        if (ph0 == 0) {
            const uint2 sv = lds64(S + SM_SEL + 8 * j);
            const uint4* src = (const uint4*)p.u + sv.y * 72 + (i >> 3);
            uint4 v[5];
#pragma unroll
            for (int n = 0; n < 5; n++) v[n] = ldg4(src + (n < 4 ? 16 * n : 56));
            const uint32_t s1 = ld_rlx(&p.s->stat[sv.x & 2047]);
            const float ri = rcpf(bf_hi(s1));
            const uint32_t mu = prmt(s1, 0, 0x1010), hi = pack_bf(ri, ri), lo = pack_bf(ri - bf_lo(hi), ri - bf_lo(hi));
            auto nrm = [&](uint32_t x) { const uint32_t e = bsub(x, mu); return bfma(e, hi, bmul(e, lo)); };
#pragma unroll
            for (int n = 0; n < 5; n++) sts128(S + SM_B + 16 * i + (n < 4 ? 2048 * n : 7168), nrm(v[n].x), nrm(v[n].y), nrm(v[n].z), nrm(v[n].w));
        }
        uint32_t* const hp = p.s->h + 2304 * r;
        uint32_t g0 = 0, g1 = 0, bar = S + B_FULL * 8, of = 0;
        const uint32_t aa = S + SM_W + (8 * (mi >> 1) + j) * 128 + (((2 * fw + (mi & 1)) ^ j) << 4);
        float d[4][4];
#pragma unroll 1
        for (int ph = ph0;; ph++) {
            if (ph == 2) {
                uint4 v[5];
#pragma unroll 1
                for (int it = 0; it < SPIN_LIMIT; it++) {
                    uint32_t a = ~0u, o = 0;
#pragma unroll
                    for (int n = 0; n < 5; n++) v[n] = ld_rlx4((const uint4*)hp + i + (n < 4 ? 128 * n : 448));
#pragma unroll
                    for (int n = 0; n < 5; n++) { a &= v[n].x & v[n].z; o |= v[n].x | v[n].z; }
                    if (((tag ? a : ~o) & 1)) break;
                    __nanosleep(p.tn.hslp);
                }
                bar_sync(15, 128);
#pragma unroll
                for (int n = 0; n < 5; n++) sts128(S + SM_B + 16 * i + (n < 4 ? 2048 * n : 7168), v[n].x, v[n].y, v[n].z, v[n].w);
            }
            if (ph != 1) bar_sync(15, 128);
#pragma unroll
            for (int e = 0; e < 4; e++) d[0][e] = d[1][e] = d[2][e] = d[3][e] = 0.f;
#pragma unroll 1
            for (int n = 0; n < 9216; n += 3072) {
                uint32_t a[12][4], b[24];
#pragma unroll
                for (int e = 0; e < 6; e++) ldm4(S + SM_B + 16 * lane + n + 512 * e, b[4 * e], b[4 * e + 1], b[4 * e + 2], b[4 * e + 3]);
                mbar_wait(bar + 8 * min(lane, 2), 0);
                __syncwarp();
#pragma unroll
                for (int e = 0; e < 12; e++) ldm4t(aa + of + 2048 * e, a[e]);
#pragma unroll
                for (int e = 0; e < 12; e++) mma_bf(d[e & 3], a[e][0], a[e][1], a[e][2], a[e][3], b[2 * e], b[2 * e + 1]);
                if (lane == 0) mbar_arrive(min(bar + (B_EMPTY + NRING - B_FULL) * 8, S + 63 * 8));
                bar += 24;
                of = of == 8192 * (NRING - 3) ? 0 : of + 24576;
            }
#pragma unroll
            for (int e = 0; e < 4; e++) d[0][e] = (d[0][e] + d[1][e]) + (d[2][e] + d[3][e]);
            if (ph == 2) break;
            const uint32_t k0 = pack_bf(d[0][0], d[0][1]), k1 = pack_bf(d[0][2], d[0][3]);
            if (ph == 1) {
                const uint32_t h0 = movm(bmul(g0, k0)), h1 = movm(bmul(g1, k1)), o = __shfl_xor_sync(~0u, (lane & 1) ? h0 : h1, 1);
                st_rlx2(hp + 64 * (4 * cu + fw) + 31 * (lane & 1) + lane, (((lane & 1) ? o : h0) & ~1u) | tag, (lane & 1) ? h1 : o);
                if (ph1 == 2) return;
            }
            g0 = pack_bf(silu_half(0.5f * bf_lo(k0)), silu_half(0.5f * bf_hi(k0)));
            g1 = pack_bf(silu_half(0.5f * bf_lo(k1)), silu_half(0.5f * bf_hi(k1)));
        }
#pragma unroll
        for (int e = 0; e < 2; e++) {
            const uint32_t ob = mapa(S, 2 * t + e);
            st_async2f(ob + SM_FIN + 256 * r + 64 * fw + 8 * g, d[0][e], d[0][2 + e], ob + B_FIN * 8);
        }
        if (fw < 2) {
            const float xn = bf_round(bf_round(bf_lo(xr) - bf_lo(s2)) * rcpf(bf_hi(s2)));
            mbar_wait(S + B_FIN * 8, 0);
            float y[8];
#pragma unroll
            for (int e = 0; e < 8; e++) y[e] = __uint_as_float(lds32(S + SM_FIN + 256 * e + 4 * i));
            const float v = bf_round(xn + bf_round(bf_round(((y[0] + y[1]) + (y[2] + y[3])) + ((y[4] + y[5]) + (y[6] + y[7]))) * bf_hi(sr.x)));
            st_rlx(&p.s->gt[D_ * r + col], pack_bf(0.f, silu_half(0.5f * v)) | tag);
        }
        return;
    }

    mbar_wait(S + B_X * 8, 0);
    if (k < nch) {
        const uint32_t cb = S + SM_CH + k * CH, bx = cb + BOX + 16;
        bar_sync(1 + k, 64);
        float u[4][4], v[4][4], w[4][4];
#pragma unroll
        for (int i = 0; i < 4; i++) v[i][0] = v[i][1] = v[i][2] = v[i][3] = w[i][0] = w[i][1] = w[i][2] = w[i][3] = 0.f;
        uint2 T4[10];
        const uint32_t ta = cb + FT + 4 * (g - t);
#pragma unroll
        for (int e = 0; e < 10; e++) T4[e] = lds64(ta + 24 + 32 * e + 4 * (g - t));
        const uint32_t tb = prmt(lds32(cb + FT + 308), 0, g == 2 * t ? 0x4432 : (g == 2 * t + 1 ? 0x3244 : 0x4444));
        const uint32_t a0 = bx + 576 * (j & 1) + 16 * (j >> 1), a4 = a0 + (mi == 1 ? 1152 : (mi == 2 ? 1136 : 0));
        const uint32_t a8 = a0 + 2304 + 1152 * (mi & 1) + 64 * (mi >> 1), at = bx + 4608 + 576 * (mi & 1) + 128 * (mi >> 1) + 16 * j;
        const uint32_t hb = bx + (lane < 2 ? 1152 + 576 * lane : 2896), o = bx + 16 * lane;
        uint32_t xi = cb + xslot(8 + lane, 0), xp = cb + xslot(7 + lane, 0), hs = cb + XX;
#pragma unroll 1
        for (int n = 9; n > 0; n -= 4) {
            {
                const uint4 hv = lds128(hs);
                hs = hb + 496;
                const uint2 v0 = lds64(xp + 8);
                const uint4 v1 = lds128(xp ^ 32), v2 = lds128(xi), v3 = lds128(xi ^ 32);
                xi += 1024; xp += 1024;
                __syncwarp();
                if (lane < 3) sts128(hb - 16, hv.x, hv.y, hv.z, hv.w);
                const uint32_t P[13] = {v0.x, v0.y, v1.x, v1.y, v1.z, v1.w, v2.x, v2.y, v2.z, v2.w, v3.x, v3.y, v3.z};
                uint32_t Q[12], s2[12], s4[10], b3[11], b5[9];
#pragma unroll
                for (int e = 0; e < 12; e++) { Q[e] = prmt(P[e], P[e + 1], 0x5432); s2[e] = hadd(P[e], Q[e]); }
#pragma unroll
                for (int e = 0; e < 11; e++) b3[e] = hadd(Q[e], s2[e + 1]);
#pragma unroll
                for (int e = 0; e < 10; e++) s4[e] = hadd(s2[e], s2[e + 1]);
#pragma unroll
                for (int e = 0; e < 9; e++) b5[e] = hadd(s4[e + 1], P[e + 3]);
                sts128(o, b3[3], b3[4], b3[5], b3[6]);
                sts128(o + 1152, b3[7], b3[8], b3[9], b3[10]);
                sts128(o + 576, b5[0], b5[1], b5[2], b5[3]);
                sts128(o + 1728, b5[4], b5[5], b5[6], b5[7]);
                if (n > 4) {
                    sts128(o + 4608, s2[4], s2[5], s2[6], s2[7]);
                    sts128(o + 5184, s2[8], s2[9], s2[10], s2[11]);
                    sts128(o + 2304, hadd(b3[0], s4[2]), hadd(b3[1], s4[3]), hadd(b3[2], s4[4]), hadd(b3[3], s4[5]));
                    sts128(o + 3456, hadd(b3[4], s4[6]), hadd(b3[5], s4[7]), hadd(b3[6], s4[8]), hadd(b3[7], s4[9]));
                    sts128(o + 4032, hadd(s4[0], b5[1]), hadd(s4[1], b5[2]), hadd(s4[2], b5[3]), hadd(s4[3], b5[4]));
                    sts128(o + 2896, hadd(s4[4], b5[5]), hadd(s4[5], b5[6]), hadd(s4[6], b5[7]), hadd(s4[7], b5[8]));
                }
                __syncwarp();
            }
            uint32_t A[8][4];
#pragma unroll
            for (int e = 0; e < 8; e++) ldm4t(a4 + 64 * e, A[e]);
#pragma unroll
            for (int e = 0; e < 8; e++)
#pragma unroll
                for (int b = 3; b >= e / 2; b--) {
                    const uint2 T = T4[2 * (b - e / 2) + 1 - (e & 1)];
                    if (e == 0) mma_hc(u[b], v[b], A[e][0], A[e][1], A[e][2], A[e][3], T.x, T.y);
                    else mma_h(u[b], A[e][0], A[e][1], A[e][2], A[e][3], T.x, T.y);
                }
            if (n == 9) mbar_wait(S + (B_X + 1) * 8, 0);
#pragma unroll
            for (int e = 0; e < 2; e++)
                stm4t(cb + TAB + 2304 - 256 * n + 512 * e + 16 * lane, pack_h(u[2 * e][0], u[2 * e][1]), pack_h(u[2 * e][2], u[2 * e][3]),
                      pack_h(u[2 * e + 1][0], u[2 * e + 1][1]), pack_h(u[2 * e + 1][2], u[2 * e + 1][3]));
            __syncwarp();
            sts32v(S + SM_PROG + 4 * k, n);
            if (n == 1) break;
            uint32_t C[4][4], E[2][4], T8[16];
#pragma unroll
            for (int e = 0; e < 4; e++) ldm4t(a8 + 128 * e, C[e]);
#pragma unroll
            for (int e = 0; e < 2; e++) ldm4t(at + 256 * e, E[e]);
#pragma unroll
            for (int e = 0; e < 8; e++) T8[e] = lds32(ta + 376 + 32 * (e >> 1) - 16 * (e & 1));
#pragma unroll
            for (int e = 7; e >= 0; e--)
#pragma unroll
                for (int b = 0; b <= e / 2; b++) {
                    const uint2 T = T4[2 * (4 + b - e / 2) + 1 - (e & 1)];
                    if (e == 7) mma_hc(v[b], w[b], A[e][0], A[e][1], A[e][2], A[e][3], T.x, T.y);
                    else mma_h(v[b], A[e][0], A[e][1], A[e][2], A[e][3], T.x, T.y);
                }
#pragma unroll
            for (int e = 3; e >= 0; e--) {
                mma_h8(v[e], E[e >> 1][2 * (e & 1)], E[e >> 1][2 * (e & 1) + 1], tb);
#pragma unroll
                for (int b = 3; b >= e; b--) mma_h(v[b], C[e][0], C[e][1], C[e][2], C[e][3], T8[2 * (b - e)], T8[2 * (b - e) + 1]);
            }
            if (n == 9) {
#pragma unroll
                for (int e = 8; e < 16; e++) T8[e] = lds32(ta + 376 + 32 * (e >> 1) - 16 * (e & 1));
#pragma unroll
                for (int e = 3; e >= 0; e--)
#pragma unroll
                    for (int b = 0; b < 4; b++) mma_h(w[b], C[e][0], C[e][1], C[e][2], C[e][3], T8[2 * (4 + b - e)], T8[2 * (4 + b - e) + 1]);
            }
        }
    }

  {
    int lane;
    asm volatile("mov.u32 %0, %%laneid;" : "=r"(lane));
    const int g = lane >> 2, t = lane & 3, mi = lane >> 3, j = lane & 7, sh = (cbase >> 3) & 1;
    mbar_wait(S + B_SEL * 8, 0);
    if (warp == 12) {
        const uint2 sv = lds64(S + SM_SEL + 8 * j);
        uint32_t own = __ballot_sync(~0u, ((sv.x >> 8) & 7) == r) & 255;
        const int e = (lane * 26) >> 8, l = min(lane - 10 * e, 2 * nch - 1);
        const uint32_t tag = epoch + 1;
        st_rlx(&p.s->ep[bid * 8], tag);
#pragma unroll 1
        while (own) {
            const uint32_t o1 = own & (own - 1), o2 = o1 & (o1 - 1), o = e == 1 ? o1 : (e == 2 ? o2 : own);
            const int tk = __ffs(o ? o : own) - 1;
            own = o2 & (o2 - 1);
            const uint32_t ix = __shfl_sync(~0u, sv.x, tk), row = __shfl_sync(~0u, sv.y, tk);
            uint4 v;
#pragma unroll 1
            for (int it = 0; it < SPIN_LIMIT; it++) {
                v = ld_rlx4(&p.s->gt[D_ * tk + cbase + 4 * l]);
                if (!((((v.x ^ tag) | (v.y ^ tag)) | ((v.z ^ tag) | (v.w ^ tag))) & 1)) break;
                __nanosleep(32);
            }
            mbar_wait(S + B_Y * 8 + ((ix >> 2) & 56), 0);
            const uint32_t yb = S + SM_CH + YIN + (l >> 1) * CH + 16 * (ix & 0xE0) + 256 * (l & 1) + 16 * (((ix >> 3) ^ (l + 2 * sh)) & 3) + 2 * (ix & 7);
            const uint2 x = lds64(S + SM_RAW + (16 * (ix & 12) + ((ix >> 2) & 60) + (ix & 3)) * PITCH + 8 * l);
            *(uint2*)(p.out + row * D_ + cbase + 4 * l) = make_uint2(bfma(lds16(yb) | (lds16(yb + 64) << 16), prmt(v.x, v.y, 0x7632), x.x),
                                                                     bfma(lds16(yb + 128) | (lds16(yb + 192) << 16), prmt(v.z, v.w, 0x7632), x.y));
            __syncwarp();
        }
        return;
    }
    const uint32_t skip = lds32(S + SM_SKIP + 4 * g);
#pragma unroll 1
    for (int c = warp == 15 ? 0 : k; c <= k && c < 2 * nch - 4; c++) {
        const int u = c & 1, kk = (c & 6) - sh, q0 = warp == 15 ? 0 : p.tn.split;
        int n = (c == k ? 8 : p.tn.split) - q0;
        uint32_t xa = S + SM_RAW + (16 * (g & 4) + (g & 3) + 4 * u + 8 * q0) * PITCH + 8 * t + 16 * kk, sa = S + SM_ST + 128 * u + 8 * g + 256 * q0, bar = S + (B_Y + q0) * 8;
        uint32_t ya = S + SM_CH + YIN + ((j >> 2) + kk) * CH + 128 * (j & 2) + 128 * (mi & 1) + 64 * (j & 1) + 16 * ((mi >> 1) ^ (j >> 1) ^ (2 * u)) + 512 * q0;
        uint32_t sk = (unsigned)(kk + (t >> 1)) < (unsigned)nch ? skip >> (2 * u + 4 * q0) : ~0u;
        char* o = (char*)p.out + ((256 * q0 - 256 + 32 * r + 16 * u + 4 * (g & 2) + 2 * (g >> 2) + (g & 1)) * D_ + cbase + 8 * kk + 4 * t) * 2;
#pragma unroll 1
        for (; n > 0; n--) {
            uint2 x[2];
            uint32_t gt[4], y[4];
#pragma unroll
            for (int e = 0; e < 2; e++) {
                x[e] = lds64(xa + 128 * e * PITCH);
                const uint2 s = lds64(sa + 64 * e);
                const float a = __uint_as_float(s.x), b = __uint_as_float(s.y);
                gt[2 * e] = pack_bf(silu_half(fmaf(bf_lo(x[e].x), a, b)), silu_half(fmaf(bf_hi(x[e].x), a, b)));
                gt[2 * e + 1] = pack_bf(silu_half(fmaf(bf_lo(x[e].y), a, b)), silu_half(fmaf(bf_hi(x[e].y), a, b)));
            }
            mbar_wait(bar | ((gt[0] | gt[1] | gt[2] | gt[3]) & p.tn.zero), 0);
            ldm4t(ya, y);
            o += 256 * D_ * 2;
#pragma unroll
            for (int e = 0; e < 2; e++)
                asm volatile("{.reg .pred p; setp.eq.u32 p, %3, 0;\n@p st.global.v2.u32 [%0], {%1, %2};}" ::"l"(o + 8 * e * D_), "r"(bfma(y[2 * e], gt[2 * e], x[e].x)),
                             "r"(bfma(y[2 * e + 1], gt[2 * e + 1], x[e].y)), "r"(sk & (1 << e)) : "memory");
            xa += 8 * PITCH; sa += 256; ya += 512; bar += 8; sk >>= 4;
        }
    }
  }
}

typedef CUresult (*EncodeFn)(CUtensorMap*, CUtensorMapDataType, cuuint32_t, void*, const cuuint64_t*, const cuuint64_t*, const cuuint32_t*,
                             const cuuint32_t*, CUtensorMapInterleave, CUtensorMapSwizzle, CUtensorMapL2promotion, CUtensorMapFloatOOBfill);

static void make2d(EncodeFn enc, CUtensorMap* m, const void* base, uint64_t cols, uint64_t rows) {
    cuuint64_t gd[2] = {cols, rows};
    cuuint64_t gs[1] = {cols * 2};
    cuuint32_t bd[2] = {64, 64}, es[2] = {1, 1};
    enc(m, CU_TENSOR_MAP_DATA_TYPE_BFLOAT16, 2, const_cast<void*>(base), gd, gs, bd, es, CU_TENSOR_MAP_INTERLEAVE_NONE, CU_TENSOR_MAP_SWIZZLE_128B,
        CU_TENSOR_MAP_L2_PROMOTION_L2_128B, CU_TENSOR_MAP_FLOAT_OOB_FILL_NONE);
}

static void make5d(EncodeFn enc, CUtensorMap* m, const void* base, uint32_t cols, CUtensorMapSwizzle sw) {
    cuuint64_t gd[5] = {D_, 2, 32, 8, 4};
    cuuint64_t gs[4] = {D_ * 2, D_ * 16, D_ * 512, D_ * 4};
    cuuint32_t bd[5] = {cols, 2, 4, 8, 4}, es[5] = {1, 1, 1, 1, 1};
    enc(m, CU_TENSOR_MAP_DATA_TYPE_BFLOAT16, 5, const_cast<void*>(base), gd, gs, bd, es, CU_TENSOR_MAP_INTERLEAVE_NONE, sw,
        CU_TENSOR_MAP_L2_PROMOTION_NONE, CU_TENSOR_MAP_FLOAT_OOB_FILL_NONE);
}

static Tune g_tune = {2400, 6, 2200, 0, 1, 2, 3, 8, 6000, 100, 0};

static int max_clusters() {
    cudaFuncSetAttribute(fused_kernel, cudaFuncAttributeMaxDynamicSharedMemorySize, SM_TOTAL);
    cudaLaunchConfig_t cfg = {};
    cudaLaunchAttribute at[1];
    at[0].id = cudaLaunchAttributeClusterDimension;
    at[0].val.clusterDim.x = 8; at[0].val.clusterDim.y = 1; at[0].val.clusterDim.z = 1;
    cfg.gridDim = dim3(NCTA); cfg.blockDim = dim3(NTHREADS); cfg.dynamicSmemBytes = SM_TOTAL; cfg.attrs = at; cfg.numAttrs = 1;
    int n = 0;
    if (cudaOccupancyMaxActiveClusters(&n, fused_kernel, &cfg) != cudaSuccess) { cudaGetLastError(); n = 0; }
    return n;
}

static void launch(void* const* d_in, void* d_out) {
    static EncodeFn enc = nullptr;
    static Scratch* gs = nullptr;
    if (!enc) {
        void* fn = nullptr;
        cudaDriverEntryPointQueryResult qr;
        cudaGetDriverEntryPoint("cuTensorMapEncodeTiled", &fn, cudaEnableDefault, &qr);
        enc = (EncodeFn)fn;
        cudaFuncSetAttribute(fused_kernel, cudaFuncAttributeMaxDynamicSharedMemorySize, SM_TOTAL);
        cudaGetSymbolAddress((void**)&gs, g_s);
    }
    Hot p;
    Maps m;
    auto in = [&](int i) { return (const __nv_bfloat16*)d_in[i]; };
    p.u = in(0); p.are = in(1); p.aim = in(2); p.bre = in(3); p.bim = in(4); p.cre = in(5); p.cim = in(6);
    p.logdt = in(7); p.dskip = in(8); p.wr = in(10);
    p.out = (__nv_bfloat16*)d_out;
    p.tn = g_tune;
    p.s = gs;
    make2d(enc, &m.w[0], in(11), F_, D_);
    make2d(enc, &m.w[1], in(12), F_, D_);
    make2d(enc, &m.w[2], in(13), D_, F_);
    make5d(enc, &m.u, in(0), 40, CU_TENSOR_MAP_SWIZZLE_NONE);
    fused_kernel<<<NCTA, NTHREADS, SM_TOTAL>>>(p, m);
}

}

namespace v2 {

constexpr int L_ = 2048, D_ = 576, F_ = 4608;
constexpr int NDOWN = 72, NMAIN = 128, NCTA = 132, NTHREADS = 512;
constexpr int SPIN_LIMIT = 1 << 16;
constexpr uint32_t SLOT_FREE = 0x7FFFABCDu;

constexpr int SM_PART = 544;
constexpr int SM_RED = SM_PART;
constexpr int SM_STA = 2080;
constexpr int SM_ONES = 2176;
constexpr int SM_KINF = 2192;
constexpr int SM_RP = 2272;
constexpr int SM_XS = 2704;
constexpr int KR_STRIDE = 1296;
constexpr int SM_X0 = 12080, X0_STRIDE = 4512, X0_ODD = 2240;
constexpr int SM_KT = 30128, KT_STRIDE = 3584, KT_P4 = 2144, KT_P8 = 2896;
constexpr int SM_FAR = 44544, FAR_STRIDE = 11328;
constexpr int FB5 = 0, FB3 = 3328, FB9E = 6656, FB9O = 7824, FB7E = 8992, FB7O = 10160;
constexpr int SM_ROWS = SM_FAR, ROW_STRIDE = 1168;
constexpr int SM_STG = SM_FAR + 19968;
constexpr int KG_SCR = 3072;
constexpr int SM_EX = 89856;
constexpr int EX_KT = SM_EX + X0_STRIDE, EX_FAR = EX_KT + KT_STRIDE, EX_HAND = 109312;
constexpr int SM_W_DOWN = 90112, SM_W_BIG = 121856, STAGE = 6144;
constexpr int SM_W_LAST = 12288;
constexpr int SM_TOTAL = 232448;
constexpr int SM_EPOCH = 2528, SM_SKIP = 2536;
static_assert(SM_STG + 8 * KG_SCR <= SM_EX && SM_STG % 128 == 0 && EX_HAND % 128 == 0 && EX_FAR + FAR_STRIDE <= EX_HAND && EX_HAND + 12288 <= SM_W_BIG, "scratch");

enum { B_ROWS = 0, B_KG, B_X0, B_X1, B_BOX  , B_TAB, B_EM = 6, B_SP = 10, B_OUT = 14, B_H = 15, B_RED = 16, B_TAB1 = 17, B_XS = 18, B_GX = 19, B_YIN = 22, B_P1 = 26, B_FD, B_GU = 28, B_W = 34, B_COUNT = 58 };

struct Tune { short f_start, f_t3, w2, w2b, w3, t_xs, t_svc, t_marg, f_t2, w1, zero, pad; };

struct Scratch {
    uint32_t x[144 * 4096];
    uint32_t y[128 * 4608];
    uint32_t h[2][F_ * 4];
    uint32_t key[L_];
    uint32_t stat[L_];
    uint32_t sel[4][32];
    uint32_t cnt[17 * 32];
};
__device__ __align__(1024) Scratch g_s;

struct Hot {
    const __nv_bfloat16* u;
    Scratch* s;
    const __nv_bfloat16 *wr, *are, *aim, *bre, *bim, *cre, *cim, *logdt;
    Tune tn;
    const __nv_bfloat16 *dskip, *pwg, *pwu, *pwd;
    __nv_bfloat16* out;
};
struct Maps { CUtensorMap wg, wu, wd; };

__device__ __forceinline__ uint32_t smem_u32(const void* p) { return (uint32_t)__cvta_generic_to_shared(p); }
__device__ __forceinline__ void mbar_init(uint32_t b, int c) { asm volatile("mbarrier.init.shared::cta.b64 [%0], %1;" ::"r"(b), "r"(c) : "memory"); }
__device__ __forceinline__ void mbar_expect(uint32_t b, int bytes) { asm volatile("mbarrier.arrive.expect_tx.shared::cta.b64 _, [%0], %1;" ::"r"(b), "r"(bytes) : "memory"); }
__device__ __forceinline__ void mbar_arrive(uint32_t b) { asm volatile("mbarrier.arrive.shared::cta.b64 _, [%0];" ::"r"(b) : "memory"); }
__device__ __forceinline__ bool elect() { uint32_t d; asm volatile("{.reg .pred p; elect.sync _|p, 0xffffffff; selp.u32 %0,1,0,p;}" : "=r"(d)); return d; }
__device__ __forceinline__ bool mbar_test(uint32_t b, int par) {
    uint32_t d;
    asm volatile("{.reg .pred p; mbarrier.test_wait.parity.shared::cta.b64 p, [%1], %2; selp.u32 %0,1,0,p;}" : "=r"(d) : "r"(b), "r"(par) : "memory");
    return d;
}
#define WAIT_LOOP(ins) "{\n.reg .pred p;\n.reg .u32 n;\nmov.u32 n, 0;\nLW:\n" ins " p, [%0], %1;\n@p bra LD;\nadd.u32 n, n, 1;\nsetp.lt.u32 p, n, 16384;\n@p bra LW;\nLD:\n}"
__device__ __forceinline__ void mbar_wait(uint32_t b, int par) { asm volatile(WAIT_LOOP("mbarrier.try_wait.parity.shared::cta.b64")::"r"(b), "r"(par) : "memory"); }
__device__ __forceinline__ uint32_t mapa(uint32_t a, uint32_t rank) { uint32_t d; asm("mapa.shared::cluster.u32 %0, %1, %2;" : "=r"(d) : "r"(a), "r"(rank)); return d; }
__device__ __forceinline__ void bulk_g2s(uint32_t dst, const void* src, int bytes, uint32_t bar) {
    asm volatile("cp.async.bulk.shared::cluster.global.mbarrier::complete_tx::bytes [%0], [%1], %2, [%3];" ::"r"(dst), "l"(src), "r"(bytes), "r"(bar) : "memory");
}
__device__ __forceinline__ void tma2d(uint32_t dst, const CUtensorMap* m, int c0, int c1, uint32_t bar) {
    asm volatile("cp.async.bulk.tensor.2d.shared::cluster.global.mbarrier::complete_tx::bytes [%0], [%1, {%3, %4}], [%2];" ::"r"(dst), "l"(m), "r"(bar), "r"(c0), "r"(c1) : "memory");
}
__device__ __forceinline__ void pf_tmap(const CUtensorMap* m) { asm volatile("prefetch.tensormap [%0];" ::"l"(m) : "memory"); }
__device__ __forceinline__ void bar_sync(int id, int n) { asm volatile("bar.sync %0, %1;" ::"r"(id), "r"(n) : "memory"); }
__device__ __forceinline__ uint4 ld_rlx4(const void* p) { uint4 v; asm volatile("ld.relaxed.gpu.global.v4.u32 {%0,%1,%2,%3}, [%4];" : "=r"(v.x), "=r"(v.y), "=r"(v.z), "=r"(v.w) : "l"(p) : "memory"); return v; }
__device__ __forceinline__ uint32_t ld_rlx(const void* p) { uint32_t v; asm volatile("ld.relaxed.gpu.global.u32 %0, [%1];" : "=r"(v) : "l"(p) : "memory"); return v; }
__device__ __forceinline__ void st_rlx(void* p, uint32_t v) { asm volatile("st.relaxed.gpu.global.u32 [%0], %1;" ::"l"(p), "r"(v) : "memory"); }
__device__ __forceinline__ uint32_t lds32(uint32_t a) { uint32_t v; asm volatile("ld.shared.u32 %0, [%1];" : "=r"(v) : "r"(a) : "memory"); return v; }
__device__ __forceinline__ uint32_t lds32v(uint32_t a) { uint32_t v; asm volatile("ld.volatile.shared.u32 %0, [%1];" : "=r"(v) : "r"(a) : "memory"); return v; }
__device__ __forceinline__ uint4 lds128v(uint32_t a) { uint4 v; asm volatile("ld.volatile.shared.v4.u32 {%0,%1,%2,%3}, [%4];" : "=r"(v.x), "=r"(v.y), "=r"(v.z), "=r"(v.w) : "r"(a) : "memory"); return v; }
__device__ __forceinline__ uint32_t lds16(uint32_t a) { uint16_t v; asm volatile("ld.shared.u16 %0, [%1];" : "=h"(v) : "r"(a) : "memory"); return v; }
__device__ __forceinline__ uint2 lds64(uint32_t a) { uint2 v; asm volatile("ld.shared.v2.u32 {%0,%1}, [%2];" : "=r"(v.x), "=r"(v.y) : "r"(a) : "memory"); return v; }
__device__ __forceinline__ uint4 lds128(uint32_t a) { uint4 v; asm volatile("ld.shared.v4.u32 {%0,%1,%2,%3}, [%4];" : "=r"(v.x), "=r"(v.y), "=r"(v.z), "=r"(v.w) : "r"(a) : "memory"); return v; }
__device__ __forceinline__ void sts16(uint32_t a, uint32_t v) { asm volatile("st.shared.u16 [%0], %1;" ::"r"(a), "h"((uint16_t)v) : "memory"); }
__device__ __forceinline__ void sts32(uint32_t a, uint32_t v) { asm volatile("st.shared.u32 [%0], %1;" ::"r"(a), "r"(v) : "memory"); }
__device__ __forceinline__ void sts64(uint32_t a, uint32_t x, uint32_t y) { asm volatile("st.shared.v2.u32 [%0], {%1,%2};" ::"r"(a), "r"(x), "r"(y) : "memory"); }
__device__ __forceinline__ void sts128(uint32_t a, uint32_t x, uint32_t y, uint32_t z, uint32_t w) { asm volatile("st.shared.v4.u32 [%0], {%1,%2,%3,%4};" ::"r"(a), "r"(x), "r"(y), "r"(z), "r"(w) : "memory"); }
__device__ __forceinline__ void st_async32(uint32_t a, uint32_t v, uint32_t bar) {
    asm volatile("st.async.shared::cluster.mbarrier::complete_tx::bytes.b32 [%0], %1, [%2];" ::"r"(a), "r"(v), "r"(bar) : "memory");
}
__device__ __forceinline__ void ldm4(uint32_t a, uint32_t& r0, uint32_t& r1, uint32_t& r2, uint32_t& r3) {
    asm volatile("ldmatrix.sync.aligned.m8n8.x4.shared.b16 {%0,%1,%2,%3}, [%4];" : "=r"(r0), "=r"(r1), "=r"(r2), "=r"(r3) : "r"(a) : "memory");
}
__device__ __forceinline__ void ldm4t(uint32_t a, uint32_t& r0, uint32_t& r1, uint32_t& r2, uint32_t& r3) {
    asm volatile("ldmatrix.sync.aligned.m8n8.x4.trans.shared.b16 {%0,%1,%2,%3}, [%4];" : "=r"(r0), "=r"(r1), "=r"(r2), "=r"(r3) : "r"(a) : "memory");
}
__device__ __forceinline__ void ldm2(uint32_t a, uint32_t& r0, uint32_t& r1) {
    asm volatile("ldmatrix.sync.aligned.m8n8.x2.shared.b16 {%0,%1}, [%2];" : "=r"(r0), "=r"(r1) : "r"(a) : "memory");
}
__device__ __forceinline__ void stm4(uint32_t a, uint32_t r0, uint32_t r1, uint32_t r2, uint32_t r3) {
    asm volatile("stmatrix.sync.aligned.m8n8.x4.shared.b16 [%0], {%1,%2,%3,%4};" ::"r"(a), "r"(r0), "r"(r1), "r"(r2), "r"(r3) : "memory");
}
__device__ __forceinline__ void mma_bf(float& c0, float& c1, float& c2, float& c3, uint32_t a0, uint32_t a1, uint32_t a2, uint32_t a3, uint32_t b0, uint32_t b1) {
    asm volatile("mma.sync.aligned.m16n8k16.row.col.f32.bf16.bf16.f32 {%0,%1,%2,%3},{%4,%5,%6,%7},{%8,%9},{%0,%1,%2,%3};"
                 : "+f"(c0), "+f"(c1), "+f"(c2), "+f"(c3) : "r"(a0), "r"(a1), "r"(a2), "r"(a3), "r"(b0), "r"(b1));
}
__device__ __forceinline__ void mma_bf(float (&c)[4], uint32_t a0, uint32_t a1, uint32_t a2, uint32_t a3, uint32_t b0, uint32_t b1) { mma_bf(c[0], c[1], c[2], c[3], a0, a1, a2, a3, b0, b1); }
__device__ __forceinline__ void mma_h(float (&c)[4], uint32_t a0, uint32_t a1, uint32_t a2, uint32_t a3, uint32_t b0, uint32_t b1) {
    asm volatile("mma.sync.aligned.m16n8k16.row.col.f32.f16.f16.f32 {%0,%1,%2,%3},{%4,%5,%6,%7},{%8,%9},{%0,%1,%2,%3};"
                 : "+f"(c[0]), "+f"(c[1]), "+f"(c[2]), "+f"(c[3]) : "r"(a0), "r"(a1), "r"(a2), "r"(a3), "r"(b0), "r"(b1));
}
__device__ __forceinline__ void mma_bf8(float (&c)[4], uint32_t a0, uint32_t a1, uint32_t b0) {
    asm volatile("mma.sync.aligned.m16n8k8.row.col.f32.bf16.bf16.f32 {%0,%1,%2,%3},{%4,%5},{%6},{%0,%1,%2,%3};"
                 : "+f"(c[0]), "+f"(c[1]), "+f"(c[2]), "+f"(c[3]) : "r"(a0), "r"(a1), "r"(b0));
}
__device__ __forceinline__ uint32_t pack_bf(float lo, float hi) { uint32_t r; asm("cvt.rn.bf16x2.f32 %0, %1, %2;" : "=r"(r) : "f"(hi), "f"(lo)); return r; }
__device__ __forceinline__ uint32_t pack_h(float lo, float hi) { uint32_t r; asm("cvt.rn.f16x2.f32 %0, %1, %2;" : "=r"(r) : "f"(hi), "f"(lo)); return r; }
__device__ __forceinline__ float bf_lo(uint32_t w) { return __uint_as_float(w << 16); }
__device__ __forceinline__ float bf_hi(uint32_t w) { return __uint_as_float(w & 0xFFFF0000u); }
__device__ __forceinline__ float bf_round(float x) { return bf_lo(pack_bf(x, 0.f)); }
__device__ __forceinline__ uint32_t badd(uint32_t a, uint32_t b) { uint32_t r; asm("add.rn.bf16x2 %0, %1, %2;" : "=r"(r) : "r"(a), "r"(b)); return r; }
__device__ __forceinline__ uint32_t bsub(uint32_t a, uint32_t b) { uint32_t r; asm("sub.rn.bf16x2 %0, %1, %2;" : "=r"(r) : "r"(a), "r"(b)); return r; }
__device__ __forceinline__ uint32_t bmul(uint32_t a, uint32_t b) { uint32_t r; asm("mul.rn.bf16x2 %0, %1, %2;" : "=r"(r) : "r"(a), "r"(b)); return r; }
__device__ __forceinline__ uint32_t bfma(uint32_t a, uint32_t b, uint32_t c) { uint32_t r; asm("fma.rn.bf16x2 %0, %1, %2, %3;" : "=r"(r) : "r"(a), "r"(b), "r"(c)); return r; }
__device__ __forceinline__ uint32_t prmt(uint32_t a, uint32_t b, uint32_t s) { uint32_t r; asm("prmt.b32 %0, %1, %2, %3;" : "=r"(r) : "r"(a), "r"(b), "r"(s)); return r; }
__device__ __forceinline__ float ex2f(float x) { float r; asm("ex2.approx.ftz.f32 %0, %1;" : "=f"(r) : "f"(x)); return r; }
__device__ __forceinline__ float rcpf(float x) { float r; asm("rcp.approx.ftz.f32 %0, %1;" : "=f"(r) : "f"(x)); return r; }
__device__ __forceinline__ float silu_f(float x) { return x * rcpf(1.f + ex2f(-1.4426950408889634f * x)); }
__device__ __forceinline__ uint32_t norm2(uint32_t x, uint32_t m, uint32_t hi, uint32_t lo) { uint32_t d = bsub(x, m); return bfma(d, hi, bmul(d, lo)); }
__device__ __forceinline__ uint32_t clk32() { uint32_t c; asm volatile("mov.u32 %0, %%clock;" : "=r"(c)); return c; }
__device__ __forceinline__ void spin_until(uint32_t t0, int dt) {
#pragma unroll 1
    while ((int)(clk32() - t0) < dt) __nanosleep(32);
}
__device__ __forceinline__ float sqrt_ap(float x) { float r; asm("sqrt.approx.ftz.f32 %0, %1;" : "=f"(r) : "f"(x)); return r; }

__device__ __forceinline__ void cp16(uint32_t dst, const void* src) { asm volatile("cp.async.cg.shared.global [%0], [%1], 16;" ::"r"(dst), "l"(src) : "memory"); }
__device__ __forceinline__ void pf_l2(const void* p) { asm volatile("cp.async.bulk.prefetch.L2.global [%0], 16;" ::"l"(p) : "memory"); }
__device__ __forceinline__ void bulk_s2g(void* dst, uint32_t src, int bytes) {
    asm volatile("cp.async.bulk.global.shared::cta.bulk_group [%0], [%1], %2;" ::"l"(dst), "r"(src), "r"(bytes) : "memory");
}
__device__ __forceinline__ uint32_t ld_acq(const void* p) { uint32_t v; asm volatile("ld.acquire.gpu.global.u32 %0, [%1];" : "=r"(v) : "l"(p) : "memory"); return v; }
__device__ __forceinline__ void red_add(void* p) { asm volatile("red.relaxed.gpu.global.add.u32 [%0], 1;" ::"l"(p) : "memory"); }
__device__ __forceinline__ void fence_async() { asm volatile("fence.proxy.async.shared::cta;" ::: "memory"); }
__device__ __forceinline__ void fence_async_g() { asm volatile("fence.proxy.async.global;" ::: "memory"); }
__device__ __forceinline__ void red_rel(void* p) { asm volatile("red.release.gpu.global.add.u32 [%0], 1;" ::"l"(p) : "memory"); }
__device__ __forceinline__ void wait_count(const uint32_t* p, uint32_t want) {
#pragma unroll 1
    for (int it = 0; it < SPIN_LIMIT && ld_rlx(p) != want; it++) __nanosleep(20);
}
__device__ __forceinline__ uint32_t ld_stat(const uint32_t* p, uint32_t tag) {
    uint32_t v = 0;
#pragma unroll 1
    for (int it = 0; it < SPIN_LIMIT; it++) {
        v = ld_rlx(p);
        if ((v >> 31) == tag) break;
    }
    return v & 0x7FFFFFFFu;
}
__device__ __forceinline__ uint32_t hadd(uint32_t a, uint32_t b) { uint32_t r; asm("add.rn.f16x2 %0, %1, %2;" : "=r"(r) : "r"(a), "r"(b)); return r; }
__device__ __forceinline__ float h_lo(uint32_t w) { return __half2float(__ushort_as_half((unsigned short)w)); }
__device__ __forceinline__ float h_hi(uint32_t w) { return __half2float(__ushort_as_half((unsigned short)(w >> 16))); }
__device__ __forceinline__ uint32_t x0_chunk(uint32_t xb, int c) { return xb + ((c & 1) ? X0_ODD + 120 : 128) + 8 * c; }

struct cf { float x, y; };
__device__ __forceinline__ cf cmul(cf a, cf b) { return {a.x * b.x - a.y * b.y, a.x * b.y + a.y * b.x}; }
__device__ __forceinline__ cf csq(cf a) { return {a.x * a.x - a.y * a.y, (a.x + a.x) * a.y}; }
__device__ __forceinline__ cf cpow_direct(float zr2, float zi, float l) {
    const float mag = ex2f(zr2 * l), th = zi * l;
    return {mag * __cosf(th), mag * __sinf(th)};
}
__device__ __forceinline__ __half2 as_h2(uint32_t v) { return *reinterpret_cast<__half2*>(&v); }
__device__ __forceinline__ uint32_t as_u32(__half2 v) { return *reinterpret_cast<uint32_t*>(&v); }
struct hm { uint32_t v, s; };
__device__ __forceinline__ hm mk_hm(cf a) {
    const uint32_t v = pack_h(a.x, a.y);
    return {v, prmt(v, v, 0x1032) ^ 0x8000u};
}
__device__ __forceinline__ uint32_t hcmul(uint32_t x, hm y) {
    const __half2 xx = as_h2(x);
    return as_u32(__hfma2(__high2half2(xx), as_h2(y.s), __hmul2(__low2half2(xx), as_h2(y.v))));
}

struct KParams { uint32_t are, aim, bre, bim, cre, cim, ldt; };
__device__ __forceinline__ KParams kgen_load(const Hot& p, int ch, int half, int lane) {
    const uint32_t po = ch * 64 + half * 32 + lane;
    KParams k;
    k.are = __ldg((const uint32_t*)p.are + po); k.aim = __ldg((const uint32_t*)p.aim + po);
    k.bre = __ldg((const uint32_t*)p.bre + po); k.bim = __ldg((const uint32_t*)p.bim + po);
    k.cre = __ldg((const uint32_t*)p.cre + po); k.cim = __ldg((const uint32_t*)p.cim + po);
    k.ldt = __ldg((const uint16_t*)p.logdt + ch + (lane & p.tn.zero));
    return k;
}

__device__ __forceinline__ void kgen(KParams kp, uint32_t scr, uint32_t os, int c0, int c1, uint32_t pause) {
    const int lane = threadIdx.x & 31;
    const float dt = bf_round(ex2f(bf_lo(kp.ldt) * 1.4426950408889634f));
    const cf w0 = cmul({bf_lo(kp.cre), bf_lo(kp.cim)}, {dt * bf_lo(kp.bre), dt * bf_lo(kp.bim)});
    const cf w1 = cmul({bf_hi(kp.cre), bf_hi(kp.cim)}, {dt * bf_hi(kp.bre), dt * bf_hi(kp.bim)});
    uint32_t eb = __reduce_max_sync(~0u, __float_as_uint(fmaxf(fmaxf(fabsf(w0.x), fabsf(w0.y)), fmaxf(fabsf(w1.x), fabsf(w1.y))))) & 0x7F800000u;
    eb = min(max(eb, 0x00800000u), 0x7E800000u);
    const float sc = __uint_as_float(0x7F000000u - eb);
    float k0 = c0 ? 0.f : w0.x + w1.x;
#pragma unroll
    for (int o = 16; o > 0; o >>= 1) k0 += __shfl_xor_sync(~0u, k0, o);
    float d[5][4];
#pragma unroll
    for (int i = 0; i < 5; i++) d[i][0] = d[i][1] = d[i][2] = d[i][3] = 0.f;
    const int mi = lane >> 3, j = lane & 7;
    const uint32_t st0 = scr + mi * 128 + ((j ^ mi) << 4), st1 = st0 ^ 64;
    const uint32_t la = scr + (lane & 15) * 128 + (((lane >> 4) ^ j) << 4), lb = scr + j * 128 + ((mi ^ j) << 4);
    auto st = [&](int row, uint32_t a, uint32_t b, uint32_t c, uint32_t e) { stm4(((row & 4) ? st1 : st0) + row * 128, a, b, c, e); };
#pragma unroll 1
    for (int c = c0; c < c1; c++) {
        if (c > c0 && pause) mbar_wait(pause, 0);
        const float zr2 = dt * (c ? bf_hi(kp.are) : bf_lo(kp.are)) * 1.4426950408889634f;
        const float zi = dt * (c ? bf_hi(kp.aim) : bf_lo(kp.aim));
        const cf w = {(c ? w1.x : w0.x) * sc, (c ? w1.y : w0.y) * sc};
        const cf a1 = cpow_direct(zr2, zi, 1.f), a256 = cpow_direct(zr2, zi, 256.f);
        uint32_t a[4][4];
        {
            const cf a16 = cpow_direct(-zr2, zi, -16.f);
            const cf a32 = csq(a16), a48 = cmul(a32, a16), a64 = csq(a32), a128 = csq(a64), a192 = cmul(a128, a64);
            const uint32_t p1 = pack_h(a16.x, a16.y), p2 = pack_h(a32.x, a32.y), p3 = pack_h(a48.x, a48.y);
            const hm q1 = mk_hm(a64), q2 = mk_hm(a128), q3 = mk_hm(a192);
            __syncwarp();
            st(0, 0x00003C00u, p1, p2, p3);
            st(4, q1.v, hcmul(p1, q1), hcmul(p2, q1), hcmul(p3, q1));
            st(8, q2.v, hcmul(p1, q2), hcmul(p2, q2), hcmul(p3, q2));
            st(12, q3.v, hcmul(p1, q3), hcmul(p2, q3), hcmul(p3, q3));
            __syncwarp();
#pragma unroll
            for (int k = 0; k < 4; k++) ldm4(la ^ (k * 32), a[k][0], a[k][1], a[k][2], a[k][3]);
        }
        auto tile = [&](int T, int row) {
#pragma unroll
            for (int kp2 = 0; kp2 < 2; kp2++) {
                uint32_t b0, b1, b2, b3;
                ldm4((lb ^ (kp2 * 64)) + row * 128, b0, b1, b2, b3);
                mma_h(d[T], a[2 * kp2][0], a[2 * kp2][1], a[2 * kp2][2], a[2 * kp2][3], b0, b1);
                mma_h(d[T], a[2 * kp2 + 1][0], a[2 * kp2 + 1][1], a[2 * kp2 + 1][2], a[2 * kp2 + 1][3], b2, b3);
            }
        };
        const cf a2 = csq(a1), a4 = csq(a2), a8 = csq(a4), a12 = cmul(a8, a4);
        const cf u1 = cmul(w, a1), u2 = cmul(w, a2), u3 = cmul(u2, a1), u4 = cmul(w, a4);
        uint32_t v[16];
        v[0] = pack_h(u1.x, u1.y); v[1] = pack_h(u2.x, u2.y); v[2] = pack_h(u3.x, u3.y); v[3] = pack_h(u4.x, u4.y);
        const hm m4 = mk_hm(a4), m8 = mk_hm(a8), m12 = mk_hm(a12);
#pragma unroll
        for (int i = 0; i < 4; i++) { v[4 + i] = hcmul(v[i], m4); v[8 + i] = hcmul(v[i], m8); v[12 + i] = hcmul(v[i], m12); }
        const hm m256 = mk_hm(a256);
        __syncwarp();
#pragma unroll
        for (int i = 0; i < 4; i++) st(4 * i, v[4 * i], v[4 * i + 1], v[4 * i + 2], v[4 * i + 3]);
        st(16, hcmul(v[1], m256), hcmul(v[3], m256), hcmul(v[5], m256), hcmul(v[7], m256));
        st(20, hcmul(v[9], m256), hcmul(v[11], m256), hcmul(v[13], m256), hcmul(v[15], m256));
        __syncwarp();
        tile(0, 0); tile(1, 8); tile(2, 16);
        const cf a512 = csq(a256), a768 = cmul(a512, a256), a1024 = csq(a512);
        const cf a1280 = cmul(a1024, a256), a1536 = csq(a768), a1792 = cmul(a1024, a768);
        const hm m512 = mk_hm(a512), m768 = mk_hm(a768);
        const hm n0 = mk_hm(a1024), n1 = mk_hm(a1280), n2 = mk_hm(a1536), n3 = mk_hm(a1792);
        __syncwarp();
        st(0, hcmul(v[3], m512), hcmul(v[7], m512), hcmul(v[11], m512), hcmul(v[15], m512));
        st(4, hcmul(v[3], m768), hcmul(v[7], m768), hcmul(v[11], m768), hcmul(v[15], m768));
        st(8, hcmul(v[7], n0), hcmul(v[15], n0), hcmul(v[7], n1), hcmul(v[15], n1));
        st(12, hcmul(v[7], n2), hcmul(v[15], n2), hcmul(v[7], n3), hcmul(v[15], n3));
        __syncwarp();
        tile(3, 0); tile(4, 8);
    }
    __syncwarp();
#pragma unroll
    for (int i = 0; i < 5; i++) sts128(os + i * 512 + lane * 16, __float_as_uint(d[i][0]), __float_as_uint(d[i][1]), __float_as_uint(d[i][2]), __float_as_uint(d[i][3]));
    sts64(os + 2560, eb, __float_as_uint(k0));
}

__device__ __forceinline__ void ktables(uint32_t os, int ostep, int np, uint32_t kr, uint32_t kt, uint32_t kinf, int part) {
    const int lane = threadIdx.x & 31, g = lane >> 2, t = lane & 3;
    uint32_t eb = 0;
    float k0 = 0.f, f[4];
#pragma unroll
    for (int q = 0; q < 4; q++) {
        uint2 v = make_uint2(0u, 0u);
        if (q < np) v = lds64(os + q * ostep + 2560);
        eb = max(eb, v.x);
        k0 += __uint_as_float(v.y);
        f[q] = __uint_as_float(v.x);
    }
    const float rs = __uint_as_float(0x7F000000u - eb);
#pragma unroll
    for (int q = 0; q < 4; q++) f[q] *= rs;
#pragma unroll 1
    for (int i = (part & 1) ? 0 : 2; i < ((part & 2) ? 5 : 3); i++) {
        float a0 = 0.f, a1 = 0.f, a2 = 0.f, a3 = 0.f;
        uint4 v[4];
#pragma unroll
        for (int q = 0; q < 4; q++) {
            v[q] = make_uint4(0u, 0u, 0u, 0u);
            if (q < np) v[q] = lds128(os + q * ostep + i * 512 + lane * 16);
        }
#pragma unroll
        for (int q = 0; q < 4; q++) { a0 += __uint_as_float(v[q].x) * f[q]; a1 += __uint_as_float(v[q].y) * f[q]; a2 += __uint_as_float(v[q].z) * f[q]; a3 += __uint_as_float(v[q].w) * f[q]; }
        const int sg = 32 >> max(i - 1, 0);
        const uint32_t o = kr + 4 + (i < 2 ? 16 * i : 256 * i) + sg * g + (i < 3 ? 8 : 128) * (t >> 1) + (i < 4 ? 4 : 64) * (t & 1);
        sts32(o, pack_h(a0, a1));
        sts32(o + 8 * sg, pack_h(a2, a3));
    }
    sts32(kr, pack_h(0.f, k0 * rs));
    __syncwarp();
    if (part & 1) {
        uint32_t w0[4], w1[4], a[2], b[2];
#pragma unroll
        for (int r = 0; r < 4; r++) { w0[r] = lds32(kr + 4 * lane + 128 * r); w1[r] = lds32(kr + 4 * lane + 128 * r + 4); }
#pragma unroll
        for (int r = 0; r < 2; r++) { a[r] = lds32(kr + 512 + 4 * lane + 128 * r); b[r] = lds32(kr + 516 + 4 * lane + 128 * r); }
#pragma unroll
        for (int r = 0; r < 4; r++) sts64(kt + 8 * lane + 256 * r + 32, prmt(w0[r], w0[r], 0x1032), prmt(w0[r], w1[r], 0x3254));
        if (lane == 31) b[1] = pack_h(h_lo(b[1]) - h_hi(b[1]), 0.f);
#pragma unroll
        for (int r = 0; r < 2; r++)
            sts128(kt + 4 * 264 + 16 * lane + 512 * r, prmt(a[r], a[r], (r == 0 && lane == 0) ? 0x1032 : 0x3232), prmt(a[r], a[r], 0x3232), prmt(a[r], b[r], 0x3254), prmt(b[r], b[r], 0x1032));
        if (lane < 24) sts32(kt + 4 * (lane < 8 ? lane : 512 + lane), 0u);
    }
    if (part & 2) {
        const uint32_t k512 = lds16(kr + 2 * 385), k1024 = lds16(kr + 2 * 513);
        if (lane == 0) {
            sts128(kinf, eb, __float_as_uint(h_lo(k512)), k1024, 0u);
            sts16(kr + 2 * 512, pack_h(h_lo(lds16(kr + 2 * 512)) - h_lo(k1024), 0.f));
        }
#pragma unroll
        for (int r = 0; r < 3; r++)
            if (r < 2 || lane < 26) sts128(kt + KT_P4 + 16 * lane + 512 * r, 0u, 0u, 0u, 0u);
        __syncwarp();
        uint32_t x0[5], x1[5], y0[5], y1[5];
#pragma unroll
        for (int r = 0; r < 5; r++) {
            const int m = min(126 + lane + 32 * r, 256);
            x0[r] = lds16(kr + 2 * (257 + m)); x1[r] = lds16(kr + 2 * (259 + m)); y0[r] = lds16(kr + 2 * (385 + m)); y1[r] = lds16(kr + 2 * (387 + m));
        }
#pragma unroll
        for (int r = 0; r < 5; r++) {
            const int m = 126 + lane + 32 * r;
            if (m < 128) x0[r] = y0[r] = 0;
            if (m > 253) x1[r] = 0;
            if (m > 254) y1[r] = 0;
            if (m < 256) sts32(kt + KT_P4 + 4 * (((m - 96) & ~3) | ((m & 1) << 1) | ((m >> 1) & 1)), x0[r] | (x1[r] << 16));
            if (m < 257) sts32(kt + KT_P8 + 4 * (m - 96), y0[r] | (y1[r] << 16));
        }
    }
    __syncwarp();
}

__device__ __forceinline__ void mma_hc(float (&d)[4], const float (&c)[4], uint32_t a0, uint32_t a1, uint32_t a2, uint32_t a3, uint32_t b0, uint32_t b1) {
    asm volatile("mma.sync.aligned.m16n8k16.row.col.f32.f16.f16.f32 {%0,%1,%2,%3},{%4,%5,%6,%7},{%8,%9},{%10,%11,%12,%13};"
                 : "=f"(d[0]), "=f"(d[1]), "=f"(d[2]), "=f"(d[3]) : "r"(a0), "r"(a1), "r"(a2), "r"(a3), "r"(b0), "r"(b1), "f"(c[0]), "f"(c[1]), "f"(c[2]), "f"(c[3]));
}
template <int Q0, int Q1>
__device__ __forceinline__ void sweep_steps(float (&w)[5][4], const uint32_t (&R)[66], uint32_t xa, uint32_t (&x)[5], uint32_t z) {
#pragma unroll
    for (int q = Q0; q <= Q1; q++) {
        uint32_t n0, n1;
        ldm2(xa + 16 * (q + 1), n0, n1);
        const uint32_t a2 = x[0] | z, a3 = x[1] | z;
#pragma unroll
        for (int j = 0; j < 4; j++) {
            const int s = 8 * j + 8 - q;
            if (q == 1) mma_hc(w[j], w[j + 1], x[1], x[2], a2, a3, R[2 * s], R[2 * s + 1]);
            else mma_h(w[j], x[1], x[2], a2, a3, R[2 * s], R[2 * s + 1]);
        }
        if (q == 8) {
            const float zero[4] = {0.f, 0.f, 0.f, 0.f};
            mma_hc(w[4], zero, x[1], x[2], a2, a3, R[64], R[65]);
        }
        x[0] = x[2]; x[1] = x[3]; x[2] = x[4]; x[3] = n0; x[4] = n1;
    }
}

__device__ __forceinline__ void box_round(uint32_t xb, uint32_t fa, int rho, int lane) {
    if (rho == 6) {
        const int a = lane >> 3, j = lane & 7;
        sts128(fa + 3328 * (lane >> 4) + 16 * ((lane & 15) < 15 ? (lane & 15) : 207), 0u, 0u, 0u, 0u);
        sts128(fa + FB9E + 1168 * a + 16 * (j < 7 ? j : 71 + (a & 1)), 0u, 0u, 0u, 0u);
        __syncwarp();
    }
    const int c = rho < 6 ? 32 * rho + lane : -1;
    const uint4 pv = lds128(x0_chunk(xb, c - 1)), ow = lds128(x0_chunk(xb, c));
    const uint2 nx = lds64(x0_chunk(xb, c + 1));
    const uint32_t P[9] = {pv.y, pv.z, pv.w, ow.x, ow.y, ow.z, ow.w, nx.x, nx.y};
    uint32_t Q[8], b3[6], b5[4];
#pragma unroll
    for (int k = 0; k < 8; k++) Q[k] = prmt(P[k], P[k + 1], 0x5432);
#pragma unroll
    for (int k = 0; k < 6; k++) b3[k] = hadd(hadd(Q[k], Q[k + 1]), P[k + 1]);
#pragma unroll
    for (int k = 0; k < 4; k++) b5[k] = hadd(b3[k + 2], hadd(P[k + 2], P[k + 4]));
    sts128(fa + FB5 + 240 + 16 * c, b5[0], b5[1], b5[2], b5[3]);
    sts128(fa + FB3 + 240 + 16 * c, b3[0], b3[1], b3[2], b3[3]);
    if (rho < 4 || rho == 6) {
        uint32_t b7[4], b9[4];
#pragma unroll
        for (int k = 0; k < 4; k++) {
            b7[k] = hadd(b5[k], hadd(Q[k + 1], Q[k + 4]));
            b9[k] = hadd(b7[k], hadd(P[k + 1], P[k + 5]));
        }
        const uint32_t ad = fa + ((c & 1) ? FB9O + 120 : FB9E + 112) + 8 * c;
        sts128(ad, b9[0], b9[1], b9[2], b9[3]);
        sts128(ad + (FB7E - FB9E), b7[0], b7[1], b7[2], b7[3]);
    }
}

__global__ void __cluster_dims__(2, 1, 1) __launch_bounds__(NTHREADS, 1) fused_kernel(const Hot p, const __grid_constant__ Maps m) {
    extern __shared__ __align__(1024) char smem[];
    const uint32_t t0 = clk32();
    const int tid = (threadIdx.x + 32 * 0) & (NTHREADS - 1), lane = tid & 31, warp = __shfl_sync(~0u, tid >> 5, 0), bid = blockIdx.x;
    const uint32_t S = smem_u32(smem), z = (uint32_t)p.tn.zero;
    const bool down = bid < NDOWN, rowcta = bid < NMAIN, big = rowcta && !down;
    const int xd = rowcta ? bid : 142 + ((bid - NMAIN) >> 1);
    const int slot = warp < 8 ? (warp & 3) : 4;
    const bool has = warp < 8 ? (rowcta || (slot >> 1) == (bid & 1)) : (big && warp < 12);
    const int ch = slot < 4 ? 4 * xd + slot : 512 + bid - NDOWN;
    KParams kp;
    if (has) kp = kgen_load(p, ch, warp < 8 ? warp >> 2 : (warp >> 1) & 1, lane);
    if (elect()) {
#pragma unroll 1
        for (int i = warp; i < B_COUNT; i += 16) {
            const uint32_t c = i < 16 ? (uint32_t)((big ? 0x1411115555412290ull : 0x1411114444412290ull) >> (4 * i)) & 15 : 1;
            mbar_init(S + i * 8, c ? c : NTHREADS);
        }
        asm volatile("fence.mbarrier_init.release.cluster;" ::: "memory");
    }
    if (rowcta) {
#pragma unroll 1
        for (int i = tid; i < 1224; i += NTHREADS)
            cp16(S + SM_ROWS + 16 * (i + min((i * 911) >> 16, 16)), i < 1152 ? (const uint4*)p.u + bid * 1152 + i : (const uint4*)p.wr + (i - 1152));
    }
    if (tid >= 256 && tid < 336) {
        const int i = tid - 256;
        if (i < 64 || big) sts128(S + (i < 64 ? SM_X0 + (i >> 4) * X0_STRIDE : SM_EX) + ((i & 8) ? X0_ODD : 0) + 16 * (i & 7), 0u, 0u, 0u, 0u);
    }
    if (tid == 447) sts128(S + SM_ONES, 0x3F803F80u, 0x3F803F80u, 0x3F803F80u, 0x3F803F80u);
    __syncthreads();
    if (rowcta) asm volatile("cp.async.mbarrier.arrive.noinc.shared::cta.b64 [%0];" ::"r"(S + B_ROWS * 8) : "memory");
    if (warp == 15 && lane < 4) mbar_expect(S + (lane < 3 ? B_GX + lane : B_RED) * 8, 256);
    asm volatile("barrier.cluster.arrive.relaxed.aligned;" ::: "memory");
    const int g = lane >> 2, t = lane & 3, mi = lane >> 3, j = lane & 7;
    const uint32_t SW = S + (down ? SM_W_DOWN : SM_W_BIG);
    const int pr = bid >> 1, r = bid & 1, nsl = pr >= 54 ? 3 : 2, sl0 = pr < 54 ? 2 * pr : 3 * pr - 54;

    if (warp == 12) {
        if (elect()) {
            const int ng = 6 * nsl, ns = down ? 24 : ng;
            const CUtensorMap* mg = r ? &m.wu : &m.wg;
            pf_tmap(mg);
            if (down) pf_tmap(&m.wd);
            const uint32_t epoch = ld_rlx(&p.s->cnt[16 * 32]) + 1;
            spin_until(t0, p.tn.f_start);
            int done = 0;
#pragma unroll 1
            for (int s = 0; s < ns; s++) {
                if (s == ng) spin_until(t0, p.tn.f_t3);
                #pragma unroll 1
                for (int it = 0; it < SPIN_LIMIT; it++) {
                    const int w = s >= ng ? p.tn.w3 : ((int)(clk32() - t0) < p.tn.f_t2 ? p.tn.w1 : (nsl == 3 ? p.tn.w2b : p.tn.w2));
                    if (s - done < w) break;
                    if (mbar_test(S + (B_W + done) * 8, 0)) done++;
                    else __nanosleep(32);
                }
                const uint32_t bar = S + (B_W + s) * 8;
                uint32_t dst = SW + s * STAGE;
                if (s == 23) { mbar_wait(S + B_EM * 8, 0); fence_async(); dst = S + SM_W_LAST; }
                mbar_expect(bar, STAGE);
                const int u = (s * 43) >> 8;
                if (s < ng) tma2d(dst, mg, 32 * (sl0 + u), 96 * (s - 6 * u), bar);
                else tma2d(dst, &m.wd, 16 * pr, r * 2304 + 192 * (s - 12), bar);
            }
            if (rowcta) {
                mbar_wait(S + B_FD * 8, 0);
                fence_async();
#pragma unroll 1
                for (int q = 0; q < 4; q++) {
                    wait_count(&p.s->cnt[(8 + q) * 32], epoch * (uint32_t)D_);
                    fence_async_g();
                    mbar_expect(S + (B_YIN + q) * 8, 4608);
                    bulk_g2s(S + SM_STG + q * 4608, p.s->y + (32 * q + (bid >> 2)) * 4608 + (bid & 3) * 1152, 4608, S + (B_YIN + q) * 8);
                }
            }
        }
        return;
    }

    uint32_t epoch = 0;
    if (warp >= 8 || !rowcta) epoch = ld_rlx(&p.s->cnt[16 * 32] + (lane & z)) + 1;
    const uint32_t tag = epoch & 1;
    const int hw = warp < 12 ? warp - 8 : warp - 9;

    if (rowcta && warp >= 8 && warp < 15) {
        const uint32_t ad = S + SM_ROWS + (lane & 15) * ROW_STRIDE + 192 * hw + 16 * (lane >> 4);
        uint32_t wd = j ? S + SM_ROWS + 16 * ROW_STRIDE + 192 * hw + 16 * mi : S + SM_ONES;
        const uint32_t wstep = j ? 64 : 0, ones = 0x3F803F80u | z;
        float d1[4] = {0, 0, 0, 0}, d2[4] = {0, 0, 0, 0}, d3[4] = {0, 0, 0, 0}, d4[4] = {0, 0, 0, 0};
        mbar_wait(S + B_ROWS * 8, 0);
#pragma unroll
        for (int kk = 0; kk < 3; kk++) {
            uint32_t w[4];
            ldm4(wd, w[0], w[1], w[2], w[3]);
            wd += wstep;
#pragma unroll
            for (int e = 0; e < 2; e++) {
                uint32_t a0, a1, a2, a3;
                ldm4(ad + 64 * kk + 32 * e, a0, a1, a2, a3);
                mma_bf(d1, a0, a1, a2, a3, w[2 * e], w[2 * e + 1]);
                mma_bf(d2, a0, a1, a2, a3, a0, a2);
                mma_bf(d3, a0, a1, a2, a3, a1, a3);
                mma_bf(d4, ones, ones ^ z, ones + z, ones - z, w[2 * e], w[2 * e + 1]);
            }
        }
        float* part = (float*)(smem + SM_PART + hw * 256) + g * 4;
        if (t == 0) {
            *(float2*)part = make_float2(d1[0], d1[1]);
            *(float2*)(part + 32) = make_float2(d1[2], d1[3]);
            part[3] = d4[1];
            part[35] = d4[1];
        }
        if (t == (g >> 1)) {
            part[2] = (g & 1) ? d2[1] : d2[0];
            part[34] = (g & 1) ? d3[3] : d3[2];
        }
        bar_sync(1, 192);
        if (hw == 0 && lane < 16) {
            float4 s = *(const float4*)(smem + SM_PART + lane * 16);
#pragma unroll
            for (int w = 1; w < 6; w++) {
                const float4 v = *(const float4*)(smem + SM_PART + w * 256 + lane * 16);
                s.x += v.x; s.y += v.y; s.z += v.z; s.w += v.w;
            }
            const float mean = s.x * (1.f / 576.f);
            const float var = fmaxf(s.z * (1.f / 576.f) - mean * mean, 0.f);
            const uint32_t mm = pack_bf(mean, mean);
            const float mu = bf_lo(mm), sd = bf_round(sqrt_ap(bf_round(bf_round(var) + 1e-5f))), ri = rcpf(sd);
            const uint32_t hi = pack_bf(ri, ri);
            const float rl = ri - bf_lo(hi);
            sts16(S + SM_STA + 2 * lane, mm); sts16(S + SM_STA + 32 + 2 * lane, hi); sts16(S + SM_STA + 64 + 2 * lane, pack_bf(rl, rl));
            const uint32_t rb = pack_bf(0.f, (s.y - mu * s.w) * ri);
            const int row = bid * 16 + lane;
            p.s->stat[row] = (mm & 0xFFFFu) | __float_as_uint(sd) | (tag << 31);
            p.s->key[row] = ((rb ^ (((int)rb >> 31) | 0x80000000u)) & 0xFFFF0000u) | (tag << 15) | (2047 - row);
        }
        bar_sync(1, 192);
        if (tid == 256) mbar_arrive(S + B_P1 * 8);
        {
            const uint2 sm = lds64(S + SM_STA + 8 * t), sh = lds64(S + SM_STA + 32 + 8 * t), sl = lds64(S + SM_STA + 64 + 8 * t);
            const uint32_t at = S + SM_ROWS + (4 * (j >> 1) + (j & 1) + 2 * (mi & 1)) * ROW_STRIDE + 32 * hw + 16 * (mi >> 1);
            uint2* dst = (uint2*)p.s->x + (4 * hw + (g >> 2)) * 2048 + bid * 16 + (g & 3) * 4 + t;
            uint32_t r4[6][4];
#pragma unroll
            for (int n = 5; n >= 0; n--) ldm4t(at + 192 * n, r4[n][0], r4[n][1], r4[n][2], r4[n][3]);
#pragma unroll
            for (int n = 5; n >= 0; n--) {
                uint32_t o[4];
#pragma unroll
                for (int e = 0; e < 4; e++) {
                    const uint32_t v = (e & 1) ? norm2(r4[n][e], sm.y, sh.y, sl.y) : norm2(r4[n][e], sm.x, sh.x, sl.x);
                    o[e] = pack_h(bf_lo(v), bf_hi(v));
                }
                dst[n * 49152] = make_uint2((o[0] & ~1u) | tag, o[1]);
                dst[n * 49152 + 4096] = make_uint2((o[2] & ~1u) | tag, o[3]);
            }
        }
        bar_sync(1, 192);
    }

    if (has) {
        asm volatile("" : "+r"(kp.ldt), "+r"(kp.are), "+r"(kp.aim), "+r"(kp.bre), "+r"(kp.bim), "+r"(kp.cre), "+r"(kp.cim));

        const uint32_t scr = warp < 8 ? S + SM_STG + warp * KG_SCR : S + EX_HAND + hw * KG_SCR;
        kgen(kp, scr, warp < 8 ? scr : S + EX_FAR + hw * 2576, warp < 8 ? 0 : warp & 1, warp < 8 ? 2 : (warp & 1) + 1, rowcta ? S + B_P1 * 8 : 0);
        if (warp >= 8) { __syncwarp(); if (lane == 0) mbar_arrive(S + B_TAB * 8); }
    }
    if (warp < 8 || warp == 15) {
        if (warp < 8 ? has : big) {
            if (warp < 8) bar_sync(4 + slot, 64); else mbar_wait(S + B_TAB * 8, 0);
            ktables(warp < 8 ? S + SM_STG + slot * KG_SCR : S + EX_FAR, warp < 8 ? 4 * KG_SCR : 2576, warp < 8 ? 2 : 4, S + SM_XS + slot * KR_STRIDE,
                    S + (warp < 8 ? SM_KT + slot * KT_STRIDE : EX_KT), S + SM_KINF + slot * 16, warp < 8 ? 1 + (warp >> 2) : 3);
        }
        if (lane == 0) { mbar_arrive(S + B_KG * 8); if (warp == 15) mbar_arrive(S + B_TAB1 * 8); }
    }

    if (!rowcta && warp < 8 && !has) {
        const int w4 = (warp >> 2) * 2 + (warp & 1), i = 32 * w4 + lane;
#pragma unroll 1
        for (int pass = 1; pass < 2; pass++) {
        uint4 k[4];
        if (pass) spin_until(t0, p.tn.t_svc - 1500);
#pragma unroll 1
        for (int it = 0; it < SPIN_LIMIT; it++) {
            if (!pass) {
#pragma unroll
                for (int q = 0; q < 4; q++) k[q] = make_uint4(16 * i + 4 * q, 16 * i + 4 * q + 1, 16 * i + 4 * q + 2, 16 * i + 4 * q + 3);
                break;
            }
            uint32_t bad = 0;
#pragma unroll
            for (int q = 0; q < 4; q++) k[q] = ld_rlx4(&p.s->key[4 * i + 512 * q]);
#pragma unroll
            for (int q = 0; q < 4; q++) bad |= tag ? ~(k[q].x & k[q].y & k[q].z & k[q].w) : (k[q].x | k[q].y | k[q].z | k[q].w);
            if (!(bad & 0x8000u)) break;
            __nanosleep(100);
        }
        const uint32_t sc = S + SM_XS + ((bid & 1) ? 0 : 2) * KR_STRIDE;
        auto pk = [](uint32_t v) { return ((v >> 16) << 11) | (v & 2047u); };
        auto gt = [](uint32_t a, uint32_t b) { return (b - a) >> 31; };
        uint32_t mx = 0;
#pragma unroll
        for (int q = 0; q < 4; q++) {
            k[q] = make_uint4(pk(k[q].x), pk(k[q].y), pk(k[q].z), pk(k[q].w));
            mx = max(max(mx, max(k[q].x, k[q].y)), max(k[q].z, k[q].w));
        }
        bar_sync(1, 128);
        sts32(sc + 4 * i, mx);
        if (i == 0) sts32(sc + 1024, 0u);
        bar_sync(1, 128);
        int rank;
        {
            int c[8] = {0, 0, 0, 0, 0, 0, 0, 0};
#pragma unroll 1
            for (int q = 0; q < 32; q += 4) {
                uint4 v[4];
#pragma unroll
                for (int e = 0; e < 4; e++) v[e] = lds128(sc + 16 * (q + e));
#pragma unroll
                for (int e = 0; e < 4; e++) {
                    c[(2 * e) & 7] += gt(v[e].x, mx); c[(2 * e + 1) & 7] += gt(v[e].y, mx);
                    c[(2 * e + 4) & 7] += gt(v[e].z, mx); c[(2 * e + 5) & 7] += gt(v[e].w, mx);
                }
            }
            rank = ((c[0] + c[1]) + (c[2] + c[3])) + ((c[4] + c[5]) + (c[6] + c[7]));
        }
        if (rank == 7) sts32(sc + 1028, mx);
        bar_sync(1, 128);
        if (rank < 8) {
            const uint32_t lb = lds32(sc + 1028);
            int cq[4];
#pragma unroll
            for (int q = 0; q < 4; q++) cq[q] = (gt(lb, k[q].x) + gt(lb, k[q].y)) + (gt(lb, k[q].z) + gt(lb, k[q].w));
            const int c = 16 - ((cq[0] + cq[1]) + (cq[2] + cq[3]));
            uint32_t pos;
            asm volatile("atom.shared.add.u32 %0, [%1], %2;" : "=r"(pos) : "r"(sc + 1024), "r"(c) : "memory");
            pos = sc + 512 + 4 * pos;
#pragma unroll
            for (int q = 0; q < 4; q++) {
                if (k[q].x >= lb) { sts32(pos, k[q].x); pos += 4; }
                if (k[q].y >= lb) { sts32(pos, k[q].y); pos += 4; }
                if (k[q].z >= lb) { sts32(pos, k[q].z); pos += 4; }
                if (k[q].w >= lb) { sts32(pos, k[q].w); pos += 4; }
            }
        }
        bar_sync(1, 128);
        const int n = lds32(sc + 1024);
        if (i < n) {
            const uint32_t mine = lds32(sc + 512 + 4 * i);
            rank = 0;
#pragma unroll 1
            for (int q = 0; q < n; q += 4) {
                const uint4 v = lds128(sc + 512 + 4 * q);
                rank += ((v.x > mine) + (q + 1 < n && v.y > mine)) + ((q + 2 < n && v.z > mine) + (q + 3 < n && v.w > mine));
            }
            const uint32_t k32 = (mine >> 11) << 16, rb = (k32 ^ ((~(int)k32 >> 31) | 0x80000000u)) & 0xFFFF0000u;
            if (rank < 8 && pass) st_rlx(&p.s->sel[bid - NMAIN][rank], (2047 - (mine & 2047)) | (tag << 15) | (pack_bf(rcpf(1.f + ex2f(-1.4426950408889634f * __uint_as_float(rb))), 0.f) << 16));
        }
        }
    }

    if (warp == 13 || warp == 14) {
        const int i = tid - 416;
        if (i == 0) sts32(S + SM_EPOCH, tag);
        if (rowcta) {
            if (p.tn.t_marg <= 600) {
                const uint32_t back = ld_rlx(p.s->x + 2 * ((4 * hw + 2 + (g >> 2)) * 2048 + bid * 16 + (g & 3) * 4 + t));
                if (back == 0xFFFFFFFFu) __nanosleep(20);
            }
            spin_until(clk32(), p.tn.t_marg);
        } else {
            spin_until(t0, p.tn.t_svc);
        }
        const uint4* xa = (const uint4*)p.s->x + xd * 1024 + i;
        const int e = bid - NDOWN;
        const uint4* xe = (const uint4*)p.s->x + (128 + (e >> 2)) * 1024 + (i >> 1) * 8 + (e & 3) * 2 + (i & 1);
        const uint32_t da = S + SM_X0 + ((i >> 1) & 3) * X0_STRIDE + ((i & 1) ? X0_ODD : 0) + 128 + 16 * (i >> 3);
        const uint32_t de = S + SM_EX + ((i & 1) ? X0_ODD : 0) + 128 + 16 * (i >> 1);
        uint4 v[2][10];
        auto fetch = [&](int half) {
#pragma unroll
            for (int k = 0; k < 10; k++) {
                v[half][k].x = v[half][k].z = tag;
                if (k < 8 || big) v[half][k] = ld_rlx4(k < 8 ? xa + 512 * half + 64 * k : xe + 512 * half + 256 * (k - 8));
            }
        };
        fetch(0); fetch(1);
#pragma unroll
        for (int half = 0; half < 2; half++) {
#pragma unroll 1
            for (int it = 0; it < SPIN_LIMIT; it++) {
                uint32_t bad = 0;
#pragma unroll
                for (int k = 0; k < 10; k++) bad |= (v[half][k].x ^ tag) | (v[half][k].z ^ tag);
                if (!(bad & 1)) break;
                __nanosleep(60);
                fetch(half);
            }
#pragma unroll
            for (int k = 0; k < 10; k++)
                if (k < 8 || big) sts128(k < 8 ? da + 1024 * half + 128 * k : de + 1024 * half + 512 * (k - 8), v[half][k].x & ~1u, v[half][k].y, v[half][k].z & ~1u, v[half][k].w);
            __syncwarp();
            if (lane == 0) mbar_arrive(S + (B_X0 + half) * 8);
        }
    }

    if (warp < 12) {
        const bool cw = warp >= 8;
        if (has) {
            const uint32_t xb = S + (cw ? SM_EX : SM_X0 + slot * X0_STRIDE), kt = S + (cw ? EX_KT : SM_KT + slot * KT_STRIDE);
            const int g0 = cw ? warp - 8 : 0, g1 = cw ? warp - 7 : 4;
            const uint32_t park = (cw ? S + EX_HAND + g0 * 2048 : kt) + lane * 16;
            if (cw) mbar_wait(S + B_TAB1 * 8, 0);
            const uint4 ki = lds128(S + SM_KINF + slot * 16);
            const float inv = __uint_as_float(ki.x);
            if (warp >= 4) {
                const uint32_t fa = S + (cw ? EX_FAR : SM_FAR + slot * FAR_STRIDE);
                mbar_wait(S + (cw ? B_X1 : B_X0) * 8, 0);
                mbar_wait(S + B_KG * 8, 0);
#pragma unroll 1
                for (int rho = cw ? g0 : 0; rho < (cw ? 7 : 4); rho += cw ? 4 : 1) box_round(xb, fa, (!cw && rho == 3) ? 6 : rho, lane);
                if (cw) bar_sync(2, 128); else __syncwarp();
                const int dd = g - 2 * t, gf = g0 ? g0 : 1;
                const uint32_t tb0 = dd == -5 ? ki.z : (dd == -4 ? ki.z << 16 : 0u), tb1 = dd == 3 ? ki.z : (dd == 4 ? ki.z << 16 : 0u);
                uint32_t tad = xb + (mi == 1 ? 144 : mi == 2 ? 128 : X0_ODD + 128) + 16 * j + 512 * gf - 1024;
                uint32_t ad8 = fa + (mi == 0 ? FB9E : mi == 1 ? FB7O : mi == 2 ? FB9O + 16 : FB7E) + 112 - 16 * j + 512 * gf - 768;
                uint32_t ad4 = fa + ((mi & 1) ? FB3 : FB5) + 240 + 16 * (8 * (mi >> 1) - j) + 1024 * gf - 640;
                const uint32_t p4 = kt + KT_P4 + 16 * (g + t), p8 = kt + KT_P8 + 8 * (g + 2 * t);
#pragma unroll 1
                for (int grp = gf; grp < g1; grp++) {
                    float a[4][4], e[2][4], o[2][4];
#pragma unroll
                    for (int k = 0; k < 4; k++) a[0][k] = a[1][k] = a[2][k] = a[3][k] = e[0][k] = e[1][k] = o[0][k] = o[1][k] = 0.f;
                    {
                        if (!cw && grp == 2) {
                            mbar_wait(S + B_X1 * 8, 0);
#pragma unroll 1
                            for (int rho = 3; rho < 6; rho++) box_round(xb, fa, rho, lane);
                            __syncwarp();
                        }
                        {
                            uint4 A4[10];
#pragma unroll
                            for (int s = 0; s < 10; s++) A4[s] = lds128(p4 + 64 * s);
                            auto s4 = [&](int m) {
                                uint32_t b[4];
                                ldm4t(ad4 - 256 * m, b[0], b[1], b[2], b[3]);
#pragma unroll
                                for (int h = 1; h >= 0; h--)
#pragma unroll
                                    for (int i = 0; i < 4; i++) {
                                        const int s = 2 * m - 2 + 2 * i + (1 - h), k = m + (i & 2);
                                        if (k <= 5 && k >= ((i & 1) ? 0 : 1) && !((i & 1) && k == 5)) mma_h(a[i], A4[s >= 0 && s < 10 ? s : 0].x, A4[s >= 0 && s < 10 ? s : 0].y, A4[s >= 0 && s < 10 ? s : 0].z, A4[s >= 0 && s < 10 ? s : 0].w, b[2 * h], b[2 * h + 1]);
                                    }
                            };
                            auto tap = [&](int i) {
                                uint32_t b[4];
                                ldm4(tad + 128 * i, b[0], b[1], b[2], b[3]);
                                mma_h(a[i], b[0], b[1], b[2], b[3], tb1, tb0);
                            };
                            s4(1); s4(0); s4(2); s4(-1); tap(3); s4(-2);
                            if (grp >= 2) { s4(3); tap(0); s4(4); tap(1); s4(5); tap(2); }
                        }
                        {
                            uint32_t A8[9][4];
#pragma unroll
                            for (int k = 0; k < 9; k++) { A8[k][0] = lds32(p8 + 64 * k); A8[k][1] = lds32(p8 + 64 * k + 64); A8[k][2] = lds32(p8 + 64 * k + 4); A8[k][3] = lds32(p8 + 64 * k + 68); }
                            auto s8 = [&](int m) {
                                uint32_t b[4];
                                ldm4t(ad8 - 128 * m, b[0], b[1], b[2], b[3]);
                                mma_h(e[1], A8[m + 2][0], A8[m + 2][1], A8[m + 2][2], A8[m + 2][3], b[0], b[1]);
                                mma_h(o[1], A8[m + 2][0], A8[m + 2][1], A8[m + 2][2], A8[m + 2][3], b[2], b[3]);
                                if (m >= 0) {
                                    mma_h(e[0], A8[m >= 0 ? m : 0][0], A8[m >= 0 ? m : 0][1], A8[m >= 0 ? m : 0][2], A8[m >= 0 ? m : 0][3], b[0], b[1]);
                                    mma_h(o[0], A8[m >= 0 ? m : 0][0], A8[m >= 0 ? m : 0][1], A8[m >= 0 ? m : 0][2], A8[m >= 0 ? m : 0][3], b[2], b[3]);
                                }
                            };
                            s8(-2);
                            if (grp >= 2) {
                                s8(-1); s8(0); s8(1); s8(2);
                                if (grp >= 3) { s8(3); s8(4); s8(5); s8(6); }
                            }
                        }
                    }
                    tad += 512; ad8 += 512; ad4 += 1024;
#pragma unroll
                    for (int pp = 0; pp < 2; pp++) {
                        if (!cw) {
#pragma unroll 1
                            for (int it = 0; it < SPIN_LIMIT && !__all_sync(~0u, lds32v(park + (2 * pp + 1) * 512) == SLOT_FREE); it++) __nanosleep(32);
                        }
#pragma unroll
                        for (int i = 0; i < 2; i++)
                            sts128(park + (2 * pp + i) * 512, __float_as_uint((a[2 * pp + i][0] + e[pp][2 * i]) * inv), __float_as_uint((a[2 * pp + i][1] + e[pp][2 * i + 1]) * inv),
                                   __float_as_uint((a[2 * pp + i][2] + o[pp][2 * i]) * inv), __float_as_uint((a[2 * pp + i][3] + o[pp][2 * i + 1]) * inv));
                    }
                }
            }
            if ((warp & 12) != 4) {
                uint32_t R[66], x[5];
#pragma unroll
                for (int i = 0; i < 66; i++) R[i] = lds32(kt + 4 * (8 + g - 2 * t) + 32 * i);
                float w[5][4];
#pragma unroll
                for (int i = 0; i < 5; i++) w[i][0] = w[i][1] = w[i][2] = w[i][3] = 0.f;
                uint32_t xa = xb + ((lane & 8) ? X0_ODD + 16 : 16) + 16 * j + 512 * g0;
                uint2* yo = (uint2*)p.s->y + (32 * g0 + g) * 2304 + ch * 4 + t;
                mbar_wait(S + B_X0 * 8, 0);
                const uint32_t ytag = lds32(S + SM_EPOCH);
                if (g0 == 0) {
                    const uint32_t x01 = lds32(xb + 128);
                    const float c0 = lane == 31 ? __uint_as_float(ki.y) * inv * h_lo(x01) : 0.f, c1 = lane == 31 ? c0 + __uint_as_float(ki.y) * inv * h_hi(x01) : 0.f;
                    __syncwarp();
#pragma unroll
                    for (int i = 0; i < 4; i++) sts128(park + i * 512, 0u, 0u, i == 3 ? __float_as_uint(c0) : 0u, i == 3 ? __float_as_uint(c1) : 0u);
                }
                ldm2(xa - 16, x[1], x[0]);
                ldm2(xa, x[1], x[2]);
                ldm2(xa + 16, x[3], x[4]);
                uint32_t zz = z, pk = park;
                float sc = inv;
                const bool direct = g0 == 0;
                uint32_t dir = direct;
                asm volatile("" : "+r"(pk));
#pragma unroll 1
                for (int gq = g0; gq < g1; gq++) {
                    uint32_t pa = pk;
#pragma unroll 1
                    for (int n = 4; n > 0; n--) {
                        asm volatile("" : "+r"(zz), "+f"(sc), "+r"(pa), "+r"(dir));
                        sweep_steps<1, 5>(w, R, xa, x, zz);
                        uint4 v = lds128v(pa | (x[4] & zz));
                        sweep_steps<6, 8>(w, R, xa, x, zz);
                        xa += 128;
                        if (__any_sync(~0u, v.x == SLOT_FREE)) {
#pragma unroll 1
                            for (int it = 0; it < SPIN_LIMIT; it++) {
                                v = lds128v(pa);
                                if (!__any_sync(~0u, v.x == SLOT_FREE)) break;
                            }
                        }
                        const float y0 = fmaf(w[0][0], sc, __uint_as_float(v.x)), y1 = fmaf(w[0][1], sc, __uint_as_float(v.y));
                        const float y2 = fmaf(w[0][2], sc, __uint_as_float(v.z)), y3 = fmaf(w[0][3], sc, __uint_as_float(v.w));
                        if (dir) {
                            *yo = make_uint2((pack_bf(y0, y1) & ~1u) | ytag, pack_bf(y2, y3));
                            sts32(pa, SLOT_FREE);
                        } else {
                            sts128(pa, __float_as_uint(y0), __float_as_uint(y1), __float_as_uint(y2), __float_as_uint(y3));
                        }
                        yo += 18432;
                        pa += 512;
                    }
                    if (direct && lane == 0) red_add(&p.s->cnt[(8 + gq) * 32]);
                }
                __syncwarp();
                if (lane == 0) mbar_arrive(S + (direct ? B_EM : B_SP + g0) * 8);
                if (cw && g0 < 3) {
                    mbar_wait(S + (B_SP + g0 + 1) * 8, 0);
#pragma unroll
                    for (int i = 0; i < 4; i++) {
                        const uint4 v = lds128(park + 2048 + i * 512);
                        yo[i * 18432] = make_uint2((pack_bf(fmaf(w[i + 1][0], inv, __uint_as_float(v.x)), fmaf(w[i + 1][1], inv, __uint_as_float(v.y))) & ~1u) | ytag,
                                                   pack_bf(fmaf(w[i + 1][2], inv, __uint_as_float(v.z)), fmaf(w[i + 1][3], inv, __uint_as_float(v.w))));
                    }
                    if (lane == 0) red_add(&p.s->cnt[(8 + g0 + 1) * 32]);
                }
            }
        }
        if (rowcta && (warp & 12) == 4) {
            bar_sync(10, 128);
            const int i = tid - 128, rb0 = 16 * (bid >> 2), c0 = 144 * (bid & 3);
            if (i == 0) mbar_arrive(S + B_FD * 8);
#pragma unroll 3
            for (int v = i; v < 1152; v += 128) {
                const int row = (v * 3641) >> 16, vv = v - 18 * row;
                cp16(S + SM_ROWS + row * 304 + 16 * vv, (const uint4*)(p.u + (size_t)(512 * (row >> 4) + rb0 + (row & 15)) * D_ + c0) + vv);
            }
            if (i < 64) {
                const uint32_t sw = ld_stat(&p.s->stat[512 * (i >> 4) + rb0 + (i & 15)], lds32(S + SM_EPOCH));
                const float ri = rcpf(bf_hi(sw));
                const uint32_t hi = pack_bf(ri, ri);
                const float rl = ri - bf_lo(hi);
                sts128(S + SM_KT + KT_P4 + 16 * i, prmt(sw, sw, 0x1010), hi, pack_bf(rl, rl), 0u);
            }
            asm volatile("cp.async.wait_all;" ::: "memory");
            __syncwarp();
            if (lane == 0) mbar_arrive(S + B_OUT * 8);
        }
        if (!rowcta) return;

        const int rb0 = 16 * (bid >> 2), c0 = 144 * (bid & 3);
        mbar_wait(S + B_OUT * 8, 0);
        mbar_wait(S + B_XS * 8, 0);
        const uint32_t otag = lds32(S + SM_EPOCH) * 0x00010001u;
        const uint2 skip = lds64(S + SM_SKIP);
        const int pi_g = (g & 1) + 8 * ((g >> 1) & 1) + 2 * (g >> 2), pi_j = (j & 1) + 8 * ((j >> 1) & 1) + 2 * (j >> 2);
#pragma unroll 1
        for (int un = warp; un < 36; un += 12) {
            const int q = (un * 57) >> 9, cu = un - 9 * q;
            const uint32_t rw = S + SM_ROWS + 16 * q * 304 + 32 * cu;
            const uint32_t ad = rw + (pi_j + 4 * (mi & 1)) * 304 + 16 * (mi >> 1);
            const uint32_t dk0 = __ldg((const uint32_t*)p.dskip + (c0 >> 1) + 8 * cu + t), dk1 = __ldg((const uint32_t*)p.dskip + (c0 >> 1) + 8 * cu + 4 + t);
            const uint4 sa = lds128(S + SM_KT + KT_P4 + 16 * (16 * q + pi_g)), sb = lds128(S + SM_KT + KT_P4 + 16 * (16 * q + 4 + pi_g));
            uint32_t x[4], tt[4], gt[4], y[4];
            ldm4(ad, x[0], x[1], x[2], x[3]);
#pragma unroll
            for (int e = 0; e < 4; e++) {
                const uint4 s = (e & 1) ? sb : sa;
                const uint32_t xn = norm2(x[e], s.x, s.y, s.z);
                tt[e] = bmul(xn, e < 2 ? dk0 : dk1);
                gt[e] = pack_bf(silu_f(bf_lo(xn)), silu_f(bf_hi(xn)));
            }
            mbar_wait(S + (B_YIN + q) * 8, 0);
            const uint32_t yb = S + SM_STG + q * 4608 + 512 * cu;
#pragma unroll 1
            for (int it = 0; it < SPIN_LIMIT; it++) {
                ldm4t(yb + (8 * (mi >> 1) + j) * 32 + 16 * (mi & 1), y[0], y[1], y[2], y[3]);
                const uint32_t bad = ((y[0] ^ otag) | (y[1] ^ otag) | (y[2] ^ otag) | (y[3] ^ otag)) & 0x00010001u;
                if (!__any_sync(~0u, (g & 3) == 0 && bad)) break;
                const uint4 v = ld_rlx4((const uint4*)(p.s->y + (32 * q + (bid >> 2)) * 4608 + (bid & 3) * 1152 + 128 * cu) + lane);
                __syncwarp();
                sts128(yb + 16 * lane, v.x, v.y, v.z, v.w);
                __syncwarp();
            }
#pragma unroll
            for (int e = 0; e < 4; e++) y[e] = badd(x[e], bmul(badd(y[e], tt[e]), gt[e]));
            stm4(ad, y[0], y[1], y[2], y[3]);
            __syncwarp();
            const int row = lane >> 1;
            const uint4 o = lds128(rw + row * 304 + 16 * (lane & 1));
            if (!((((q & 2) ? skip.y : skip.x) >> (16 * (q & 1) + row)) & 1))
                *((uint4*)(p.out + (size_t)(512 * q + rb0 + row) * D_ + c0 + 16 * cu) + (lane & 1)) = o;
        }
        return;
    }

    {
        const int fw = warp - 13;
        if (fw < nsl) {
            st_rlx(&p.s->h[tag ^ 1][(32 * (sl0 + fw) + 16 * r) * 4 + lane], 0u);
            st_rlx(&p.s->h[tag ^ 1][(32 * (sl0 + fw) + 16 * r) * 4 + 32 + lane], 0u);
        }
        if (fw == 2) {
            spin_until(t0, p.tn.t_xs);
            uint32_t sv = 0;
#pragma unroll 1
            for (int it = 0; it < SPIN_LIMIT; it++) {
                sv = ld_rlx(&p.s->sel[bid & 3][j]);
                if (__all_sync(~0u, ((sv >> 15) & 1) == tag)) break;
                __nanosleep(40);
            }
            mbar_wait(S + B_KG * 8, 0);
            if (lane == 0) { fence_async(); mbar_expect(S + B_BOX * 8, 8 * 1152); }
            __syncwarp();
            if (lane < 8) bulk_g2s(S + SM_XS + lane * ROW_STRIDE, p.u + (size_t)(sv & 2047) * D_, 1152, S + B_BOX * 8);
            const uint32_t st = ld_stat(&p.s->stat[sv & 2047], tag);
            const float ri = rcpf(bf_hi(st));
            const uint32_t hi = pack_bf(ri, ri);
            const float rl = ri - bf_lo(hi);
            if (lane == 0) sts64(S + SM_SKIP, 0u, 0u);
            __syncwarp();
            if (lane < 8) {
                const int row = sv & 2047;
                if (((row >> 4) & 31) == (bid >> 2)) asm volatile("red.shared.or.b32 [%0], %1;" ::"r"(S + SM_SKIP + 4 * (row >> 10)), "r"(1u << (16 * ((row >> 9) & 1) + (row & 15))) : "memory");
                sts32(S + SM_XS + 8 * ROW_STRIDE + 4 * lane, sv);
                sts128(S + SM_RP + 16 * lane, prmt(st, st, 0x1010), hi, pack_bf(rl, rl), 0u);
            }
        }
        asm volatile("barrier.cluster.wait.aligned;" ::: "memory");
        bar_sync(9, 96);
        mbar_wait(S + B_BOX * 8, 0);
#pragma unroll
        for (int k = 0; k < 6; k++) {
            const int v = tid - 416 + 96 * k, tk = (v * 911) >> 16;
            const uint4 x = lds128(S + SM_XS + 16 * (v + tk)), st = lds128(S + SM_RP + 16 * tk);
            sts128(S + SM_XS + 16 * (v + tk), norm2(x.x, st.x, st.y, st.z), norm2(x.y, st.x, st.y, st.z), norm2(x.z, st.x, st.y, st.z), norm2(x.w, st.x, st.y, st.z));
        }
        bar_sync(9, 96);
        if (tid == 416) mbar_arrive(S + B_XS * 8);
        const uint32_t ob = mapa(S, r ^ 1);
        if (fw == 2) {
            if (elect()) {
#pragma unroll 1
                for (int st = 0; st < (down ? 24 : 6 * nsl); st++) {
                    if (st == 12 && down) break;
                    mbar_wait(S + (B_W + st) * 8, 0);
                    if (st % 3 == 2) mbar_arrive(S + (B_GU + st / 3) * 8);
                }
            }
            __syncwarp();
        }
        if (fw < 2) {
            const uint32_t bad = S + SM_XS + j * ROW_STRIDE + mi * 16;
            uint32_t aad = (SW + (8 * (mi >> 1) + j) * 64 + 16 * ((mi & 1) ^ (j >> 1))) ^ ((r ^ fw) * 32);
            uint32_t b[18][4];
#pragma unroll
            for (int k = 0; k < 18; k++) ldm4(bad + 64 * k, b[k][0], b[k][1], b[k][2], b[k][3]);
#pragma unroll 1
            for (int u = 0; u < nsl; u++) {
                float d[4][4];
#pragma unroll
                for (int i = 0; i < 4; i++) d[i][0] = d[i][1] = d[i][2] = d[i][3] = 0.f;
#pragma unroll
                for (int hf = 0; hf < 2; hf++) {
                    mbar_wait(S + (B_GU + 2 * u + hf) * 8, 0);
#pragma unroll
                    for (int sub = 0; sub < 3; sub++) {
                        uint32_t a[6][4];
#pragma unroll
                        for (int k = 0; k < 6; k++) ldm4t(aad + 1024 * k, a[k][0], a[k][1], a[k][2], a[k][3]);
#pragma unroll
                        for (int k = 0; k < 6; k++) {
                            const int kb = 9 * hf + 3 * sub + (k >> 1);
                            mma_bf(d[k & 3], a[k][0], a[k][1], a[k][2], a[k][3], b[kb][2 * (k & 1)], b[kb][2 * (k & 1) + 1]);
                        }
                        aad += STAGE;
                    }
                }
                const uint32_t k0 = pack_bf((d[0][0] + d[1][0]) + (d[2][0] + d[3][0]), (d[0][1] + d[1][1]) + (d[2][1] + d[3][1]));
                const uint32_t k1 = pack_bf((d[0][2] + d[1][2]) + (d[2][2] + d[3][2]), (d[0][3] + d[1][3]) + (d[2][3] + d[3][3]));
                if (fw == 1) {
                    asm volatile("st.async.shared::cluster.mbarrier::complete_tx::bytes.v2.b32 [%0], {%1, %2}, [%3];" ::"r"(ob + SM_PART + u * 256 + lane * 8), "r"(k0), "r"(k1), "r"(ob + (B_GX + u) * 8) : "memory");
                } else {
                    mbar_wait(S + (B_GX + u) * 8, 0);
                    const uint2 o = lds64(S + SM_PART + u * 256 + lane * 8);
#pragma unroll
                    for (int i = 0; i < 2; i++) {
                        const uint32_t mine = i ? k1 : k0, other = i ? o.y : o.x, gb = r ? other : mine, ub = r ? mine : other;
                        uint32_t hv = bmul(pack_bf(silu_f(bf_lo(gb)), silu_f(bf_hi(gb))), ub);
                        if ((hv & 0xFFFFu) == 0) hv |= 0x8000u;
                        if ((hv >> 16) == 0) hv |= 0x80000000u;
                        st_rlx(&p.s->h[tag][(32 * (sl0 + u) + 16 * r) * 4 + 32 * i + lane], hv);
                    }
                    __syncwarp();
                    if (lane < 8) red_add(&p.s->cnt[lane * 32]);
                }
            }
        }
        if (!down) return;

        const int fi = 32 * fw + lane, tok = 4 * r + ((fi >> 4) & 3), cc = 16 * pr + (fi & 15);
        const uint32_t sel = lds32(S + SM_XS + 8 * ROW_STRIDE + 4 * tok);
        const int row = sel & 2047;
        const uint32_t* ya = p.s->y + (row >> 4) * 4608 + cc * 8 + (row & 6);
        const float xraw = __bfloat162float(p.u[(size_t)row * D_ + cc]), dsk = __bfloat162float(p.dskip[cc]);
        const float xn = bf_lo(lds16(S + SM_XS + tok * ROW_STRIDE + 2 * cc));
        if (fw == 0) {
#pragma unroll 1
            for (int st = 12; st < 24; st++) mbar_wait(S + (B_W + st) * 8, 0);
        }
        if (fw == 2 && elect()) wait_count(&p.s->cnt[(bid & 7) * 32], epoch * 288u);
        bar_sync(9, 96);
        float dn[4][4];
        uint2 yv2 = make_uint2(tag ^ 1, 0u);
#pragma unroll 1
        for (int ph = 0; ph < 64; ph++) {
            if (fw == 2 && elect()) {
                fence_async();
                fence_async_g();
                mbar_expect(S + B_H * 8, 36864);
                bulk_g2s(SW, (const char*)p.s->h[tag] + r * 36864, 36864, S + B_H * 8);
            }
            asm volatile("ld.relaxed.gpu.global.v2.u32 {%0,%1}, [%2];" : "=r"(yv2.x), "=r"(yv2.y) : "l"(ya) : "memory");
            mbar_wait(S + B_H * 8, ph & 1);
#pragma unroll
            for (int i = 0; i < 4; i++) dn[i][0] = dn[i][1] = dn[i][2] = dn[i][3] = 0.f;
            uint32_t bq[4] = {~0u, ~0u, ~0u, ~0u};
            const int fr = j + 8 * (mi >> 1);
            uint32_t wa = SW + 12 * STAGE + fw * 2048 + fr * 32 + (((mi & 1) ^ ((fr >> 2) & 1)) << 4), ha = SW + fw * 1024 + lane * 16;
#pragma unroll 1
            for (int s0 = 0; s0 < 12; s0 += 3) {
                uint32_t a[6][8], b[6][4];
#pragma unroll
                for (int s = 0; s < 3; s++) {
                    if (s == 2 && s0 == 9) wa += S + SM_W_LAST - (SW + 23 * STAGE);
#pragma unroll
                    for (int e = 0; e < 2; e++) {
                        ldm4t(ha + e * 512, b[2 * s + e][0], b[2 * s + e][1], b[2 * s + e][2], b[2 * s + e][3]);
                        ldm4t(wa + e * 1024, a[2 * s + e][0], a[2 * s + e][1], a[2 * s + e][2], a[2 * s + e][3]);
                        ldm4t(wa + e * 1024 + 512, a[2 * s + e][4], a[2 * s + e][5], a[2 * s + e][6], a[2 * s + e][7]);
                    }
                    wa += STAGE; ha += 3072;
                }
#pragma unroll
                for (int k = 0; k < 6; k++) {
                    mma_bf(dn[2 * (k & 1)], a[k][0], a[k][1], a[k][2], a[k][3], b[k][0], b[k][1]);
                    mma_bf(dn[2 * (k & 1) + 1], a[k][4], a[k][5], a[k][6], a[k][7], b[k][2], b[k][3]);
#pragma unroll
                    for (int q = 0; q < 4; q++) bq[q] = __vminu2(bq[q], b[k][q]);
                }
            }
            const uint32_t bm = __vminu2(__vminu2(bq[0], bq[1]), __vminu2(bq[2], bq[3])), bd = (bm - 0x00010001u) & ~bm;
            uint32_t anybad;
            asm volatile("{.reg .pred p, q; setp.ne.u32 p, %1, 0; bar.red.or.pred q, 9, 96, p; selp.u32 %0, 1, 0, q;}" : "=r"(anybad) : "r"(bd & 0x80008000u) : "memory");
            if (!anybad) break;
        }
        float* red = (float*)(smem + SM_RED + fw * 512);
        red[(2 * t) * 16 + g] = (dn[0][0] + dn[1][0]) + (dn[2][0] + dn[3][0]);
        red[(2 * t + 1) * 16 + g] = (dn[0][1] + dn[1][1]) + (dn[2][1] + dn[3][1]);
        red[(2 * t) * 16 + g + 8] = (dn[0][2] + dn[1][2]) + (dn[2][2] + dn[3][2]);
        red[(2 * t + 1) * 16 + g + 8] = (dn[0][3] + dn[1][3]) + (dn[2][3] + dn[3][3]);
        bar_sync(9, 96);
        if (fw < 2) {
            const float* rs = (const float*)(smem + SM_RED);
            const int mine = 64 * r + fi, other = mine ^ 64;
            st_async32(ob + SM_RP + 4 * fi, __float_as_uint(rs[other] + rs[128 + other] + rs[256 + other]), ob + B_RED * 8);
            const float s = rs[mine] + rs[128 + mine] + rs[256 + mine];
#pragma unroll 1
            for (int it = 0; it < SPIN_LIMIT && (yv2.x & 1) != tag; it++)
                asm volatile("ld.relaxed.gpu.global.v2.u32 {%0,%1}, [%2];" : "=r"(yv2.x), "=r"(yv2.y) : "l"(ya) : "memory");
            const uint32_t yw = (row & 8) ? yv2.y : yv2.x;
            const float sg = bf_round(((row & 1) ? bf_hi(yw) : bf_lo(yw)) + bf_round(xn * dsk));
            mbar_wait(S + B_RED * 8, 0);
            const float o = *(const float*)(smem + SM_RP + 4 * fi);
            const float yv = bf_round(bf_round(r == 0 ? s + o : o + s) * bf_hi(sel));
            p.out[(size_t)row * D_ + cc] = __float2bfloat16(xraw + bf_round(sg * bf_round(silu_f(bf_round(xn + yv)))));
            if (bid == 0 && fi == 0) st_rlx(&p.s->cnt[16 * 32], epoch);
        }
    }
}

typedef CUresult (*EncodeFn)(CUtensorMap*, CUtensorMapDataType, cuuint32_t, void*, const cuuint64_t*, const cuuint64_t*, const cuuint32_t*,
                             const cuuint32_t*, CUtensorMapInterleave, CUtensorMapSwizzle, CUtensorMapL2promotion, CUtensorMapFloatOOBfill);

static void make2d(EncodeFn enc, CUtensorMap* m, const void* base, uint64_t cols, uint64_t rows, uint32_t bc, uint32_t br, CUtensorMapSwizzle sw) {
    cuuint64_t gd[2] = {cols, rows};
    cuuint64_t gs[1] = {cols * 2};
    cuuint32_t bd[2] = {bc, br}, es[2] = {1, 1};
    enc(m, CU_TENSOR_MAP_DATA_TYPE_BFLOAT16, 2, const_cast<void*>(base), gd, gs, bd, es, CU_TENSOR_MAP_INTERLEAVE_NONE, sw,
        CU_TENSOR_MAP_L2_PROMOTION_L2_128B, CU_TENSOR_MAP_FLOAT_OOB_FILL_NONE);
}

static Tune g_tune = {2000, 9000, 3, 5, 8, 5000, 7500, 0, 9000, 1, 0, 0};


static void launch(void* const* d_in, void* d_out) {
    static EncodeFn enc = nullptr;
    static Scratch* gs = nullptr;
    if (!enc) {
        void* fn = nullptr;
        cudaDriverEntryPointQueryResult qr;
        cudaGetDriverEntryPoint("cuTensorMapEncodeTiled", &fn, cudaEnableDefault, &qr);
        enc = (EncodeFn)fn;
        cudaFuncSetAttribute(fused_kernel, cudaFuncAttributeMaxDynamicSharedMemorySize, SM_TOTAL);
        cudaGetSymbolAddress((void**)&gs, g_s);
    }
    Hot p;
    Maps m;
    auto in = [&](int i) { return (const __nv_bfloat16*)d_in[i]; };
    p.u = in(0); p.are = in(1); p.aim = in(2); p.bre = in(3); p.bim = in(4); p.cre = in(5); p.cim = in(6);
    p.logdt = in(7); p.dskip = in(8); p.wr = in(10); p.pwg = in(11); p.pwu = in(12); p.pwd = in(13);
    p.out = (__nv_bfloat16*)d_out;
    p.tn = g_tune;
    p.s = gs;
    make2d(enc, &m.wg, p.pwg, F_, D_, 32, 96, CU_TENSOR_MAP_SWIZZLE_64B);
    make2d(enc, &m.wu, p.pwu, F_, D_, 32, 96, CU_TENSOR_MAP_SWIZZLE_64B);
    make2d(enc, &m.wd, p.pwd, D_, F_, 16, 192, CU_TENSOR_MAP_SWIZZLE_32B);
    fused_kernel<<<NCTA, NTHREADS, SM_TOTAL>>>(p, m);
}

}

extern "C" void kernel_launch(void* const* d_in, const int* in_sizes, int n_in, void* d_out, int out_size) {
    static int clusters = -1;
    if (clusters < 0) clusters = v3::max_clusters();
    if (clusters >= 15) v3::launch(d_in, d_out);
    else v2::launch(d_in, d_out);
}
```

```cpp
#include <cuda_runtime.h>
#include <cuda_bf16.h>
#include <cuda_fp16.h>
#include <cuda.h>
#include <stdint.h>
#include <stddef.h>
#include <type_traits>


namespace v3 {

constexpr bool LD4 = false, ZZ = true;

constexpr int D_ = 576, F_ = 4608;
constexpr int NCTA = 120, NTHREADS = 512;
constexpr int SPIN_LIMIT = 1 << 16;

enum { B_Y = 0, B_X = 8, B_TOP = 10, B_XS = 12, B_FIN = 13, B_SEL = 14, B_RAW = 15, B_FULL = 16, B_EMPTY = 38  , B_ROWS = 66, B_WR = 67 };
constexpr int SM_SKIP = 544, SM_SEL = 576;
constexpr int SM_ST = 640;
constexpr int SM_RAW = 2688, PITCH = 80;
constexpr int SM_CH = SM_RAW + 256 * PITCH, CH = 18304;
constexpr int TAB = 0, FT = 3072, XX = 3712, BOX = 8064, YIN = 14208;
constexpr int SM_B = SM_CH + 5 * CH, BP = 1168;
constexpr int SM_CAND = SM_B + 8 * BP, SM_PROG = SM_CAND + 256, SM_DUMP = SM_PROG + 128;
constexpr int NRING = 12, SM_W = SM_B + 10240, SM_FIN = SM_W + NRING * 8192, SM_TOTAL = 232448;
static_assert(SM_W % 1024 == 0 && SM_FIN + 6144 <= SM_TOTAL && SM_TOTAL - 18432 >= SM_W + 10 * 8192 && SM_TOTAL - 36864 >= SM_W + 8 * 8192, "smem");

struct Tune { int t_w, win, t_tile, split, stag, tail, win0, s0, t_d, hslp, t_rows, pf, zero; };

struct Scratch {
    uint32_t h[8 * 2304];
    uint2 stat[2048];
    uint32_t ep[NCTA * 8];
};
__device__ __align__(1024) Scratch g_s;

struct Hot {
    const __nv_bfloat16* u;
    int bre, bim, cre, cim, are, aim, logdt, dskip, wr, ep;
    Scratch* s;
    __nv_bfloat16* out;
    Tune tn;
};
struct Maps { CUtensorMap w[3], u; };

__device__ __forceinline__ uint32_t smem_u32(const void* p) { return (uint32_t)__cvta_generic_to_shared(p); }
__device__ __forceinline__ void mbar_init(uint32_t b, int c) { asm volatile("mbarrier.init.shared::cta.b64 [%0], %1;" ::"r"(b), "r"(c) : "memory"); }
__device__ __forceinline__ void mbar_expect(uint32_t b, int bytes) { asm volatile("mbarrier.arrive.expect_tx.shared::cta.b64 _, [%0], %1;" ::"r"(b), "r"(bytes) : "memory"); }
__device__ __forceinline__ void mbar_arrive(uint32_t b) { asm volatile("mbarrier.arrive.shared::cta.b64 _, [%0];" ::"r"(b) : "memory"); }
__device__ __forceinline__ bool elect() { uint32_t d; asm volatile("{.reg .pred p; elect.sync _|p, 0xffffffff; selp.u32 %0,1,0,p;}" : "=r"(d)); return d; }
__device__ __forceinline__ void mbar_wait(uint32_t b, int par) {
    asm volatile("{\n.reg .pred p;\nLW:\nmbarrier.try_wait.parity.shared::cta.b64 p, [%0], %1, 2000;\n@!p bra LW;\n}" ::"r"(b), "r"(par) : "memory");
}
__device__ __forceinline__ uint32_t mapa(uint32_t a, uint32_t rank) { uint32_t d; asm("mapa.shared::cluster.u32 %0, %1, %2;" : "=r"(d) : "r"(a), "r"(rank)); return d; }
__device__ __forceinline__ void tma2d(uint32_t dst, const CUtensorMap* m, int c0, int c1, uint32_t bar) {
    asm volatile("cp.async.bulk.tensor.2d.shared::cluster.global.mbarrier::complete_tx::bytes [%0], [%1, {%3, %4}], [%2];" ::"r"(dst), "l"(m), "r"(bar), "r"(c0), "r"(c1) : "memory");
}
__device__ __forceinline__ void bulk_g2s(uint32_t dst, const void* src, int bytes, uint32_t bar) {
    asm volatile("cp.async.bulk.shared::cluster.global.mbarrier::complete_tx::bytes [%0], [%1], %2, [%3];" ::"r"(dst), "l"(src), "r"(bytes), "r"(bar) : "memory");
}
__device__ __forceinline__ void bulk_mc(uint32_t dst, const void* src, int bytes, uint32_t bar) {
    asm volatile("cp.async.bulk.shared::cluster.global.mbarrier::complete_tx::bytes.multicast::cluster [%0], [%1], %2, [%3], %4;"
                 ::"r"(dst), "l"(src), "r"(bytes), "r"(bar), "h"((uint16_t)255) : "memory");
}
__device__ __forceinline__ void bar_sync(int id, int n) { asm volatile("bar.sync %0, %1;" ::"r"(id), "r"(n) : "memory"); }
__device__ __forceinline__ void bar_arrive(int id, int n) { asm volatile("bar.arrive %0, %1;" ::"r"(id), "r"(n) : "memory"); }
__device__ __forceinline__ uint4 ld_rlx4(const void* p) { uint4 v; asm volatile("ld.relaxed.gpu.global.v4.u32 {%0,%1,%2,%3}, [%4];" : "=r"(v.x), "=r"(v.y), "=r"(v.z), "=r"(v.w) : "l"(p) : "memory"); return v; }
__device__ __forceinline__ uint2 ld_rlx2(const void* p) { uint2 v; asm volatile("ld.relaxed.gpu.global.v2.u32 {%0,%1}, [%2];" : "=r"(v.x), "=r"(v.y) : "l"(p) : "memory"); return v; }
__device__ __forceinline__ uint32_t ld_rlx(const void* p) { uint32_t v; asm volatile("ld.relaxed.gpu.global.u32 %0, [%1];" : "=r"(v) : "l"(p) : "memory"); return v; }
__device__ __forceinline__ void st_rlx(void* p, uint32_t v) { asm volatile("st.relaxed.gpu.global.u32 [%0], %1;" ::"l"(p), "r"(v) : "memory"); }
__device__ __forceinline__ void st_rlx2(void* p, uint32_t x, uint32_t y) { asm volatile("st.relaxed.gpu.global.v2.u32 [%0], {%1,%2};" ::"l"(p), "r"(x), "r"(y) : "memory"); }
__device__ __forceinline__ uint4 ldg4(const void* p) { uint4 v; asm volatile("ld.global.nc.v4.u32 {%0,%1,%2,%3}, [%4];" : "=r"(v.x), "=r"(v.y), "=r"(v.z), "=r"(v.w) : "l"(p)); return v; }
__device__ __forceinline__ uint32_t ldg1(const void* p) { uint32_t v; asm volatile("ld.global.nc.u32 %0, [%1];" : "=r"(v) : "l"(p)); return v; }
__device__ __forceinline__ uint32_t ldg16(const void* p) { uint16_t v; asm volatile("ld.global.nc.u16 %0, [%1];" : "=h"(v) : "l"(p)); return v; }
__device__ __forceinline__ const void* at256(const void* b, int o) { const void* r; asm("mad.wide.s32 %0, %1, 256, %2;" : "=l"(r) : "r"(o), "l"(b)); return r; }
__device__ __forceinline__ int laneid() { int v; asm volatile("mov.u32 %0, %%laneid;" : "=r"(v)); return v; }
__device__ __forceinline__ int ctaid() { int v; asm volatile("mov.u32 %0, %%ctaid.x;" : "=r"(v)); return v; }
__device__ __forceinline__ uint32_t lds32(uint32_t a) { uint32_t v; asm volatile("ld.shared.u32 %0, [%1];" : "=r"(v) : "r"(a) : "memory"); return v; }
__device__ __forceinline__ uint32_t lds32v(uint32_t a) { uint32_t v; asm volatile("ld.volatile.shared.u32 %0, [%1];" : "=r"(v) : "r"(a) : "memory"); return v; }
__device__ __forceinline__ uint32_t lds16(uint32_t a) { uint16_t v; asm volatile("ld.shared.u16 %0, [%1];" : "=h"(v) : "r"(a) : "memory"); return v; }
__device__ __forceinline__ uint2 lds64(uint32_t a) { uint2 v; asm volatile("ld.shared.v2.u32 {%0,%1}, [%2];" : "=r"(v.x), "=r"(v.y) : "r"(a) : "memory"); return v; }
__device__ __forceinline__ uint4 lds128(uint32_t a) { uint4 v; asm volatile("ld.shared.v4.u32 {%0,%1,%2,%3}, [%4];" : "=r"(v.x), "=r"(v.y), "=r"(v.z), "=r"(v.w) : "r"(a) : "memory"); return v; }
__device__ __forceinline__ void sts16(uint32_t a, uint32_t v) { asm volatile("st.shared.u16 [%0], %1;" ::"r"(a), "h"((uint16_t)v) : "memory"); }
__device__ __forceinline__ void sts32(uint32_t a, uint32_t v) { asm volatile("st.shared.u32 [%0], %1;" ::"r"(a), "r"(v) : "memory"); }
__device__ __forceinline__ void sts32v(uint32_t a, uint32_t v) { asm volatile("st.volatile.shared.u32 [%0], %1;" ::"r"(a), "r"(v) : "memory"); }
__device__ __forceinline__ void sts64(uint32_t a, uint32_t x, uint32_t y) { asm volatile("st.shared.v2.u32 [%0], {%1,%2};" ::"r"(a), "r"(x), "r"(y) : "memory"); }
__device__ __forceinline__ void sts128(uint32_t a, uint32_t x, uint32_t y, uint32_t z, uint32_t w) { asm volatile("st.shared.v4.u32 [%0], {%1,%2,%3,%4};" ::"r"(a), "r"(x), "r"(y), "r"(z), "r"(w) : "memory"); }
__device__ __forceinline__ void sts128f(uint32_t a, float x, float y, float z, float w) { asm volatile("st.shared.v4.f32 [%0], {%1,%2,%3,%4};" ::"r"(a), "f"(x), "f"(y), "f"(z), "f"(w) : "memory"); }
__device__ __forceinline__ void st_async4(uint32_t a, uint32_t x, uint32_t y, uint32_t z, uint32_t w, uint32_t bar) {
    asm volatile("st.async.shared::cluster.mbarrier::complete_tx::bytes.v4.b32 [%0], {%1,%2,%3,%4}, [%5];" ::"r"(a), "r"(x), "r"(y), "r"(z), "r"(w), "r"(bar) : "memory");
}
__device__ __forceinline__ void st_async2(uint32_t a, uint32_t x, uint32_t y, uint32_t bar) {
    asm volatile("st.async.shared::cluster.mbarrier::complete_tx::bytes.v2.b32 [%0], {%1,%2}, [%3];" ::"r"(a), "r"(x), "r"(y), "r"(bar) : "memory");
}
__device__ __forceinline__ void st_async2f(uint32_t a, float x, float y, uint32_t bar) {
    asm volatile("st.async.shared::cluster.mbarrier::complete_tx::bytes.v2.f32 [%0], {%1,%2}, [%3];" ::"r"(a), "f"(x), "f"(y), "r"(bar) : "memory");
}
__device__ __forceinline__ void ldm4(uint32_t a, uint32_t& r0, uint32_t& r1, uint32_t& r2, uint32_t& r3) {
    asm volatile("ldmatrix.sync.aligned.m8n8.x4.shared.b16 {%0,%1,%2,%3}, [%4];" : "=r"(r0), "=r"(r1), "=r"(r2), "=r"(r3) : "r"(a) : "memory");
}
__device__ __forceinline__ void ldm4t(uint32_t a, uint32_t (&r)[4]) {
    asm volatile("ldmatrix.sync.aligned.m8n8.x4.trans.shared.b16 {%0,%1,%2,%3}, [%4];" : "=r"(r[0]), "=r"(r[1]), "=r"(r[2]), "=r"(r[3]) : "r"(a) : "memory");
}
__device__ __forceinline__ void ldm2(uint32_t a, uint32_t& r0, uint32_t& r1) {
    asm volatile("ldmatrix.sync.aligned.m8n8.x2.shared.b16 {%0,%1}, [%2];" : "=r"(r0), "=r"(r1) : "r"(a) : "memory");
}
__device__ __forceinline__ void ldm2t(uint32_t a, uint32_t& r0, uint32_t& r1) {
    asm volatile("ldmatrix.sync.aligned.m8n8.x2.trans.shared.b16 {%0,%1}, [%2];" : "=r"(r0), "=r"(r1) : "r"(a) : "memory");
}
__device__ __forceinline__ void stm4(uint32_t a, uint32_t r0, uint32_t r1, uint32_t r2, uint32_t r3) {
    asm volatile("stmatrix.sync.aligned.m8n8.x4.shared.b16 [%0], {%1,%2,%3,%4};" ::"r"(a), "r"(r0), "r"(r1), "r"(r2), "r"(r3) : "memory");
}
__device__ __forceinline__ void stm4t(uint32_t a, uint32_t r0, uint32_t r1, uint32_t r2, uint32_t r3) {
    asm volatile("stmatrix.sync.aligned.m8n8.x4.trans.shared.b16 [%0], {%1,%2,%3,%4};" ::"r"(a), "r"(r0), "r"(r1), "r"(r2), "r"(r3) : "memory");
}
__device__ __forceinline__ void stm2t(uint32_t a, uint32_t r0, uint32_t r1) {
    asm volatile("stmatrix.sync.aligned.m8n8.x2.trans.shared.b16 [%0], {%1,%2};" ::"r"(a), "r"(r0), "r"(r1) : "memory");
}
__device__ __forceinline__ uint32_t movm(uint32_t a) { uint32_t d; asm volatile("movmatrix.sync.aligned.m8n8.trans.b16 %0, %1;" : "=r"(d) : "r"(a)); return d; }
__device__ __forceinline__ void mma_bf(float (&c)[4], uint32_t a0, uint32_t a1, uint32_t a2, uint32_t a3, uint32_t b0, uint32_t b1) {
    asm volatile("mma.sync.aligned.m16n8k16.row.col.f32.bf16.bf16.f32 {%0,%1,%2,%3},{%4,%5,%6,%7},{%8,%9},{%0,%1,%2,%3};"
                 : "+f"(c[0]), "+f"(c[1]), "+f"(c[2]), "+f"(c[3]) : "r"(a0), "r"(a1), "r"(a2), "r"(a3), "r"(b0), "r"(b1));
}
__device__ __forceinline__ void mma_bf8(float (&c)[4], uint32_t a0, uint32_t a1, uint32_t b0) {
    asm volatile("mma.sync.aligned.m16n8k8.row.col.f32.bf16.bf16.f32 {%0,%1,%2,%3},{%4,%5},{%6},{%0,%1,%2,%3};"
                 : "+f"(c[0]), "+f"(c[1]), "+f"(c[2]), "+f"(c[3]) : "r"(a0), "r"(a1), "r"(b0));
}
__device__ __forceinline__ void mma_h(float (&c)[4], uint32_t a0, uint32_t a1, uint32_t a2, uint32_t a3, uint32_t b0, uint32_t b1) {
    asm volatile("mma.sync.aligned.m16n8k16.row.col.f32.f16.f16.f32 {%0,%1,%2,%3},{%4,%5,%6,%7},{%8,%9},{%0,%1,%2,%3};"
                 : "+f"(c[0]), "+f"(c[1]), "+f"(c[2]), "+f"(c[3]) : "r"(a0), "r"(a1), "r"(a2), "r"(a3), "r"(b0), "r"(b1));
}
__device__ __forceinline__ void mma_h8(float (&c)[4], uint32_t a0, uint32_t a1, uint32_t b0) {
    asm volatile("mma.sync.aligned.m16n8k8.row.col.f32.f16.f16.f32 {%0,%1,%2,%3},{%4,%5},{%6},{%0,%1,%2,%3};"
                 : "+f"(c[0]), "+f"(c[1]), "+f"(c[2]), "+f"(c[3]) : "r"(a0), "r"(a1), "r"(b0));
}
template <int LIM>
__device__ __forceinline__ void mma_hp(int n, float (&d)[4], const float (&c)[4], uint32_t a0, uint32_t a1, uint32_t a2, uint32_t a3, uint32_t b0, uint32_t b1) {
    asm volatile("{.reg .pred p; setp.gt.s32 p, %14, %15;\n"
                 "@p mma.sync.aligned.m16n8k16.row.col.f32.f16.f16.f32 {%0,%1,%2,%3},{%4,%5,%6,%7},{%8,%9},{%10,%11,%12,%13};}"
                 : "+f"(d[0]), "+f"(d[1]), "+f"(d[2]), "+f"(d[3])
                 : "r"(a0), "r"(a1), "r"(a2), "r"(a3), "r"(b0), "r"(b1), "f"(c[0]), "f"(c[1]), "f"(c[2]), "f"(c[3]), "r"(n), "n"(LIM));
}
template <int LIM>
__device__ __forceinline__ void mma_hq(int n, float (&d)[4], uint32_t a0, uint32_t a1, uint32_t a2, uint32_t a3, uint32_t b0, uint32_t b1) {
    asm volatile("{.reg .pred p; setp.gt.s32 p, %10, %11;\n"
                 "@p mma.sync.aligned.m16n8k16.row.col.f32.f16.f16.f32 {%0,%1,%2,%3},{%4,%5,%6,%7},{%8,%9},{%0,%1,%2,%3};}"
                 : "+f"(d[0]), "+f"(d[1]), "+f"(d[2]), "+f"(d[3]) : "r"(a0), "r"(a1), "r"(a2), "r"(a3), "r"(b0), "r"(b1), "r"(n), "n"(LIM));
}
__device__ __forceinline__ void mma_hc(float (&d)[4], const float (&c)[4], uint32_t a0, uint32_t a1, uint32_t a2, uint32_t a3, uint32_t b0, uint32_t b1) {
    asm volatile("mma.sync.aligned.m16n8k16.row.col.f32.f16.f16.f32 {%0,%1,%2,%3},{%4,%5,%6,%7},{%8,%9},{%10,%11,%12,%13};"
                 : "=f"(d[0]), "=f"(d[1]), "=f"(d[2]), "=f"(d[3]) : "r"(a0), "r"(a1), "r"(a2), "r"(a3), "r"(b0), "r"(b1), "f"(c[0]), "f"(c[1]), "f"(c[2]), "f"(c[3]));
}
__device__ __forceinline__ uint32_t pack_bf(float lo, float hi) { uint32_t r; asm("cvt.rn.bf16x2.f32 %0, %1, %2;" : "=r"(r) : "f"(hi), "f"(lo)); return r; }
__device__ __forceinline__ uint32_t pack_h(float lo, float hi) { uint32_t r; asm("cvt.rn.f16x2.f32 %0, %1, %2;" : "=r"(r) : "f"(hi), "f"(lo)); return r; }
__device__ __forceinline__ float bf_lo(uint32_t w) { return __uint_as_float(w << 16); }
__device__ __forceinline__ float bf_hi(uint32_t w) { return __uint_as_float(w & 0xFFFF0000u); }
__device__ __forceinline__ float bf_round(float x) { return __uint_as_float(pack_bf(0.f, x)); }
__device__ __forceinline__ uint32_t badd(uint32_t a, uint32_t b) { uint32_t r; asm("add.rn.bf16x2 %0, %1, %2;" : "=r"(r) : "r"(a), "r"(b)); return r; }
__device__ __forceinline__ uint32_t bsub(uint32_t a, uint32_t b) { uint32_t r; asm("sub.rn.bf16x2 %0, %1, %2;" : "=r"(r) : "r"(a), "r"(b)); return r; }
__device__ __forceinline__ uint32_t bmul(uint32_t a, uint32_t b) { uint32_t r; asm("mul.rn.bf16x2 %0, %1, %2;" : "=r"(r) : "r"(a), "r"(b)); return r; }
__device__ __forceinline__ uint32_t bfma(uint32_t a, uint32_t b, uint32_t c) { uint32_t r; asm("fma.rn.bf16x2 %0, %1, %2, %3;" : "=r"(r) : "r"(a), "r"(b), "r"(c)); return r; }
__device__ __forceinline__ uint32_t hadd(uint32_t a, uint32_t b) { uint32_t r; asm("add.rn.f16x2 %0, %1, %2;" : "=r"(r) : "r"(a), "r"(b)); return r; }
__device__ __forceinline__ uint32_t prmt(uint32_t a, uint32_t b, uint32_t s) { uint32_t r; asm("prmt.b32 %0, %1, %2, %3;" : "=r"(r) : "r"(a), "r"(b), "r"(s)); return r; }
__device__ __forceinline__ float ex2f(float x) { float r; asm("ex2.approx.ftz.f32 %0, %1;" : "=f"(r) : "f"(x)); return r; }
__device__ __forceinline__ float rcpf(float x) { float r; asm("rcp.approx.ftz.f32 %0, %1;" : "=f"(r) : "f"(x)); return r; }
__device__ __forceinline__ float sqrt_ap(float x) { float r; asm("sqrt.approx.ftz.f32 %0, %1;" : "=f"(r) : "f"(x)); return r; }
__device__ __forceinline__ float tanh_ap(float x) { float r; asm("tanh.approx.f32 %0, %1;" : "=f"(r) : "f"(x)); return r; }
__device__ __forceinline__ float sigm(float x) { return rcpf(1.f + ex2f(-1.4426950408889634f * x)); }
__device__ __forceinline__ float silu_half(float h) { return fmaf(h, tanh_ap(h), h); }
__device__ __forceinline__ uint32_t clk32() { uint32_t c; asm volatile("mov.u32 %0, %%clock;" : "=r"(c)); return c; }
__device__ __forceinline__ void spin_until(uint32_t t0, int dt) {
#pragma unroll 1
    while ((int)(clk32() - t0) < dt) __nanosleep(32);
}
__device__ __forceinline__ void cp16(uint32_t dst, const void* src) { asm volatile("cp.async.cg.shared.global [%0], [%1], 16;" ::"r"(dst), "l"(src) : "memory"); }

__device__ __forceinline__ uint32_t xslot(int s, int h) { return XX + 32 * (s & ~1) + 16 * ((2 * h + (s & 1)) ^ ((s >> 1) & 2)); }

struct cf { float x, y; };
__device__ __forceinline__ cf cmul(cf a, cf b) { return {a.x * b.x - a.y * b.y, a.x * b.y + a.y * b.x}; }
__device__ __forceinline__ cf csq(cf a) { return {a.x * a.x - a.y * a.y, (a.x + a.x) * a.y}; }
__device__ __forceinline__ cf cpow_direct(float zr2, float zi, float l) {
    const float mag = ex2f(zr2 * l), th = zi * l;
    return {mag * __cosf(th), mag * __sinf(th)};
}
struct hp { uint32_t re, im; };
__device__ __forceinline__ hp mk2(cf a, cf b) { return {pack_h(a.x, b.x), pack_h(a.y, b.y)}; }
__device__ __forceinline__ hp his(hp a, hp b) { return {prmt(a.re, b.re, 0x7632), prmt(a.im, b.im, 0x7632)}; }
__device__ __forceinline__ hp operator*(hp a, hp b) {
    hp r;
    asm("{.reg .b32 t, u;\nmul.rn.f16x2 t, %3, %5;\nneg.f16x2 t, t;\nfma.rn.f16x2 %0, %2, %4, t;\nmul.rn.f16x2 u, %3, %4;\nfma.rn.f16x2 %1, %2, %5, u;}"
        : "=&r"(r.re), "=r"(r.im) : "r"(a.re), "r"(a.im), "r"(b.re), "r"(b.im));
    return r;
}
struct KParams { uint32_t are, aim, bre, bim, cre, cim, ldt, dsk; };

__device__ __forceinline__ uint32_t kgen(KParams kp, uint32_t scr, uint32_t oth, int bar, int lane, float (&d)[5][4], float& k0, int nc, uint32_t pause) {
    const float dt = bf_round(ex2f(bf_lo(kp.ldt) * 1.4426950408889634f));
    cf w = cmul({bf_lo(kp.cre), bf_lo(kp.cim)}, {dt * bf_lo(kp.bre), dt * bf_lo(kp.bim)});
    cf w1 = cmul({bf_hi(kp.cre), bf_hi(kp.cim)}, {dt * bf_hi(kp.bre), dt * bf_hi(kp.bim)});
    const float dk = bf_lo(kp.dsk);
    uint32_t z = prmt(kp.are, kp.aim, 0x5410), z1 = prmt(kp.are, kp.aim, 0x7632);
    uint32_t eb = __reduce_max_sync(~0u, __float_as_uint(fmaxf(fmaxf(fmaxf(fabsf(w.x), fabsf(w.y)), fmaxf(fabsf(w1.x), fabsf(w1.y))), fabsf(dk) * 0x1p-20f)));
    k0 = fmaf(dk, 1.f / 64.f, w.x + w1.x);
#pragma unroll
    for (int o = 16; o > 0; o >>= 1) k0 += __shfl_xor_sync(~0u, k0, o);
    const uint32_t sa = scr + 16 * lane;
    sts128(oth + 2048 + 16 * lane, __float_as_uint(w1.x), __float_as_uint(w1.y), z1, __float_as_uint(k0));
    sts32(oth + 2560, eb);
    bar_sync(bar, 64);
    const uint4 ov = lds128(sa + 2048);
    eb = min(max(max(eb, lds32(scr + 2560)) & 0x7F800000u, 0x00800000u), 0x7A000000u);
    const float sc = __uint_as_float(0x7B000000u - eb);
    k0 = (k0 + __uint_as_float(ov.w)) * sc;
#pragma unroll
    for (int i = 0; i < 5; i++) d[i][0] = d[i][1] = d[i][2] = d[i][3] = 0.f;
    const int mi = lane >> 3, j = lane & 7;
    const uint32_t la = scr + 1024 * (mi & 1) + 512 * (mi >> 1) + 16 * j, lb = scr + 512 * (mi & 1) + 128 * (mi >> 1) + 16 * j;
    auto st = [&](int grp, hp a, hp b, hp c, hp e) { sts128(sa + 1024 * grp, a.re, b.re, c.re, e.re); sts128(sa + 1024 * grp + 512, a.im, b.im, c.im, e.im); };
#pragma unroll 1
    do {
        const float zr2 = dt * bf_lo(z) * 1.4426950408889634f, zi = dt * bf_hi(z);
        const cf ws = {w.x * sc, w.y * sc};
        z = z1; w = w1;
        z1 = ov.z; w1 = {__uint_as_float(ov.x), __uint_as_float(ov.y)};
        const cf a1 = cpow_direct(zr2, zi, 1.f), a256 = cpow_direct(zr2, zi, 256.f);
        uint32_t a[4][4];
        {
            const cf b1 = cpow_direct(-zr2, zi, -16.f), b2 = csq(b1), b4 = csq(b2), b8 = csq(b4);
            const hp m2 = mk2(b2, b2), m4 = mk2(b4, b4), m8 = mk2(b8, b8);
            const hp u0 = mk2({1.f, 0.f}, b1), u1 = u0 * m2, u2 = u0 * m4, u3 = u1 * m4;
            __syncwarp();
            st(0, u0, u1, u2, u3);
            st(1, u0 * m8, u1 * m8, u2 * m8, u3 * m8);
            __syncwarp();
#pragma unroll
            for (int k = 0; k < 4; k++) ldm4t(la + 128 * k, a[k]);
        }
        auto tile = [&](int T, int grp) {
#pragma unroll
            for (int e = 0; e < 2; e++) {
                uint32_t b[4];
                ldm4t(lb + 1024 * grp + 256 * e, b);
                mma_h(d[T], a[2 * e][0], a[2 * e][1], a[2 * e][2], a[2 * e][3], b[0], b[1]);
                mma_h(d[T], a[2 * e + 1][0], a[2 * e + 1][1], a[2 * e + 1][2], a[2 * e + 1][3], b[2], b[3]);
            }
        };
        const cf a2 = csq(a1), a4 = csq(a2), a8 = csq(a4), a512 = csq(a256), a1024 = csq(a512);
        const hp m2 = mk2(a2, a2), m4 = mk2(a4, a4), m8 = mk2(a8, a8), m256 = mk2(a256, a256), m512 = mk2(a512, a512);
        const hp v1 = mk2(cmul(ws, a1), cmul(ws, a2)), v3 = v1 * m2, v5 = v1 * m4, v7 = v3 * m4, v15 = v7 * m8;
        const hp e1 = his(v1, v3) * m256, e2 = e1 * m4;
        __syncwarp();
        st(0, v1, v5, v1 * m8, v5 * m8);
        st(1, v3, v7, v3 * m8, v15);
        st(2, e1, e2, e1 * m8, e2 * m8);
        __syncwarp();
        tile(0, 0); tile(1, 1); tile(2, 2);
        const hp f1 = his(v3, v7) * m512, f2 = f1 * m8, g1 = his(v7, v15) * mk2(a1024, a1024), g2 = g1 * m256;
        __syncwarp();
        st(0, f1, f2, f1 * m256, f2 * m256);
        st(1, g1, g2, g1 * m512, g2 * m512);
        __syncwarp();
        tile(3, 0); tile(4, 1);
        if (pause) mbar_wait(pause, 0);
    } while (--nc);
    return eb;
}

__device__ __forceinline__ void near_lags(uint32_t S, int k, uint32_t yo, uint32_t eb) {
    const int lane = threadIdx.x & 31, g = lane >> 2, t = lane & 3, mi = lane >> 3, j = lane & 7, warp = k;
    const uint32_t cb = S + SM_CH + k * CH;
    uint32_t R[66], x[5];
#pragma unroll
    for (int i = 0; i < 66; i++) R[i] = lds32(cb + TAB + 4 * (7 + g - 2 * t) + 32 * i);
    bar_arrive(1 + k, 64);
    float w[5][4];
#pragma unroll
    for (int i = 0; i < 5; i++) w[i][0] = w[i][1] = w[i][2] = w[i][3] = 0.f;
    uint32_t xa[8], xo = cb;
    {
        const uint32_t v = xslot(lane & 15, lane >> 4);
#pragma unroll
        for (int i = 0; i < 8; i++) xa[i] = __shfl_sync(~0u, v, LD4 ? j + i + (mi == 1 ? 17 : (mi == 2 ? 16 : 1)) : j + 2 * (lane & 8) + i);
    }
    uint32_t fa = xa[0], idm = 0;
    uint32_t ya = S + SM_DUMP + 8 * lane, ybar = S + 61 * 8, dy = 0, db = 0;
    const uint32_t sc = prmt(eb + 0x04800000u, 0, 0x3232);
    uint32_t z = lds32(cb + XX + 4 * lane);
    int n = 16;
    mbar_wait(S + B_X * 8, 0);
    uint32_t A[3][4];
    if (LD4) {
        ldm4(xo + xa[0], A[0][0], A[0][1], A[0][2], A[0][3]);
        ldm4(xo + xa[1], A[1][0], A[1][1], A[1][2], A[1][3]);
    } else {
        ldm2(xo + xa[0], x[1], x[0]);
        ldm2(xo + xa[1], x[1], x[2]);
        ldm2(xo + xa[2], x[3], x[4]);
    }
    auto send = [&]() { st_async2(ya, bmul(pack_bf(w[0][0], w[0][1]), sc), bmul(pack_bf(w[0][2], w[0][3]), sc), ybar); };
    auto tile = [&](auto nj) {
        constexpr int NJ = decltype(nj)::value;
        asm volatile("" : "+r"(z), "+r"(xo));
        uint32_t f0, f1;
        ldm2(xo + fa, f0, f1);
        send();
#pragma unroll
        for (int q = 1; q <= 8; q++) {
            uint32_t n0, n1, a2, a3;
            if (LD4) {
                ldm4(xo + xa[(q + 1) & 7] + 32 * ((q + 1) & 8), A[2][0], A[2][1], A[2][2], A[2][3]);
                x[1] = A[0][0]; x[2] = A[0][1]; a2 = A[0][2]; a3 = A[0][3];
#pragma unroll
                for (int e = 0; e < 4; e++) { A[0][e] = A[1][e]; A[1][e] = A[2][e]; }
            } else {
                ldm2(xo + xa[(q + 2) & 7] + 32 * ((q + 2) & 8), n0, n1);
                a2 = x[0] | z; a3 = x[1] | z;
            }
#pragma unroll
            for (int i = 0; i < NJ; i++) {
                const int s = 16 * i + 16 - 2 * q;
                if (q == 1) mma_hc(w[i], w[i + 1], x[1], x[2], a2, a3, R[s], R[s + 1]);
                else mma_h(w[i], x[1], x[2], a2, a3, R[s], R[s + 1]);
            }
            if (q == 4) mma_h8(w[1], f0, f1, idm);
            if (q == 7 && ZZ) {
                const uint32_t zz = x[1] & z;
                ya += dy + zz; ybar += db + zz; dy = 512 - dy; db = 8 - db;
            }
            if (q == 8 && NJ == 4) {
                const float zero[4] = {0.f, 0.f, 0.f, 0.f};
                mma_hc(w[4], zero, x[1], x[2], a2, a3, R[64], R[65]);
            }
            if (!LD4) { x[0] = x[2]; x[1] = x[3]; x[2] = x[4]; x[3] = n0; x[4] = n1; }
        }
        xo += 256; if (!ZZ) { ya += dy; ybar += db; dy = 512 - dy; db = 8 - db; }
    };
    int lim = 15;
#pragma unroll 1
    for (;;) {
        n -= lim;
#pragma unroll 1
        do tile(std::integral_constant<int, 4>()); while (--n);
        n = lim;
        if (n < 5) break;
        const int lane = laneid(), g = lane >> 2, t = lane & 3;
        if (n == 15) {
            ybar = mapa(S + B_Y * 8, g >> 1);
            db = dy = mapa(S + B_Y * 8, 4 + (g >> 1)) - ybar;
            ya = ybar - B_Y * 8 + SM_CH + k * CH + YIN + (yo ^ (8 * (lane & 7)));
        }
        if (n == 13) { fa = TAB - 768 + 16 * (lane & 15); idm = g == 2 * t ? 0x3C00u : (g == 2 * t + 1 ? 0x3C000000u : 0u); }
#pragma unroll 1
        while ((lim = lds32v(S + SM_PROG + 4 * k)) >= n) __nanosleep(40);
        if (n == 15) lim = 13;
    }
#pragma unroll 1
    for (; n > 0; n--) tile(std::integral_constant<int, 2>());
    send();
}

__global__ void __cluster_dims__(8, 1, 1) __launch_bounds__(NTHREADS, 1) fused_kernel(const Hot p, const __grid_constant__ Maps m) {
    extern __shared__ __align__(1024) char smem[];
    const uint32_t t0 = clk32();
    const int tid = threadIdx.x, lane = tid & 31, warp = __shfl_sync(~0u, tid >> 5, 0), bid = blockIdx.x;
    const int g = lane >> 2, t = lane & 3, mi = lane >> 3, j = lane & 7;
    const int r = bid & 7, cl = bid >> 3;
    const int nch = cl < 3 ? 4 : 5, cbase = max(32 * cl, 40 * cl - 24);
    uint32_t S = smem_u32(smem);
    asm volatile("" : "+r"(S));

    const int half = warp > 4, k = (int)(0x5436666621043210ull >> (4 * warp)) & 15;
    const bool extra = cl == 2 && warp < 4, svcwarp = (warp >> 2) == 2;
    KParams kp;
    uint32_t epoch;
    if (k < nch) {
        const uint32_t ch = cbase + 8 * k + r;
        const char* pb = (const char*)p.u + (ch * 256 + half * 128 + lane * 4);
        kp.bre = ldg1(at256(pb, p.bre)); kp.bim = ldg1(at256(pb, p.bim));
        kp.cre = ldg1(at256(pb, p.cre)); kp.cim = ldg1(at256(pb, p.cim));
        kp.ldt = ldg16(at256(p.u + ch, lane & 1 ? p.dskip : p.logdt));
        kp.are = ldg1(at256(pb, p.are)); kp.aim = ldg1(at256(pb, p.aim));
        sts128(S + SM_CH + k * CH + 16 * lane + (half ? FT : (lane < 2 ? TAB : (lane < 8 ? TAB + 2048 : FT + 384))), 0u, 0u, 0u, 0u);
        sts32(S + SM_PROG + 4 * k, 13);
    } else if (warp == 12) {
        if (elect()) {
            mbar_init(S + B_WR * 8, 1);
            mbar_init(S + B_ROWS * 8, 1);
            mbar_expect(S + B_WR * 8, 1152);
            bulk_g2s(S + SM_B + 2048, (const char*)p.u + p.wr * 256ll, 1152, S + B_WR * 8);
            while ((int)(clk32() - t0) < p.tn.t_rows) {}
            mbar_expect(S + B_ROWS * 8, cl == 2 ? 36864 : 18432);
            const __nv_bfloat16* src = p.u + (8 * (cl & 14) + 2 * r + (cl & 1)) * 9216;
            bulk_g2s(S + SM_TOTAL - 18432, src, 18432, S + B_ROWS * 8);
            if (cl == 2) bulk_g2s(S + SM_TOTAL - 36864, src + 97 * 9216, 18432, S + B_ROWS * 8);
        }
    } else if (svcwarp) {
        if (elect()) {
#pragma unroll
            for (int i = 0; i < 16; i++) mbar_init(S + (warp & 3) * 128 + i * 8, warp > (i < 14 ? 10 : 9) ? 4 : 1);
            asm volatile("fence.mbarrier_init.release.cluster;" ::: "memory");
        }
        __syncwarp();
        if (tid <= 256 + B_XS) mbar_expect(S + lane * 8, (uint32_t)(0x490101180804ull >> (8 * max(lane - 7, 0)) & 255) * (lane < B_TOP ? 128 * nch : 128));
    }
    if (svcwarp || extra) epoch = ld_rlx(at256(p.u + bid * 16, p.ep));
    __syncthreads();
    asm volatile("barrier.cluster.arrive.relaxed.aligned;" ::: "memory");
    const uint2* sp = &p.s->stat[256 * r + 2 * (tid & 127)];
    uint4 sw;
    if (svcwarp) sw = ld_rlx4(sp);
    if (svcwarp || extra) {
        const uint32_t tag = ~epoch & 1;
        const int tile = extra ? 15 : cl;
        float d2[4] = {0, 0, 0, 0}, d3[4] = {0, 0, 0, 0}, d4[4] = {0, 0, 0, 0}, d5[4] = {0, 0, 0, 0}, d6[4] = {0, 0, 0, 0}, d7[4] = {0, 0, 0, 0};
        const uint32_t xa = S + SM_TOTAL - (extra ? 36864 : 18432) + (8 * (mi >> 1) + 2 * (warp & 3) + (mi & 1)) * 1152 + 16 * j;
        const uint32_t wa = S + SM_B + 2048 + 64 * (g >> 2) + 16 * t + 2 * (g & 2), ones = 0x3F803F80u;
        uint32_t wv[18];
        mbar_wait(S + B_WR * 8, 0);
#pragma unroll
        for (int i = 0; i < 18; i++) { wv[i] = ones; if (g & 1) wv[i] = lds32(wa + 128 * (i >> 1) + 8 * (i & 1)); }
#pragma unroll
        for (int i = 0; i < 9; i++) mma_bf(d5, ones, ones, ones, ones, wv[2 * i], wv[2 * i + 1]);
        float wsum = d5[1] + __shfl_xor_sync(~0u, d5[1], 1);
        wsum += __shfl_xor_sync(~0u, wsum, 2);
        mbar_wait((S + B_ROWS * 8) | (__float_as_uint(wsum) & p.tn.zero), 0);
        __syncwarp();
#pragma unroll
        for (int i = 0; i < 9; i++) {
            const uint4 x = lds128(xa + 128 * i);
            mma_bf8(d3, x.x, x.y, x.x);
            mma_bf8(d4, x.x, x.y, x.y);
            mma_bf8(d6, x.z, x.w, x.z);
            mma_bf8(d7, x.z, x.w, x.w);
            mma_bf(d2, x.x, x.y, x.z, x.w, wv[2 * i], wv[2 * i + 1]);
        }
        float sx = d2[0] + d2[2], sq = (g & 1) ? (d3[1] + d4[3]) + (d6[1] + d7[3]) : (d3[0] + d4[2]) + (d6[0] + d7[2]);
        float dot = (t & 1) ? d2[3] : d2[1];
        sx += __shfl_xor_sync(~0u, sx, 4);
        sq = __shfl_sync(~0u, sq, 9 * mi) + __shfl_sync(~0u, sq, 9 * mi + 4);
        dot += __shfl_xor_sync(~0u, dot, 1);
        dot += __shfl_xor_sync(~0u, dot, 6);
        const float mean = sx * (1.f / 576.f), var = fmaxf(sq * (1.f / 576.f) - mean * mean, 0.f);
        const float mu = bf_round(mean), sd = bf_round(sqrt_ap(bf_round(bf_round(var) + 1e-5f)));
        const uint32_t idx = 2047 - (128 * (tile & 14) + 32 * r + 16 * (tile & 1) + 8 * (mi >> 1) + 2 * (warp & 3) + (mi & 1));
        const uint32_t rb = pack_bf(0.f, (dot - mu * wsum) * rcpf(sd));
        const uint32_t ga = S + SM_B + 3200 + 32 * warp;
        if (j == 0) sts64(ga + 8 * mi, (__float_as_uint(mu) >> 16) | __float_as_uint(sd), (((rb ^ (((int)rb >> 31) | 0x80000000u)) >> 1) & 0x7FFF8000u) | (tag << 31) | idx);
        bar_sync(extra ? 14 : 15, 128);
        if ((tid & 127) < 16) {
            const uint2 v = lds64(ga + 8 * lane);
            st_rlx2(&p.s->stat[256 * r + 16 * tile + lane], v.x, v.y);
        }
        if (lane == 0) mbar_arrive(S + (B_EMPTY + (extra ? 8 : 10)) * 8);
    }

    if (k < nch) {
        const uint32_t cb = S + SM_CH + k * CH, scr = cb + BOX + 3072 * half, oth = cb + BOX + 3072 - 3072 * half;
        float d[5][4], k0;
        kp.dsk = __shfl_sync(~0u, kp.ldt, 1);
        kp.ldt = __shfl_sync(~0u, kp.ldt, 0);
        const uint32_t eb = kgen(kp, scr, oth, 1 + k, lane, d, k0, k > 2 ? 3 - 2 * half : 2, ((p.tn.stag >> warp) & 1) ? S + (B_EMPTY + 10) * 8 : 0);
        __syncwarp();
#pragma unroll
        for (int i = 0; i < 5; i++)
            if (half == (i < 3)) sts128f(scr + i * 512 + lane * 16, d[i][0], d[i][1], d[i][2], d[i][3]);
        bar_sync(1 + k, 64);
        auto both = [&](int i, uint32_t& w0, uint32_t& w1) {
            const uint4 v = lds128(oth + i * 512 + lane * 16);
            w0 = pack_h(d[i][0] + __uint_as_float(v.x), d[i][1] + __uint_as_float(v.y));
            w1 = pack_h(d[i][2] + __uint_as_float(v.z), d[i][3] + __uint_as_float(v.w));
        };
        if (half) {
            uint32_t a0, a1, b0, b1;
            both(3, a0, a1); both(4, b0, b1);
            const uint32_t o = cb + FT + 56 + 128 * (t >> 1) + 8 * g + 4 * (t & 1), q = cb + FT + 376 + 64 * t + 4 * g;
            sts32(o, a0); sts32(o + 64, a1); sts32(q, b0); sts32(q + 32, b1);
        } else {
            {
                uint32_t a[2], b[2], c[2], last = pack_h(k0, k0);
                both(0, a[0], a[1]); both(1, b[0], b[1]); both(2, c[0], c[1]);
                const uint32_t o = cb + TAB + 32 + 16 * lane;
                sts16(cb + TAB + 28, last);
#pragma unroll
                for (int h = 0; h < 4; h++) {
                    const uint32_t e = h < 2 ? b[h] : c[h - 2], pv = __shfl_sync(~0u, lane == 31 ? last : e, lane - 1);
                    if (h < 2) sts128(o + 512 * h, prmt(a[h], pv, 0x7610), prmt(a[h], 0, 0x1032), prmt(e, a[h], 0x7610), prmt(e, 0, 0x1032));
                    else sts128(o + 512 * h, prmt(pv, 0, 0x3232), prmt(e, pv, 0x7610), prmt(e, 0, 0x1032), prmt(e, 0, 0x3232));
                    last = e;
                }
                if (lane == 31) sts128(o + 1552, prmt(last, 0, 0x3232), prmt(last, 0, 0x3232), last & 0xFFFF0000u, 0u);
                __syncwarp();
            }
            near_lags(S, k, 64 * r + 16 * ((2 * k + (cbase >> 2) + (r >> 2)) & 3), eb);
            return;
        }
    }

    const int c2 = ctaid() >> 3, ph0 = (c2 < 3 || c2 > 8) ? 0 : 2, cu = c2 < 3 ? c2 : c2 - 6;
    if (warp == 12) {
        if (elect()) {
            asm volatile("prefetch.tensormap [%0];" ::"l"(&m.u) : "memory");
            spin_until(t0, p.tn.t_tile);
            mbar_expect(S + B_RAW * 8, 256 * PITCH);
            asm volatile("cp.async.bulk.tensor.5d.shared::cluster.global.mbarrier::complete_tx::bytes [%0], [%1, {%3, 0, %4, 0, 0}], [%2];"
                         ::"r"(S + SM_RAW), "l"(&m.u), "r"(S + B_RAW * 8), "r"(cbase), "r"(4 * r) : "memory");
            spin_until(t0, ph0 ? p.tn.t_d : p.tn.t_w);
            if (ph0) {
#pragma unroll 1
                for (int e = bid - 24; e < p.tn.pf; e += 48) {
                    const int q = (e * 911) >> 16;
                    asm volatile("cp.async.bulk.prefetch.tensor.2d.L2.global [%0, {%1, %2}];" ::"l"(m.w + 1), "r"(64 * e - F_ * q), "r"(192 + 64 * q) : "memory");
                }
            }
            uint32_t bar = S + B_FULL * 8, dst = S + SM_W, em = cl == 2 ? 0x1249500u : 0x1249400u;
            int s = 0;
#pragma unroll 1
            for (int ph = ph0; ph < 3; ph++) {
                const int c0 = ph < 2 ? 64 * cu + 576 * r : cbase;
                int c1 = ph < 2 ? 0 : 576 * r;
#pragma unroll 1
                for (int n = 0; n < 9; n++, s++) {
                    const int w = s < p.tn.s0 ? p.tn.win0 : p.tn.win;
                    if (s >= w) mbar_wait(bar - 8 * w, 0);
                    if (em & 1) mbar_wait(bar + 8 * (B_EMPTY - B_FULL), 0);
                    mbar_expect(bar, 8192);
                    tma2d(dst, m.w + ph, c0, c1, bar);
                    bar += 8; em >>= 1; c1 += 64;
                    dst = dst == S + SM_W + (NRING - 1) * 8192 ? S + SM_W : dst + 8192;
                }
            }
        }
        return;
    }

    if (warp == 15) {
        asm volatile("barrier.cluster.wait.aligned;" ::: "memory");
        sts32(S + SM_SKIP + 4 * j, 0u);
        const uint32_t ob = mapa(S, g);
        bar_sync(13, 160);
        const uint4 ka = lds128(S + SM_B + 256 + 16 * lane), kb = lds128(S + SM_B + 768 + 16 * lane);
        uint32_t k0 = ka.x, k1 = ka.y, mine = 0, c = 0;
        int rank = lane;
#pragma unroll 1
        for (int pass = 0;; pass++) {
#pragma unroll 1
            for (int n = 0; n < (pass < 2 ? 4 : 8); n++) {
                const uint32_t a = __viaddmin_u32(k0, c, __viaddmin_u32(k1, c, ka.z + c)), b = __viaddmin_u32(ka.w, c, __viaddmin_u32(kb.x, c, kb.y + c));
                c += ~__reduce_min_sync(~0u, __vimin3_u32(a, b, __viaddmin_u32(kb.z, c, kb.w + c)));
                if ((pass < 2 ? t : j) == n) mine = c;
            }
            if (pass == 2) break;
            asm volatile("st.async.shared::cluster.mbarrier::complete_tx::bytes.b32 [%0], %1, [%2];" ::"r"(ob + SM_CAND + 128 * pass + 16 * r + 4 * t), "r"(~mine), "r"(ob + (B_TOP + pass) * 8) : "memory");
            mbar_wait(S + (B_TOP + pass) * 8, 0);
            const uint32_t v = lds32(S + SM_CAND + 4 * lane);
            if (pass) {
                k0 = v; k1 = lds32(S + SM_CAND + 128 + 4 * lane); c = 0;
            } else {
                uint32_t cn[4] = {0, 0, 0, 0};
#pragma unroll 4
                for (int e = 0; e < 128; e += 16) {
                    const uint4 o = lds128(S + SM_CAND + e);
                    cn[0] += (o.x - v) >> 31; cn[1] += (o.y - v) >> 31; cn[2] += (o.z - v) >> 31; cn[3] += (o.w - v) >> 31;
                }
                const int rk = (cn[0] + cn[1]) + (cn[2] + cn[3]);
                if (!__any_sync(~0u, t == 3 && rk < 8)) { rank = rk; mine = ~v; break; }
            }
        }
        const uint32_t row = ~mine & 2047, ix = (row & 0xE0) * 8 + ((row >> 3) & 0xE0) + (row & 0x11) + ((row >> 2) & 2) + (row & 6) * 2;
        if (rank == r && ph0 == 0) {
            bulk_mc(S + SM_B + BP * r, p.u + row * D_, 1152, S + B_XS * 8);
            asm volatile("fence.proxy.async.global;" ::: "memory");
            bulk_mc(S + SM_B + BP * r + 1152, &p.s->stat[ix & ~1], 16, S + B_XS * 8);
        }
        const bool own = rank < 8 && (ix >> 8) == r;
        const uint32_t m2 = 2 * mine, rb = (m2 ^ ((~(int)m2 >> 31) | 0x80000000u)) & 0xFFFF0000u;
        if (rank < 8) sts64(S + SM_SEL + 8 * rank, ix | rb, row);
        if (own) asm volatile("red.shared.or.b32 [%0], %1;" ::"r"(S + SM_SKIP + 4 * (ix & 7)), "r"(1u << ((ix >> 3) & 31)) : "memory");
        const int no = __popc(__ballot_sync(~0u, own));
        if (lane < 2) mbar_expect(S + (B_FIN + lane) * 8, lane ? 0 : no * (nch - 2) * 256);
    }

    if (svcwarp) {
        const uint32_t tag = ~epoch & 1;
        const int fw = warp & 3, i = tid & 127;
        asm volatile("barrier.cluster.wait.aligned;" ::: "memory");
        mbar_wait(S + B_RAW * 8, 0);
#pragma unroll 1
        for (int it = 0; it < SPIN_LIMIT && (int)((sw.y ^ -tag) | (sw.w ^ -tag)) < 0; it++) sw = ld_rlx4(sp);
        sts64(S + SM_B + 256 + 8 * i, ~sw.y, ~sw.w);
        {
            const float r0 = 0.5f * rcpf(bf_hi(sw.x)), r1 = 0.5f * rcpf(bf_hi(sw.z));
            sts128f(S + SM_ST + 16 * i, r0, -bf_lo(sw.x) * r0, r1, -bf_lo(sw.z) * r1);
        }
        bar_sync(13, 160);
        if (i == 0) st_rlx(&p.s->ep[bid * 8], epoch + 1);
        {
            const uint32_t xb = mapa(S, g);
            uint32_t xd = xb + SM_CH + xslot(8 + 2 * r + (t >> 1), t & 1) + 256 * (fw & 2), xbar = xb + B_X * 8;
            uint32_t ra = S + SM_RAW + (64 * mi + j + 4 * (fw & 2)) * PITCH, sa = S + SM_ST + 64 * (t & 2) + 16 * (t & 1) + 128 * (fw & 2);
#pragma unroll 1
            for (int u = fw; u < fw + 4; u++) {
                uint4 s[4];
#pragma unroll
                for (int e = 0; e < 4; e++) s[e] = lds128(sa + 32 * e);
#pragma unroll 1
                for (int n = u & 1; n < nch; n += 2) {
                    uint32_t a[4];
                    ldm4t(ra + 16 * n, a);
#pragma unroll
                    for (int e = 0; e < 4; e++)
                        a[e] = pack_h(fmaf(bf_lo(a[e]), __uint_as_float(s[e].x), __uint_as_float(s[e].y)), fmaf(bf_hi(a[e]), __uint_as_float(s[e].z), __uint_as_float(s[e].w)));
                    st_async4(xd + n * CH, a[0], a[1], a[2], a[3], xbar);
                }
                xd += 1024; ra += 16 * PITCH; sa += 512; xbar |= 8;
            }
        }
        mbar_wait(S + B_SEL * 8, 0);
        const uint2 sv = lds64(S + SM_SEL + 8 * j);
        const uint32_t bw = S + SM_B + BP * j + 16 * (i >> 3);
        if (ph0 == 0) {
            mbar_wait(S + B_XS * 8, 0);
            const uint32_t s1 = lds32(S + SM_B + BP * j + 1152 + 8 * (sv.x & 1));
            uint4 v[5];
#pragma unroll
            for (int n = 0; n < 5; n++) v[n] = lds128(bw + 256 * n);
            const float ri = rcpf(bf_hi(s1));
            const uint32_t mu = prmt(s1, 0, 0x1010), hi = pack_bf(ri, ri), lo = pack_bf(ri - bf_lo(hi), ri - bf_lo(hi));
            auto nrm = [&](uint32_t x) { const uint32_t e = bsub(x, mu); return bfma(e, hi, bmul(e, lo)); };
#pragma unroll
            for (int n = 0; n < 5; n++)
                if (n < 4 || fw < 2) sts128(bw + 256 * n, nrm(v[n].x), nrm(v[n].y), nrm(v[n].z), nrm(v[n].w));
        }
        const int mt = (fw + 3) & 3;
        uint32_t* const hp = p.s->h + 2304 * r;
        uint32_t g0 = 0x3F803F80u, g1 = g0, bar = S + B_FULL * 8, of = 0;
        const uint32_t aa = S + SM_W + (8 * (mi >> 1) + j) * 128 + (((2 * mt + (mi & 1)) ^ j) << 4);
        float d[4][4];
#pragma unroll 1
        for (int ph = ph0;; ph++) {
            if (ph == 2) {
                uint4 v[5];
#pragma unroll 1
                for (int it = 0; it < SPIN_LIMIT; it++) {
                    uint32_t a = ~0u, o = 0;
#pragma unroll
                    for (int n = 0; n < 5; n++) v[n] = ld_rlx4((const uint4*)hp + i + (n < 4 ? 128 * n : 448));
#pragma unroll
                    for (int n = 0; n < 5; n++) { a &= v[n].x & v[n].z; o |= v[n].x | v[n].z; }
                    if (((tag ? a : ~o) & 1)) break;
                    __nanosleep(p.tn.hslp);
                }
                if (ph0 == 0) bar_sync(15, 128);
#pragma unroll
                for (int n = 0; n < 5; n++) sts128(bw + (n < 4 ? 256 * n : 896), v[n].x, v[n].y, v[n].z, v[n].w);
            }
            if (ph != 1) bar_sync(15, 128);
            if (ph == 2 && mt >= nch - 2) break;
#pragma unroll
            for (int e = 0; e < 4; e++) d[0][e] = d[1][e] = d[2][e] = d[3][e] = 0.f;
#pragma unroll 1
            for (int n = 0; n < 1152; n += 384) {
                uint32_t a[12][4], b[24];
#pragma unroll
                for (int e = 0; e < 6; e++) ldm4(S + SM_B + BP * j + 16 * mi + n + 64 * e, b[4 * e], b[4 * e + 1], b[4 * e + 2], b[4 * e + 3]);
                mbar_wait(bar + 8 * min(lane, 2), 0);
                __syncwarp();
#pragma unroll
                for (int e = 0; e < 12; e++) ldm4t(aa + of + 2048 * e, a[e]);
#pragma unroll
                for (int e = 0; e < 12; e++) mma_bf(d[e & 3], a[e][0], a[e][1], a[e][2], a[e][3], b[2 * e], b[2 * e + 1]);
                if (lane == 0) mbar_arrive(min(bar + (B_EMPTY + NRING - B_FULL) * 8, S + 63 * 8));
                bar += 24;
                of = of == 8192 * (NRING - 3) ? 0 : of + 24576;
            }
#pragma unroll
            for (int e = 0; e < 4; e++) d[0][e] = (d[0][e] + d[1][e]) + (d[2][e] + d[3][e]);
            uint32_t k0 = pack_bf(d[0][0], d[0][1]), k1 = pack_bf(d[0][2], d[0][3]);
            if (ph == 0) {
                g0 = pack_bf(silu_half(0.5f * bf_lo(k0)), silu_half(0.5f * bf_hi(k0)));
                g1 = pack_bf(silu_half(0.5f * bf_lo(k1)), silu_half(0.5f * bf_hi(k1)));
                continue;
            }
            k0 = movm(bmul(g0, k0)); k1 = movm(bmul(g1, k1));
            if (ph == 2) {
                const uint32_t ob = mapa(S, (__shfl_sync(~0u, sv.x, g) >> 8) & 7);
                st_async2(ob + SM_FIN + 768 * g + 96 * r + 32 * mt + 8 * t, k0, k1, ob + B_FIN * 8);
                break;
            }
            const uint32_t o = __shfl_xor_sync(~0u, (lane & 1) ? k0 : k1, 1);
            st_rlx2(hp + 64 * (4 * cu + mt) + 31 * (lane & 1) + lane, (((lane & 1) ? o : k0) & ~1u) | tag, (lane & 1) ? k1 : o);
            g0 = g1 = 0x3F803F80u;
        }
        const int l = min(lane, 4 * nch - 1);
        int n = fw;
#pragma unroll 1
        for (uint32_t own = __ballot_sync(~0u, ((sv.x >> 8) & 7) == r) & 255; own; own &= own - 1) {
            if (n-- & 3) continue;
            const int tk = __ffs(own) - 1;
            const uint2 e = lds64(S + SM_SEL + 8 * tk), st = lds64(S + SM_ST + 8 * (e.x & 255));
            const uint32_t ix = e.x, x = lds32(S + SM_RAW + (16 * (ix & 12) + ((ix >> 2) & 60) + (ix & 3)) * PITCH + 4 * l);
            const uint32_t yb = S + SM_CH + YIN + (l >> 2) * CH + 16 * (ix & 0xE0) + 128 * (l & 3) + 16 * (((ix >> 3) ^ ((l >> 1) + (cbase >> 2))) & 3) + 2 * (ix & 7);
            const float sg = 0.5f * sigm(bf_hi(ix));
            const uint32_t hx = pack_bf(fmaf(bf_lo(x), __uint_as_float(st.x), __uint_as_float(st.y)), fmaf(bf_hi(x), __uint_as_float(st.x), __uint_as_float(st.y))), sg2 = pack_bf(sg, sg);
            mbar_wait((S + B_FIN * 8) | (hx & sg2 & p.tn.zero), 0);
            float a[2] = {0.f, 0.f}, b[2] = {0.f, 0.f};
#pragma unroll
            for (int q = 0; q < 8; q++) {
                const uint32_t v = lds32(S + SM_FIN + 768 * tk + 96 * q + 4 * (l & 24) + 8 * (l & 3) + (l & 4));
                a[q & 1] += bf_lo(v); b[q & 1] += bf_hi(v);
            }
            const uint32_t hv = badd(hx, bmul(pack_bf(a[0] + a[1], b[0] + b[1]), sg2)), gt = pack_bf(silu_half(bf_lo(hv)), silu_half(bf_hi(hv)));
            mbar_wait((S + B_Y * 8 + ((ix >> 2) & 56)) | (gt & p.tn.zero), 0);
            *(uint32_t*)(p.out + e.y * D_ + cbase + 2 * l) = bfma(lds16(yb) | (lds16(yb + 64) << 16), gt, x);
        }
        return;
    }

    mbar_wait(S + B_X * 8, 0);
    if (k < nch) {
        const uint32_t cb = S + SM_CH + k * CH, bx = cb + BOX + 16;
        bar_sync(1 + k, 64);
        float u[4][4], v[4][4], w[4][4];
#pragma unroll
        for (int i = 0; i < 4; i++) v[i][0] = v[i][1] = v[i][2] = v[i][3] = w[i][0] = w[i][1] = w[i][2] = w[i][3] = 0.f;
        uint2 T4[10];
        const uint32_t ta = cb + FT + 4 * (g - t);
#pragma unroll
        for (int e = 0; e < 10; e++) T4[e] = lds64(ta + 24 + 32 * e + 4 * (g - t));
        const uint32_t tb = prmt(lds32(cb + FT + 308), 0, g == 2 * t ? 0x4432 : (g == 2 * t + 1 ? 0x3244 : 0x4444));
        const uint32_t a0 = bx + 576 * (j & 1) + 16 * (j >> 1), a4 = a0 + (mi == 1 ? 1152 : (mi == 2 ? 1136 : 0));
        const uint32_t a8 = a0 + 2304 + 1152 * (mi & 1) + 64 * (mi >> 1), at = bx + 4608 + 576 * (mi & 1) + 128 * (mi >> 1) + 16 * j;
        const uint32_t hb = bx + (lane < 2 ? 1152 + 576 * lane : 2896), o = bx + 16 * lane;
        uint32_t xi = cb + xslot(8 + lane, 0), xp = cb + xslot(7 + lane, 0), hs = cb + XX;
#pragma unroll 1
        for (int n = 9; n > 0; n -= 4) {
            {
                const uint4 hv = lds128(hs);
                hs = hb + 496;
                const uint2 v0 = lds64(xp + 8);
                const uint4 v1 = lds128(xp ^ 32), v2 = lds128(xi), v3 = lds128(xi ^ 32);
                xi += 1024; xp += 1024;
                __syncwarp();
                if (lane < 3) sts128(hb - 16, hv.x, hv.y, hv.z, hv.w);
                const uint32_t P[13] = {v0.x, v0.y, v1.x, v1.y, v1.z, v1.w, v2.x, v2.y, v2.z, v2.w, v3.x, v3.y, v3.z};
                uint32_t Q[12], s2[12], s4[10], b3[11], b5[9];
#pragma unroll
                for (int e = 0; e < 12; e++) { Q[e] = prmt(P[e], P[e + 1], 0x5432); s2[e] = hadd(P[e], Q[e]); }
#pragma unroll
                for (int e = 0; e < 11; e++) b3[e] = hadd(Q[e], s2[e + 1]);
#pragma unroll
                for (int e = 0; e < 10; e++) s4[e] = hadd(s2[e], s2[e + 1]);
#pragma unroll
                for (int e = 0; e < 9; e++) b5[e] = hadd(s4[e + 1], P[e + 3]);
                sts128(o, b3[3], b3[4], b3[5], b3[6]);
                sts128(o + 1152, b3[7], b3[8], b3[9], b3[10]);
                sts128(o + 576, b5[0], b5[1], b5[2], b5[3]);
                sts128(o + 1728, b5[4], b5[5], b5[6], b5[7]);
                if (n > 4) {
                    sts128(o + 4608, s2[4], s2[5], s2[6], s2[7]);
                    sts128(o + 5184, s2[8], s2[9], s2[10], s2[11]);
                    sts128(o + 2304, hadd(b3[0], s4[2]), hadd(b3[1], s4[3]), hadd(b3[2], s4[4]), hadd(b3[3], s4[5]));
                    sts128(o + 3456, hadd(b3[4], s4[6]), hadd(b3[5], s4[7]), hadd(b3[6], s4[8]), hadd(b3[7], s4[9]));
                    sts128(o + 4032, hadd(s4[0], b5[1]), hadd(s4[1], b5[2]), hadd(s4[2], b5[3]), hadd(s4[3], b5[4]));
                    sts128(o + 2896, hadd(s4[4], b5[5]), hadd(s4[5], b5[6]), hadd(s4[6], b5[7]), hadd(s4[7], b5[8]));
                }
                __syncwarp();
            }
            uint32_t A[8][4];
#pragma unroll
            for (int e = 0; e < 8; e++) ldm4t(a4 + 64 * e, A[e]);
#pragma unroll
            for (int e = 0; e < 8; e++)
#pragma unroll
                for (int b = 3; b >= e / 2; b--) {
                    const uint2 T = T4[2 * (b - e / 2) + 1 - (e & 1)];
                    if (e == 0) mma_hc(u[b], v[b], A[e][0], A[e][1], A[e][2], A[e][3], T.x, T.y);
                    else mma_h(u[b], A[e][0], A[e][1], A[e][2], A[e][3], T.x, T.y);
                }
            if (n == 9) mbar_wait(S + (B_X + 1) * 8, 0);
#pragma unroll
            for (int e = 0; e < 2; e++)
                stm4t(cb + TAB + 2304 - 256 * n + 512 * e + 16 * lane, pack_h(u[2 * e][0], u[2 * e][1]), pack_h(u[2 * e][2], u[2 * e][3]),
                      pack_h(u[2 * e + 1][0], u[2 * e + 1][1]), pack_h(u[2 * e + 1][2], u[2 * e + 1][3]));
            __syncwarp();
            sts32v(S + SM_PROG + 4 * k, n > 1 ? n : p.tn.tail);
            if (n == 1) break;
            uint32_t C[4][4], E[2][4], T8[16];
#pragma unroll
            for (int e = 0; e < 4; e++) ldm4t(a8 + 128 * e, C[e]);
#pragma unroll
            for (int e = 0; e < 2; e++) ldm4t(at + 256 * e, E[e]);
#pragma unroll
            for (int e = 0; e < 8; e++) T8[e] = lds32(ta + 376 + 32 * (e >> 1) - 16 * (e & 1));
#pragma unroll
            for (int e = 7; e >= 0; e--)
#pragma unroll
                for (int b = 0; b <= e / 2; b++) {
                    const uint2 T = T4[2 * (4 + b - e / 2) + 1 - (e & 1)];
                    if (e == 7) mma_hc(v[b], w[b], A[e][0], A[e][1], A[e][2], A[e][3], T.x, T.y);
                    else mma_h(v[b], A[e][0], A[e][1], A[e][2], A[e][3], T.x, T.y);
                }
#pragma unroll
            for (int e = 3; e >= 0; e--) {
                mma_h8(v[e], E[e >> 1][2 * (e & 1)], E[e >> 1][2 * (e & 1) + 1], tb);
#pragma unroll
                for (int b = 3; b >= e; b--) mma_h(v[b], C[e][0], C[e][1], C[e][2], C[e][3], T8[2 * (b - e)], T8[2 * (b - e) + 1]);
            }
            if (n == 9) {
#pragma unroll
                for (int e = 8; e < 16; e++) T8[e] = lds32(ta + 376 + 32 * (e >> 1) - 16 * (e & 1));
#pragma unroll
                for (int e = 3; e >= 0; e--)
#pragma unroll
                    for (int b = 0; b < 4; b++) mma_h(w[b], C[e][0], C[e][1], C[e][2], C[e][3], T8[2 * (4 + b - e)], T8[2 * (4 + b - e) + 1]);
            }
        }
    }

  {
    int lane;
    asm volatile("mov.u32 %0, %%laneid;" : "=r"(lane));
    const int g = lane >> 2, t = lane & 3, mi = lane >> 3, j = lane & 7, sh = (cbase >> 3) & 1;
    mbar_wait(S + B_SEL * 8, 0);
    if (k < 2 * nch - 4) {
        const int q0 = k & 1, kk = (k & 6) - sh;
        uint32_t xa = S + SM_RAW + (16 * (g & 4) + (g & 3) + 8 * q0) * PITCH + 8 * t + 16 * kk, sa = S + SM_ST + 8 * g + 256 * q0, bar = S + (B_Y + q0) * 8;
        uint32_t ya = S + SM_CH + YIN + ((j >> 2) + kk) * CH + 128 * (j & 2) + 128 * (mi & 1) + 64 * (j & 1) + 16 * ((mi >> 1) ^ (j >> 1)) + 512 * q0;
        uint32_t sk = (unsigned)(kk + (t >> 1)) < (unsigned)nch ? lds32(S + SM_SKIP + 4 * g) >> (4 * q0) : ~0u;
        char* o = (char*)p.out + ((256 * q0 + 32 * r + 4 * (g & 2) + 2 * (g >> 2) + (g & 1)) * D_ + cbase + 8 * kk + 4 * t) * 2;
#pragma unroll 1
        for (int n = 0; n < 4; n++) {
            uint2 x[4];
            uint32_t gt[8], y[2][4];
#pragma unroll
            for (int e = 0; e < 4; e++) {
                x[e] = lds64(xa + (128 * (e & 1) + 2 * (e & 2)) * PITCH);
                const uint2 s = lds64(sa + 64 * e);
                const float a = __uint_as_float(s.x), b = __uint_as_float(s.y);
                gt[2 * e] = pack_bf(silu_half(fmaf(bf_lo(x[e].x), a, b)), silu_half(fmaf(bf_hi(x[e].x), a, b)));
                gt[2 * e + 1] = pack_bf(silu_half(fmaf(bf_lo(x[e].y), a, b)), silu_half(fmaf(bf_hi(x[e].y), a, b)));
            }
            mbar_wait(bar | (((gt[0] | gt[1] | gt[2]) | (gt[3] | gt[4] | gt[5]) | (gt[6] | gt[7])) & p.tn.zero), 0);
            ldm4t(ya, y[0]);
            ldm4t(ya ^ 32, y[1]);
#pragma unroll
            for (int e = 0; e < 4; e++)
                asm volatile("{.reg .pred p; setp.eq.u32 p, %3, 0;\n@p st.global.v2.u32 [%0], {%1, %2};}" ::"l"(o + (8 * (e & 1) + 16 * (e & 2)) * D_),
                             "r"(bfma(y[e >> 1][2 * (e & 1)], gt[2 * e], x[e].x)), "r"(bfma(y[e >> 1][2 * (e & 1) + 1], gt[2 * e + 1], x[e].y)), "r"(sk & (1 << e)) : "memory");
            xa += 16 * PITCH; sa += 512; ya += 1024; bar += 16; sk >>= 8; o += 1024 * D_;
        }
    }
  }
}

typedef CUresult (*EncodeFn)(CUtensorMap*, CUtensorMapDataType, cuuint32_t, void*, const cuuint64_t*, const cuuint64_t*, const cuuint32_t*,
                             const cuuint32_t*, CUtensorMapInterleave, CUtensorMapSwizzle, CUtensorMapL2promotion, CUtensorMapFloatOOBfill);

static void make2d(EncodeFn enc, CUtensorMap* m, const void* base, uint64_t cols, uint64_t rows) {
    cuuint64_t gd[2] = {cols, rows};
    cuuint64_t gs[1] = {cols * 2};
    cuuint32_t bd[2] = {64, 64}, es[2] = {1, 1};
    enc(m, CU_TENSOR_MAP_DATA_TYPE_BFLOAT16, 2, const_cast<void*>(base), gd, gs, bd, es, CU_TENSOR_MAP_INTERLEAVE_NONE, CU_TENSOR_MAP_SWIZZLE_128B,
        CU_TENSOR_MAP_L2_PROMOTION_L2_128B, CU_TENSOR_MAP_FLOAT_OOB_FILL_NONE);
}

static void make5d(EncodeFn enc, CUtensorMap* m, const void* base, uint32_t cols, CUtensorMapSwizzle sw) {
    cuuint64_t gd[5] = {D_, 2, 32, 8, 4};
    cuuint64_t gs[4] = {D_ * 2, D_ * 16, D_ * 512, D_ * 4};
    cuuint32_t bd[5] = {cols, 2, 4, 8, 4}, es[5] = {1, 1, 1, 1, 1};
    enc(m, CU_TENSOR_MAP_DATA_TYPE_BFLOAT16, 5, const_cast<void*>(base), gd, gs, bd, es, CU_TENSOR_MAP_INTERLEAVE_NONE, sw,
        CU_TENSOR_MAP_L2_PROMOTION_NONE, CU_TENSOR_MAP_FLOAT_OOB_FILL_NONE);
}

static Tune g_tune = {2400, 6, 2200, 0, 0, 2, 4, 12, 6000, 100, 700, 0, 0};

static int max_clusters() {
    cudaFuncSetAttribute(fused_kernel, cudaFuncAttributeMaxDynamicSharedMemorySize, SM_TOTAL);
    cudaLaunchConfig_t cfg = {};
    cudaLaunchAttribute at[1];
    at[0].id = cudaLaunchAttributeClusterDimension;
    at[0].val.clusterDim.x = 8; at[0].val.clusterDim.y = 1; at[0].val.clusterDim.z = 1;
    cfg.gridDim = dim3(NCTA); cfg.blockDim = dim3(NTHREADS); cfg.dynamicSmemBytes = SM_TOTAL; cfg.attrs = at; cfg.numAttrs = 1;
    int n = 0;
    if (cudaOccupancyMaxActiveClusters(&n, fused_kernel, &cfg) != cudaSuccess) { cudaGetLastError(); n = 0; }
    return n;
}

static bool launch(void* const* d_in, void* d_out) {
    static EncodeFn enc = nullptr;
    static Scratch* gs = nullptr;
    if (!enc) {
        void* fn = nullptr;
        cudaDriverEntryPointQueryResult qr;
        cudaGetDriverEntryPoint("cuTensorMapEncodeTiled", &fn, cudaEnableDefault, &qr);
        enc = (EncodeFn)fn;
        cudaFuncSetAttribute(fused_kernel, cudaFuncAttributeMaxDynamicSharedMemorySize, SM_TOTAL);
        cudaGetSymbolAddress((void**)&gs, g_s);
    }
    Hot p;
    Maps m;
    auto in = [&](int i) { return (const __nv_bfloat16*)d_in[i]; };
    bool ok = true;
    auto off = [&](const void* q) {
        const long long d = (const char*)q - (const char*)d_in[0];
        ok = ok && d / 256 * 256 == d && (int)(d / 256) == d / 256;
        return (int)(d / 256);
    };
    p.u = in(0); p.are = off(in(1)); p.aim = off(in(2)); p.bre = off(in(3)); p.bim = off(in(4)); p.cre = off(in(5)); p.cim = off(in(6));
    p.logdt = off(in(7)); p.dskip = off(in(8)); p.wr = off(in(10)); p.ep = off(gs->ep);
    if (!ok) return false;
    p.out = (__nv_bfloat16*)d_out;
    p.tn = g_tune;
    p.s = gs;
    make2d(enc, &m.w[0], in(11), F_, D_);
    make2d(enc, &m.w[1], in(12), F_, D_);
    make2d(enc, &m.w[2], in(13), D_, F_);
    make5d(enc, &m.u, in(0), 40, CU_TENSOR_MAP_SWIZZLE_NONE);
    fused_kernel<<<NCTA, NTHREADS, SM_TOTAL>>>(p, m);
    return true;
}

}

namespace v2 {

constexpr int L_ = 2048, D_ = 576, F_ = 4608;
constexpr int NDOWN = 72, NMAIN = 128, NCTA = 132, NTHREADS = 512;
constexpr int SPIN_LIMIT = 1 << 16;
constexpr uint32_t SLOT_FREE = 0x7FFFABCDu;

constexpr int SM_PART = 544;
constexpr int SM_RED = SM_PART;
constexpr int SM_STA = 2080;
constexpr int SM_ONES = 2176;
constexpr int SM_KINF = 2192;
constexpr int SM_RP = 2272;
constexpr int SM_XS = 2704;
constexpr int KR_STRIDE = 1296;
constexpr int SM_X0 = 12080, X0_STRIDE = 4512, X0_ODD = 2240;
constexpr int SM_KT = 30128, KT_STRIDE = 3584, KT_P4 = 2144, KT_P8 = 2896;
constexpr int SM_FAR = 44544, FAR_STRIDE = 11328;
constexpr int FB5 = 0, FB3 = 3328, FB9E = 6656, FB9O = 7824, FB7E = 8992, FB7O = 10160;
constexpr int SM_ROWS = SM_FAR, ROW_STRIDE = 1168;
constexpr int SM_STG = SM_FAR + 19968;
constexpr int KG_SCR = 3072;
constexpr int SM_EX = 89856;
constexpr int EX_KT = SM_EX + X0_STRIDE, EX_FAR = EX_KT + KT_STRIDE, EX_HAND = 109312;
constexpr int SM_W_DOWN = 90112, SM_W_BIG = 121856, STAGE = 6144;
constexpr int SM_W_LAST = 12288;
constexpr int SM_TOTAL = 232448;
constexpr int SM_EPOCH = 2528, SM_SKIP = 2536;
static_assert(SM_STG + 8 * KG_SCR <= SM_EX && SM_STG % 128 == 0 && EX_HAND % 128 == 0 && EX_FAR + FAR_STRIDE <= EX_HAND && EX_HAND + 12288 <= SM_W_BIG, "scratch");

enum { B_ROWS = 0, B_KG, B_X0, B_X1, B_BOX  , B_TAB, B_EM = 6, B_SP = 10, B_OUT = 14, B_H = 15, B_RED = 16, B_TAB1 = 17, B_XS = 18, B_GX = 19, B_YIN = 22, B_P1 = 26, B_FD, B_GU = 28, B_W = 34, B_COUNT = 58 };

struct Tune { short f_start, f_t3, w2, w2b, w3, t_xs, t_svc, t_marg, f_t2, w1, zero, pad; };

struct Scratch {
    uint32_t x[144 * 4096];
    uint32_t y[128 * 4608];
    uint32_t h[2][F_ * 4];
    uint32_t key[L_];
    uint32_t stat[L_];
    uint32_t sel[4][32];
    uint32_t cnt[17 * 32];
};
__device__ __align__(1024) Scratch g_s;

struct Hot {
    const __nv_bfloat16* u;
    Scratch* s;
    const __nv_bfloat16 *wr, *are, *aim, *bre, *bim, *cre, *cim, *logdt;
    Tune tn;
    const __nv_bfloat16 *dskip, *pwg, *pwu, *pwd;
    __nv_bfloat16* out;
};
struct Maps { CUtensorMap wg, wu, wd; };

__device__ __forceinline__ uint32_t smem_u32(const void* p) { return (uint32_t)__cvta_generic_to_shared(p); }
__device__ __forceinline__ void mbar_init(uint32_t b, int c) { asm volatile("mbarrier.init.shared::cta.b64 [%0], %1;" ::"r"(b), "r"(c) : "memory"); }
__device__ __forceinline__ void mbar_expect(uint32_t b, int bytes) { asm volatile("mbarrier.arrive.expect_tx.shared::cta.b64 _, [%0], %1;" ::"r"(b), "r"(bytes) : "memory"); }
__device__ __forceinline__ void mbar_arrive(uint32_t b) { asm volatile("mbarrier.arrive.shared::cta.b64 _, [%0];" ::"r"(b) : "memory"); }
__device__ __forceinline__ bool elect() { uint32_t d; asm volatile("{.reg .pred p; elect.sync _|p, 0xffffffff; selp.u32 %0,1,0,p;}" : "=r"(d)); return d; }
__device__ __forceinline__ bool mbar_test(uint32_t b, int par) {
    uint32_t d;
    asm volatile("{.reg .pred p; mbarrier.test_wait.parity.shared::cta.b64 p, [%1], %2; selp.u32 %0,1,0,p;}" : "=r"(d) : "r"(b), "r"(par) : "memory");
    return d;
}
#define WAIT_LOOP(ins) "{\n.reg .pred p;\n.reg .u32 n;\nmov.u32 n, 0;\nLW:\n" ins " p, [%0], %1;\n@p bra LD;\nadd.u32 n, n, 1;\nsetp.lt.u32 p, n, 16384;\n@p bra LW;\nLD:\n}"
__device__ __forceinline__ void mbar_wait(uint32_t b, int par) { asm volatile(WAIT_LOOP("mbarrier.try_wait.parity.shared::cta.b64")::"r"(b), "r"(par) : "memory"); }
__device__ __forceinline__ uint32_t mapa(uint32_t a, uint32_t rank) { uint32_t d; asm("mapa.shared::cluster.u32 %0, %1, %2;" : "=r"(d) : "r"(a), "r"(rank)); return d; }
__device__ __forceinline__ void bulk_g2s(uint32_t dst, const void* src, int bytes, uint32_t bar) {
    asm volatile("cp.async.bulk.shared::cluster.global.mbarrier::complete_tx::bytes [%0], [%1], %2, [%3];" ::"r"(dst), "l"(src), "r"(bytes), "r"(bar) : "memory");
}
__device__ __forceinline__ void tma2d(uint32_t dst, const CUtensorMap* m, int c0, int c1, uint32_t bar) {
    asm volatile("cp.async.bulk.tensor.2d.shared::cluster.global.mbarrier::complete_tx::bytes [%0], [%1, {%3, %4}], [%2];" ::"r"(dst), "l"(m), "r"(bar), "r"(c0), "r"(c1) : "memory");
}
__device__ __forceinline__ void pf_tmap(const CUtensorMap* m) { asm volatile("prefetch.tensormap [%0];" ::"l"(m) : "memory"); }
__device__ __forceinline__ void bar_sync(int id, int n) { asm volatile("bar.sync %0, %1;" ::"r"(id), "r"(n) : "memory"); }
__device__ __forceinline__ uint4 ld_rlx4(const void* p) { uint4 v; asm volatile("ld.relaxed.gpu.global.v4.u32 {%0,%1,%2,%3}, [%4];" : "=r"(v.x), "=r"(v.y), "=r"(v.z), "=r"(v.w) : "l"(p) : "memory"); return v; }
__device__ __forceinline__ uint32_t ld_rlx(const void* p) { uint32_t v; asm volatile("ld.relaxed.gpu.global.u32 %0, [%1];" : "=r"(v) : "l"(p) : "memory"); return v; }
__device__ __forceinline__ void st_rlx(void* p, uint32_t v) { asm volatile("st.relaxed.gpu.global.u32 [%0], %1;" ::"l"(p), "r"(v) : "memory"); }
__device__ __forceinline__ uint32_t lds32(uint32_t a) { uint32_t v; asm volatile("ld.shared.u32 %0, [%1];" : "=r"(v) : "r"(a) : "memory"); return v; }
__device__ __forceinline__ uint32_t lds32v(uint32_t a) { uint32_t v; asm volatile("ld.volatile.shared.u32 %0, [%1];" : "=r"(v) : "r"(a) : "memory"); return v; }
__device__ __forceinline__ uint4 lds128v(uint32_t a) { uint4 v; asm volatile("ld.volatile.shared.v4.u32 {%0,%1,%2,%3}, [%4];" : "=r"(v.x), "=r"(v.y), "=r"(v.z), "=r"(v.w) : "r"(a) : "memory"); return v; }
__device__ __forceinline__ uint32_t lds16(uint32_t a) { uint16_t v; asm volatile("ld.shared.u16 %0, [%1];" : "=h"(v) : "r"(a) : "memory"); return v; }
__device__ __forceinline__ uint2 lds64(uint32_t a) { uint2 v; asm volatile("ld.shared.v2.u32 {%0,%1}, [%2];" : "=r"(v.x), "=r"(v.y) : "r"(a) : "memory"); return v; }
__device__ __forceinline__ uint4 lds128(uint32_t a) { uint4 v; asm volatile("ld.shared.v4.u32 {%0,%1,%2,%3}, [%4];" : "=r"(v.x), "=r"(v.y), "=r"(v.z), "=r"(v.w) : "r"(a) : "memory"); return v; }
__device__ __forceinline__ void sts16(uint32_t a, uint32_t v) { asm volatile("st.shared.u16 [%0], %1;" ::"r"(a), "h"((uint16_t)v) : "memory"); }
__device__ __forceinline__ void sts32(uint32_t a, uint32_t v) { asm volatile("st.shared.u32 [%0], %1;" ::"r"(a), "r"(v) : "memory"); }
__device__ __forceinline__ void sts64(uint32_t a, uint32_t x, uint32_t y) { asm volatile("st.shared.v2.u32 [%0], {%1,%2};" ::"r"(a), "r"(x), "r"(y) : "memory"); }
__device__ __forceinline__ void sts128(uint32_t a, uint32_t x, uint32_t y, uint32_t z, uint32_t w) { asm volatile("st.shared.v4.u32 [%0], {%1,%2,%3,%4};" ::"r"(a), "r"(x), "r"(y), "r"(z), "r"(w) : "memory"); }
__device__ __forceinline__ void st_async32(uint32_t a, uint32_t v, uint32_t bar) {
    asm volatile("st.async.shared::cluster.mbarrier::complete_tx::bytes.b32 [%0], %1, [%2];" ::"r"(a), "r"(v), "r"(bar) : "memory");
}
__device__ __forceinline__ void ldm4(uint32_t a, uint32_t& r0, uint32_t& r1, uint32_t& r2, uint32_t& r3) {
    asm volatile("ldmatrix.sync.aligned.m8n8.x4.shared.b16 {%0,%1,%2,%3}, [%4];" : "=r"(r0), "=r"(r1), "=r"(r2), "=r"(r3) : "r"(a) : "memory");
}
__device__ __forceinline__ void ldm4t(uint32_t a, uint32_t& r0, uint32_t& r1, uint32_t& r2, uint32_t& r3) {
    asm volatile("ldmatrix.sync.aligned.m8n8.x4.trans.shared.b16 {%0,%1,%2,%3}, [%4];" : "=r"(r0), "=r"(r1), "=r"(r2), "=r"(r3) : "r"(a) : "memory");
}
__device__ __forceinline__ void ldm2(uint32_t a, uint32_t& r0, uint32_t& r1) {
    asm volatile("ldmatrix.sync.aligned.m8n8.x2.shared.b16 {%0,%1}, [%2];" : "=r"(r0), "=r"(r1) : "r"(a) : "memory");
}
__device__ __forceinline__ void stm4(uint32_t a, uint32_t r0, uint32_t r1, uint32_t r2, uint32_t r3) {
    asm volatile("stmatrix.sync.aligned.m8n8.x4.shared.b16 [%0], {%1,%2,%3,%4};" ::"r"(a), "r"(r0), "r"(r1), "r"(r2), "r"(r3) : "memory");
}
__device__ __forceinline__ void mma_bf(float& c0, float& c1, float& c2, float& c3, uint32_t a0, uint32_t a1, uint32_t a2, uint32_t a3, uint32_t b0, uint32_t b1) {
    asm volatile("mma.sync.aligned.m16n8k16.row.col.f32.bf16.bf16.f32 {%0,%1,%2,%3},{%4,%5,%6,%7},{%8,%9},{%0,%1,%2,%3};"
                 : "+f"(c0), "+f"(c1), "+f"(c2), "+f"(c3) : "r"(a0), "r"(a1), "r"(a2), "r"(a3), "r"(b0), "r"(b1));
}
__device__ __forceinline__ void mma_bf(float (&c)[4], uint32_t a0, uint32_t a1, uint32_t a2, uint32_t a3, uint32_t b0, uint32_t b1) { mma_bf(c[0], c[1], c[2], c[3], a0, a1, a2, a3, b0, b1); }
__device__ __forceinline__ void mma_h(float (&c)[4], uint32_t a0, uint32_t a1, uint32_t a2, uint32_t a3, uint32_t b0, uint32_t b1) {
    asm volatile("mma.sync.aligned.m16n8k16.row.col.f32.f16.f16.f32 {%0,%1,%2,%3},{%4,%5,%6,%7},{%8,%9},{%0,%1,%2,%3};"
                 : "+f"(c[0]), "+f"(c[1]), "+f"(c[2]), "+f"(c[3]) : "r"(a0), "r"(a1), "r"(a2), "r"(a3), "r"(b0), "r"(b1));
}
__device__ __forceinline__ void mma_bf8(float (&c)[4], uint32_t a0, uint32_t a1, uint32_t b0) {
    asm volatile("mma.sync.aligned.m16n8k8.row.col.f32.bf16.bf16.f32 {%0,%1,%2,%3},{%4,%5},{%6},{%0,%1,%2,%3};"
                 : "+f"(c[0]), "+f"(c[1]), "+f"(c[2]), "+f"(c[3]) : "r"(a0), "r"(a1), "r"(b0));
}
__device__ __forceinline__ uint32_t pack_bf(float lo, float hi) { uint32_t r; asm("cvt.rn.bf16x2.f32 %0, %1, %2;" : "=r"(r) : "f"(hi), "f"(lo)); return r; }
__device__ __forceinline__ uint32_t pack_h(float lo, float hi) { uint32_t r; asm("cvt.rn.f16x2.f32 %0, %1, %2;" : "=r"(r) : "f"(hi), "f"(lo)); return r; }
__device__ __forceinline__ float bf_lo(uint32_t w) { return __uint_as_float(w << 16); }
__device__ __forceinline__ float bf_hi(uint32_t w) { return __uint_as_float(w & 0xFFFF0000u); }
__device__ __forceinline__ float bf_round(float x) { return bf_lo(pack_bf(x, 0.f)); }
__device__ __forceinline__ uint32_t badd(uint32_t a, uint32_t b) { uint32_t r; asm("add.rn.bf16x2 %0, %1, %2;" : "=r"(r) : "r"(a), "r"(b)); return r; }
__device__ __forceinline__ uint32_t bsub(uint32_t a, uint32_t b) { uint32_t r; asm("sub.rn.bf16x2 %0, %1, %2;" : "=r"(r) : "r"(a), "r"(b)); return r; }
__device__ __forceinline__ uint32_t bmul(uint32_t a, uint32_t b) { uint32_t r; asm("mul.rn.bf16x2 %0, %1, %2;" : "=r"(r) : "r"(a), "r"(b)); return r; }
__device__ __forceinline__ uint32_t bfma(uint32_t a, uint32_t b, uint32_t c) { uint32_t r; asm("fma.rn.bf16x2 %0, %1, %2, %3;" : "=r"(r) : "r"(a), "r"(b), "r"(c)); return r; }
__device__ __forceinline__ uint32_t prmt(uint32_t a, uint32_t b, uint32_t s) { uint32_t r; asm("prmt.b32 %0, %1, %2, %3;" : "=r"(r) : "r"(a), "r"(b), "r"(s)); return r; }
__device__ __forceinline__ float ex2f(float x) { float r; asm("ex2.approx.ftz.f32 %0, %1;" : "=f"(r) : "f"(x)); return r; }
__device__ __forceinline__ float rcpf(float x) { float r; asm("rcp.approx.ftz.f32 %0, %1;" : "=f"(r) : "f"(x)); return r; }
__device__ __forceinline__ float silu_f(float x) { return x * rcpf(1.f + ex2f(-1.4426950408889634f * x)); }
__device__ __forceinline__ uint32_t norm2(uint32_t x, uint32_t m, uint32_t hi, uint32_t lo) { uint32_t d = bsub(x, m); return bfma(d, hi, bmul(d, lo)); }
__device__ __forceinline__ uint32_t clk32() { uint32_t c; asm volatile("mov.u32 %0, %%clock;" : "=r"(c)); return c; }
__device__ __forceinline__ void spin_until(uint32_t t0, int dt) {
#pragma unroll 1
    while ((int)(clk32() - t0) < dt) __nanosleep(32);
}
__device__ __forceinline__ float sqrt_ap(float x) { float r; asm("sqrt.approx.ftz.f32 %0, %1;" : "=f"(r) : "f"(x)); return r; }

__device__ __forceinline__ void cp16(uint32_t dst, const void* src) { asm volatile("cp.async.cg.shared.global [%0], [%1], 16;" ::"r"(dst), "l"(src) : "memory"); }
__device__ __forceinline__ void pf_l2(const void* p) { asm volatile("cp.async.bulk.prefetch.L2.global [%0], 16;" ::"l"(p) : "memory"); }
__device__ __forceinline__ void bulk_s2g(void* dst, uint32_t src, int bytes) {
    asm volatile("cp.async.bulk.global.shared::cta.bulk_group [%0], [%1], %2;" ::"l"(dst), "r"(src), "r"(bytes) : "memory");
}
__device__ __forceinline__ uint32_t ld_acq(const void* p) { uint32_t v; asm volatile("ld.acquire.gpu.global.u32 %0, [%1];" : "=r"(v) : "l"(p) : "memory"); return v; }
__device__ __forceinline__ void red_add(void* p) { asm volatile("red.relaxed.gpu.global.add.u32 [%0], 1;" ::"l"(p) : "memory"); }
__device__ __forceinline__ void fence_async() { asm volatile("fence.proxy.async.shared::cta;" ::: "memory"); }
__device__ __forceinline__ void fence_async_g() { asm volatile("fence.proxy.async.global;" ::: "memory"); }
__device__ __forceinline__ void red_rel(void* p) { asm volatile("red.release.gpu.global.add.u32 [%0], 1;" ::"l"(p) : "memory"); }
__device__ __forceinline__ void wait_count(const uint32_t* p, uint32_t want) {
#pragma unroll 1
    for (int it = 0; it < SPIN_LIMIT && ld_rlx(p) != want; it++) __nanosleep(20);
}
__device__ __forceinline__ uint32_t ld_stat(const uint32_t* p, uint32_t tag) {
    uint32_t v = 0;
#pragma unroll 1
    for (int it = 0; it < SPIN_LIMIT; it++) {
        v = ld_rlx(p);
        if ((v >> 31) == tag) break;
    }
    return v & 0x7FFFFFFFu;
}
__device__ __forceinline__ uint32_t hadd(uint32_t a, uint32_t b) { uint32_t r; asm("add.rn.f16x2 %0, %1, %2;" : "=r"(r) : "r"(a), "r"(b)); return r; }
__device__ __forceinline__ float h_lo(uint32_t w) { return __half2float(__ushort_as_half((unsigned short)w)); }
__device__ __forceinline__ float h_hi(uint32_t w) { return __half2float(__ushort_as_half((unsigned short)(w >> 16))); }
__device__ __forceinline__ uint32_t x0_chunk(uint32_t xb, int c) { return xb + ((c & 1) ? X0_ODD + 120 : 128) + 8 * c; }

struct cf { float x, y; };
__device__ __forceinline__ cf cmul(cf a, cf b) { return {a.x * b.x - a.y * b.y, a.x * b.y + a.y * b.x}; }
__device__ __forceinline__ cf csq(cf a) { return {a.x * a.x - a.y * a.y, (a.x + a.x) * a.y}; }
__device__ __forceinline__ cf cpow_direct(float zr2, float zi, float l) {
    const float mag = ex2f(zr2 * l), th = zi * l;
    return {mag * __cosf(th), mag * __sinf(th)};
}
__device__ __forceinline__ __half2 as_h2(uint32_t v) { return *reinterpret_cast<__half2*>(&v); }
__device__ __forceinline__ uint32_t as_u32(__half2 v) { return *reinterpret_cast<uint32_t*>(&v); }
struct hm { uint32_t v, s; };
__device__ __forceinline__ hm mk_hm(cf a) {
    const uint32_t v = pack_h(a.x, a.y);
    return {v, prmt(v, v, 0x1032) ^ 0x8000u};
}
__device__ __forceinline__ uint32_t hcmul(uint32_t x, hm y) {
    const __half2 xx = as_h2(x);
    return as_u32(__hfma2(__high2half2(xx), as_h2(y.s), __hmul2(__low2half2(xx), as_h2(y.v))));
}

struct KParams { uint32_t are, aim, bre, bim, cre, cim, ldt; };
__device__ __forceinline__ KParams kgen_load(const Hot& p, int ch, int half, int lane) {
    const uint32_t po = ch * 64 + half * 32 + lane;
    KParams k;
    k.are = __ldg((const uint32_t*)p.are + po); k.aim = __ldg((const uint32_t*)p.aim + po);
    k.bre = __ldg((const uint32_t*)p.bre + po); k.bim = __ldg((const uint32_t*)p.bim + po);
    k.cre = __ldg((const uint32_t*)p.cre + po); k.cim = __ldg((const uint32_t*)p.cim + po);
    k.ldt = __ldg((const uint16_t*)p.logdt + ch + (lane & p.tn.zero));
    return k;
}

__device__ __forceinline__ void kgen(KParams kp, uint32_t scr, uint32_t os, int c0, int c1, uint32_t pause) {
    const int lane = threadIdx.x & 31;
    const float dt = bf_round(ex2f(bf_lo(kp.ldt) * 1.4426950408889634f));
    const cf w0 = cmul({bf_lo(kp.cre), bf_lo(kp.cim)}, {dt * bf_lo(kp.bre), dt * bf_lo(kp.bim)});
    const cf w1 = cmul({bf_hi(kp.cre), bf_hi(kp.cim)}, {dt * bf_hi(kp.bre), dt * bf_hi(kp.bim)});
    uint32_t eb = __reduce_max_sync(~0u, __float_as_uint(fmaxf(fmaxf(fabsf(w0.x), fabsf(w0.y)), fmaxf(fabsf(w1.x), fabsf(w1.y))))) & 0x7F800000u;
    eb = min(max(eb, 0x00800000u), 0x7E800000u);
    const float sc = __uint_as_float(0x7F000000u - eb);
    float k0 = c0 ? 0.f : w0.x + w1.x;
#pragma unroll
    for (int o = 16; o > 0; o >>= 1) k0 += __shfl_xor_sync(~0u, k0, o);
    float d[5][4];
#pragma unroll
    for (int i = 0; i < 5; i++) d[i][0] = d[i][1] = d[i][2] = d[i][3] = 0.f;
    const int mi = lane >> 3, j = lane & 7;
    const uint32_t st0 = scr + mi * 128 + ((j ^ mi) << 4), st1 = st0 ^ 64;
    const uint32_t la = scr + (lane & 15) * 128 + (((lane >> 4) ^ j) << 4), lb = scr + j * 128 + ((mi ^ j) << 4);
    auto st = [&](int row, uint32_t a, uint32_t b, uint32_t c, uint32_t e) { stm4(((row & 4) ? st1 : st0) + row * 128, a, b, c, e); };
#pragma unroll 1
    for (int c = c0; c < c1; c++) {
        if (c > c0 && pause) mbar_wait(pause, 0);
        const float zr2 = dt * (c ? bf_hi(kp.are) : bf_lo(kp.are)) * 1.4426950408889634f;
        const float zi = dt * (c ? bf_hi(kp.aim) : bf_lo(kp.aim));
        const cf w = {(c ? w1.x : w0.x) * sc, (c ? w1.y : w0.y) * sc};
        const cf a1 = cpow_direct(zr2, zi, 1.f), a256 = cpow_direct(zr2, zi, 256.f);
        uint32_t a[4][4];
        {
            const cf a16 = cpow_direct(-zr2, zi, -16.f);
            const cf a32 = csq(a16), a48 = cmul(a32, a16), a64 = csq(a32), a128 = csq(a64), a192 = cmul(a128, a64);
            const uint32_t p1 = pack_h(a16.x, a16.y), p2 = pack_h(a32.x, a32.y), p3 = pack_h(a48.x, a48.y);
            const hm q1 = mk_hm(a64), q2 = mk_hm(a128), q3 = mk_hm(a192);
            __syncwarp();
            st(0, 0x00003C00u, p1, p2, p3);
            st(4, q1.v, hcmul(p1, q1), hcmul(p2, q1), hcmul(p3, q1));
            st(8, q2.v, hcmul(p1, q2), hcmul(p2, q2), hcmul(p3, q2));
            st(12, q3.v, hcmul(p1, q3), hcmul(p2, q3), hcmul(p3, q3));
            __syncwarp();
#pragma unroll
            for (int k = 0; k < 4; k++) ldm4(la ^ (k * 32), a[k][0], a[k][1], a[k][2], a[k][3]);
        }
        auto tile = [&](int T, int row) {
#pragma unroll
            for (int kp2 = 0; kp2 < 2; kp2++) {
                uint32_t b0, b1, b2, b3;
                ldm4((lb ^ (kp2 * 64)) + row * 128, b0, b1, b2, b3);
                mma_h(d[T], a[2 * kp2][0], a[2 * kp2][1], a[2 * kp2][2], a[2 * kp2][3], b0, b1);
                mma_h(d[T], a[2 * kp2 + 1][0], a[2 * kp2 + 1][1], a[2 * kp2 + 1][2], a[2 * kp2 + 1][3], b2, b3);
            }
        };
        const cf a2 = csq(a1), a4 = csq(a2), a8 = csq(a4), a12 = cmul(a8, a4);
        const cf u1 = cmul(w, a1), u2 = cmul(w, a2), u3 = cmul(u2, a1), u4 = cmul(w, a4);
        uint32_t v[16];
        v[0] = pack_h(u1.x, u1.y); v[1] = pack_h(u2.x, u2.y); v[2] = pack_h(u3.x, u3.y); v[3] = pack_h(u4.x, u4.y);
        const hm m4 = mk_hm(a4), m8 = mk_hm(a8), m12 = mk_hm(a12);
#pragma unroll
        for (int i = 0; i < 4; i++) { v[4 + i] = hcmul(v[i], m4); v[8 + i] = hcmul(v[i], m8); v[12 + i] = hcmul(v[i], m12); }
        const hm m256 = mk_hm(a256);
        __syncwarp();
#pragma unroll
        for (int i = 0; i < 4; i++) st(4 * i, v[4 * i], v[4 * i + 1], v[4 * i + 2], v[4 * i + 3]);
        st(16, hcmul(v[1], m256), hcmul(v[3], m256), hcmul(v[5], m256), hcmul(v[7], m256));
        st(20, hcmul(v[9], m256), hcmul(v[11], m256), hcmul(v[13], m256), hcmul(v[15], m256));
        __syncwarp();
        tile(0, 0); tile(1, 8); tile(2, 16);
        const cf a512 = csq(a256), a768 = cmul(a512, a256), a1024 = csq(a512);
        const cf a1280 = cmul(a1024, a256), a1536 = csq(a768), a1792 = cmul(a1024, a768);
        const hm m512 = mk_hm(a512), m768 = mk_hm(a768);
        const hm n0 = mk_hm(a1024), n1 = mk_hm(a1280), n2 = mk_hm(a1536), n3 = mk_hm(a1792);
        __syncwarp();
        st(0, hcmul(v[3], m512), hcmul(v[7], m512), hcmul(v[11], m512), hcmul(v[15], m512));
        st(4, hcmul(v[3], m768), hcmul(v[7], m768), hcmul(v[11], m768), hcmul(v[15], m768));
        st(8, hcmul(v[7], n0), hcmul(v[15], n0), hcmul(v[7], n1), hcmul(v[15], n1));
        st(12, hcmul(v[7], n2), hcmul(v[15], n2), hcmul(v[7], n3), hcmul(v[15], n3));
        __syncwarp();
        tile(3, 0); tile(4, 8);
    }
    __syncwarp();
#pragma unroll
    for (int i = 0; i < 5; i++) sts128(os + i * 512 + lane * 16, __float_as_uint(d[i][0]), __float_as_uint(d[i][1]), __float_as_uint(d[i][2]), __float_as_uint(d[i][3]));
    sts64(os + 2560, eb, __float_as_uint(k0));
}

__device__ __forceinline__ void ktables(uint32_t os, int ostep, int np, uint32_t kr, uint32_t kt, uint32_t kinf, int part) {
    const int lane = threadIdx.x & 31, g = lane >> 2, t = lane & 3;
    uint32_t eb = 0;
    float k0 = 0.f, f[4];
#pragma unroll
    for (int q = 0; q < 4; q++) {
        uint2 v = make_uint2(0u, 0u);
        if (q < np) v = lds64(os + q * ostep + 2560);
        eb = max(eb, v.x);
        k0 += __uint_as_float(v.y);
        f[q] = __uint_as_float(v.x);
    }
    const float rs = __uint_as_float(0x7F000000u - eb);
#pragma unroll
    for (int q = 0; q < 4; q++) f[q] *= rs;
#pragma unroll 1
    for (int i = (part & 1) ? 0 : 2; i < ((part & 2) ? 5 : 3); i++) {
        float a0 = 0.f, a1 = 0.f, a2 = 0.f, a3 = 0.f;
        uint4 v[4];
#pragma unroll
        for (int q = 0; q < 4; q++) {
            v[q] = make_uint4(0u, 0u, 0u, 0u);
            if (q < np) v[q] = lds128(os + q * ostep + i * 512 + lane * 16);
        }
#pragma unroll
        for (int q = 0; q < 4; q++) { a0 += __uint_as_float(v[q].x) * f[q]; a1 += __uint_as_float(v[q].y) * f[q]; a2 += __uint_as_float(v[q].z) * f[q]; a3 += __uint_as_float(v[q].w) * f[q]; }
        const int sg = 32 >> max(i - 1, 0);
        const uint32_t o = kr + 4 + (i < 2 ? 16 * i : 256 * i) + sg * g + (i < 3 ? 8 : 128) * (t >> 1) + (i < 4 ? 4 : 64) * (t & 1);
        sts32(o, pack_h(a0, a1));
        sts32(o + 8 * sg, pack_h(a2, a3));
    }
    sts32(kr, pack_h(0.f, k0 * rs));
    __syncwarp();
    if (part & 1) {
        uint32_t w0[4], w1[4], a[2], b[2];
#pragma unroll
        for (int r = 0; r < 4; r++) { w0[r] = lds32(kr + 4 * lane + 128 * r); w1[r] = lds32(kr + 4 * lane + 128 * r + 4); }
#pragma unroll
        for (int r = 0; r < 2; r++) { a[r] = lds32(kr + 512 + 4 * lane + 128 * r); b[r] = lds32(kr + 516 + 4 * lane + 128 * r); }
#pragma unroll
        for (int r = 0; r < 4; r++) sts64(kt + 8 * lane + 256 * r + 32, prmt(w0[r], w0[r], 0x1032), prmt(w0[r], w1[r], 0x3254));
        if (lane == 31) b[1] = pack_h(h_lo(b[1]) - h_hi(b[1]), 0.f);
#pragma unroll
        for (int r = 0; r < 2; r++)
            sts128(kt + 4 * 264 + 16 * lane + 512 * r, prmt(a[r], a[r], (r == 0 && lane == 0) ? 0x1032 : 0x3232), prmt(a[r], a[r], 0x3232), prmt(a[r], b[r], 0x3254), prmt(b[r], b[r], 0x1032));
        if (lane < 24) sts32(kt + 4 * (lane < 8 ? lane : 512 + lane), 0u);
    }
    if (part & 2) {
        const uint32_t k512 = lds16(kr + 2 * 385), k1024 = lds16(kr + 2 * 513);
        if (lane == 0) {
            sts128(kinf, eb, __float_as_uint(h_lo(k512)), k1024, 0u);
            sts16(kr + 2 * 512, pack_h(h_lo(lds16(kr + 2 * 512)) - h_lo(k1024), 0.f));
        }
#pragma unroll
        for (int r = 0; r < 3; r++)
            if (r < 2 || lane < 26) sts128(kt + KT_P4 + 16 * lane + 512 * r, 0u, 0u, 0u, 0u);
        __syncwarp();
        uint32_t x0[5], x1[5], y0[5], y1[5];
#pragma unroll
        for (int r = 0; r < 5; r++) {
            const int m = min(126 + lane + 32 * r, 256);
            x0[r] = lds16(kr + 2 * (257 + m)); x1[r] = lds16(kr + 2 * (259 + m)); y0[r] = lds16(kr + 2 * (385 + m)); y1[r] = lds16(kr + 2 * (387 + m));
        }
#pragma unroll
        for (int r = 0; r < 5; r++) {
            const int m = 126 + lane + 32 * r;
            if (m < 128) x0[r] = y0[r] = 0;
            if (m > 253) x1[r] = 0;
            if (m > 254) y1[r] = 0;
            if (m < 256) sts32(kt + KT_P4 + 4 * (((m - 96) & ~3) | ((m & 1) << 1) | ((m >> 1) & 1)), x0[r] | (x1[r] << 16));
            if (m < 257) sts32(kt + KT_P8 + 4 * (m - 96), y0[r] | (y1[r] << 16));
        }
    }
    __syncwarp();
}

__device__ __forceinline__ void mma_hc(float (&d)[4], const float (&c)[4], uint32_t a0, uint32_t a1, uint32_t a2, uint32_t a3, uint32_t b0, uint32_t b1) {
    asm volatile("mma.sync.aligned.m16n8k16.row.col.f32.f16.f16.f32 {%0,%1,%2,%3},{%4,%5,%6,%7},{%8,%9},{%10,%11,%12,%13};"
                 : "=f"(d[0]), "=f"(d[1]), "=f"(d[2]), "=f"(d[3]) : "r"(a0), "r"(a1), "r"(a2), "r"(a3), "r"(b0), "r"(b1), "f"(c[0]), "f"(c[1]), "f"(c[2]), "f"(c[3]));
}
template <int Q0, int Q1>
__device__ __forceinline__ void sweep_steps(float (&w)[5][4], const uint32_t (&R)[66], uint32_t xa, uint32_t (&x)[5], uint32_t z) {
#pragma unroll
    for (int q = Q0; q <= Q1; q++) {
        uint32_t n0, n1;
        ldm2(xa + 16 * (q + 1), n0, n1);
        const uint32_t a2 = x[0] | z, a3 = x[1] | z;
#pragma unroll
        for (int j = 0; j < 4; j++) {
            const int s = 8 * j + 8 - q;
            if (q == 1) mma_hc(w[j], w[j + 1], x[1], x[2], a2, a3, R[2 * s], R[2 * s + 1]);
            else mma_h(w[j], x[1], x[2], a2, a3, R[2 * s], R[2 * s + 1]);
        }
        if (q == 8) {
            const float zero[4] = {0.f, 0.f, 0.f, 0.f};
            mma_hc(w[4], zero, x[1], x[2], a2, a3, R[64], R[65]);
        }
        x[0] = x[2]; x[1] = x[3]; x[2] = x[4]; x[3] = n0; x[4] = n1;
    }
}

__device__ __forceinline__ void box_round(uint32_t xb, uint32_t fa, int rho, int lane) {
    if (rho == 6) {
        const int a = lane >> 3, j = lane & 7;
        sts128(fa + 3328 * (lane >> 4) + 16 * ((lane & 15) < 15 ? (lane & 15) : 207), 0u, 0u, 0u, 0u);
        sts128(fa + FB9E + 1168 * a + 16 * (j < 7 ? j : 71 + (a & 1)), 0u, 0u, 0u, 0u);
        __syncwarp();
    }
    const int c = rho < 6 ? 32 * rho + lane : -1;
    const uint4 pv = lds128(x0_chunk(xb, c - 1)), ow = lds128(x0_chunk(xb, c));
    const uint2 nx = lds64(x0_chunk(xb, c + 1));
    const uint32_t P[9] = {pv.y, pv.z, pv.w, ow.x, ow.y, ow.z, ow.w, nx.x, nx.y};
    uint32_t Q[8], b3[6], b5[4];
#pragma unroll
    for (int k = 0; k < 8; k++) Q[k] = prmt(P[k], P[k + 1], 0x5432);
#pragma unroll
    for (int k = 0; k < 6; k++) b3[k] = hadd(hadd(Q[k], Q[k + 1]), P[k + 1]);
#pragma unroll
    for (int k = 0; k < 4; k++) b5[k] = hadd(b3[k + 2], hadd(P[k + 2], P[k + 4]));
    sts128(fa + FB5 + 240 + 16 * c, b5[0], b5[1], b5[2], b5[3]);
    sts128(fa + FB3 + 240 + 16 * c, b3[0], b3[1], b3[2], b3[3]);
    if (rho < 4 || rho == 6) {
        uint32_t b7[4], b9[4];
#pragma unroll
        for (int k = 0; k < 4; k++) {
            b7[k] = hadd(b5[k], hadd(Q[k + 1], Q[k + 4]));
            b9[k] = hadd(b7[k], hadd(P[k + 1], P[k + 5]));
        }
        const uint32_t ad = fa + ((c & 1) ? FB9O + 120 : FB9E + 112) + 8 * c;
        sts128(ad, b9[0], b9[1], b9[2], b9[3]);
        sts128(ad + (FB7E - FB9E), b7[0], b7[1], b7[2], b7[3]);
    }
}

__global__ void __cluster_dims__(2, 1, 1) __launch_bounds__(NTHREADS, 1) fused_kernel(const Hot p, const __grid_constant__ Maps m) {
    extern __shared__ __align__(1024) char smem[];
    const uint32_t t0 = clk32();
    const int tid = (threadIdx.x + 32 * 0) & (NTHREADS - 1), lane = tid & 31, warp = __shfl_sync(~0u, tid >> 5, 0), bid = blockIdx.x;
    const uint32_t S = smem_u32(smem), z = (uint32_t)p.tn.zero;
    const bool down = bid < NDOWN, rowcta = bid < NMAIN, big = rowcta && !down;
    const int xd = rowcta ? bid : 142 + ((bid - NMAIN) >> 1);
    const int slot = warp < 8 ? (warp & 3) : 4;
    const bool has = warp < 8 ? (rowcta || (slot >> 1) == (bid & 1)) : (big && warp < 12);
    const int ch = slot < 4 ? 4 * xd + slot : 512 + bid - NDOWN;
    KParams kp;
    if (has) kp = kgen_load(p, ch, warp < 8 ? warp >> 2 : (warp >> 1) & 1, lane);
    if (elect()) {
#pragma unroll 1
        for (int i = warp; i < B_COUNT; i += 16) {
            const uint32_t c = i < 16 ? (uint32_t)((big ? 0x1411115555412290ull : 0x1411114444412290ull) >> (4 * i)) & 15 : 1;
            mbar_init(S + i * 8, c ? c : NTHREADS);
        }
        asm volatile("fence.mbarrier_init.release.cluster;" ::: "memory");
    }
    if (rowcta) {
#pragma unroll 1
        for (int i = tid; i < 1224; i += NTHREADS)
            cp16(S + SM_ROWS + 16 * (i + min((i * 911) >> 16, 16)), i < 1152 ? (const uint4*)p.u + bid * 1152 + i : (const uint4*)p.wr + (i - 1152));
    }
    if (tid >= 256 && tid < 336) {
        const int i = tid - 256;
        if (i < 64 || big) sts128(S + (i < 64 ? SM_X0 + (i >> 4) * X0_STRIDE : SM_EX) + ((i & 8) ? X0_ODD : 0) + 16 * (i & 7), 0u, 0u, 0u, 0u);
    }
    if (tid == 447) sts128(S + SM_ONES, 0x3F803F80u, 0x3F803F80u, 0x3F803F80u, 0x3F803F80u);
    __syncthreads();
    if (rowcta) asm volatile("cp.async.mbarrier.arrive.noinc.shared::cta.b64 [%0];" ::"r"(S + B_ROWS * 8) : "memory");
    if (warp == 15 && lane < 4) mbar_expect(S + (lane < 3 ? B_GX + lane : B_RED) * 8, 256);
    asm volatile("barrier.cluster.arrive.relaxed.aligned;" ::: "memory");
    const int g = lane >> 2, t = lane & 3, mi = lane >> 3, j = lane & 7;
    const uint32_t SW = S + (down ? SM_W_DOWN : SM_W_BIG);
    const int pr = bid >> 1, r = bid & 1, nsl = pr >= 54 ? 3 : 2, sl0 = pr < 54 ? 2 * pr : 3 * pr - 54;

    if (warp == 12) {
        if (elect()) {
            const int ng = 6 * nsl, ns = down ? 24 : ng;
            const CUtensorMap* mg = r ? &m.wu : &m.wg;
            pf_tmap(mg);
            if (down) pf_tmap(&m.wd);
            const uint32_t epoch = ld_rlx(&p.s->cnt[16 * 32]) + 1;
            spin_until(t0, p.tn.f_start);
            int done = 0;
#pragma unroll 1
            for (int s = 0; s < ns; s++) {
                if (s == ng) spin_until(t0, p.tn.f_t3);
                #pragma unroll 1
                for (int it = 0; it < SPIN_LIMIT; it++) {
                    const int w = s >= ng ? p.tn.w3 : ((int)(clk32() - t0) < p.tn.f_t2 ? p.tn.w1 : (nsl == 3 ? p.tn.w2b : p.tn.w2));
                    if (s - done < w) break;
                    if (mbar_test(S + (B_W + done) * 8, 0)) done++;
                    else __nanosleep(32);
                }
                const uint32_t bar = S + (B_W + s) * 8;
                uint32_t dst = SW + s * STAGE;
                if (s == 23) { mbar_wait(S + B_EM * 8, 0); fence_async(); dst = S + SM_W_LAST; }
                mbar_expect(bar, STAGE);
                const int u = (s * 43) >> 8;
                if (s < ng) tma2d(dst, mg, 32 * (sl0 + u), 96 * (s - 6 * u), bar);
                else tma2d(dst, &m.wd, 16 * pr, r * 2304 + 192 * (s - 12), bar);
            }
            if (rowcta) {
                mbar_wait(S + B_FD * 8, 0);
                fence_async();
#pragma unroll 1
                for (int q = 0; q < 4; q++) {
                    wait_count(&p.s->cnt[(8 + q) * 32], epoch * (uint32_t)D_);
                    fence_async_g();
                    mbar_expect(S + (B_YIN + q) * 8, 4608);
                    bulk_g2s(S + SM_STG + q * 4608, p.s->y + (32 * q + (bid >> 2)) * 4608 + (bid & 3) * 1152, 4608, S + (B_YIN + q) * 8);
                }
            }
        }
        return;
    }

    uint32_t epoch = 0;
    if (warp >= 8 || !rowcta) epoch = ld_rlx(&p.s->cnt[16 * 32] + (lane & z)) + 1;
    const uint32_t tag = epoch & 1;
    const int hw = warp < 12 ? warp - 8 : warp - 9;

    if (rowcta && warp >= 8 && warp < 15) {
        const uint32_t ad = S + SM_ROWS + (lane & 15) * ROW_STRIDE + 192 * hw + 16 * (lane >> 4);
        uint32_t wd = j ? S + SM_ROWS + 16 * ROW_STRIDE + 192 * hw + 16 * mi : S + SM_ONES;
        const uint32_t wstep = j ? 64 : 0, ones = 0x3F803F80u | z;
        float d1[4] = {0, 0, 0, 0}, d2[4] = {0, 0, 0, 0}, d3[4] = {0, 0, 0, 0}, d4[4] = {0, 0, 0, 0};
        mbar_wait(S + B_ROWS * 8, 0);
#pragma unroll
        for (int kk = 0; kk < 3; kk++) {
            uint32_t w[4];
            ldm4(wd, w[0], w[1], w[2], w[3]);
            wd += wstep;
#pragma unroll
            for (int e = 0; e < 2; e++) {
                uint32_t a0, a1, a2, a3;
                ldm4(ad + 64 * kk + 32 * e, a0, a1, a2, a3);
                mma_bf(d1, a0, a1, a2, a3, w[2 * e], w[2 * e + 1]);
                mma_bf(d2, a0, a1, a2, a3, a0, a2);
                mma_bf(d3, a0, a1, a2, a3, a1, a3);
                mma_bf(d4, ones, ones ^ z, ones + z, ones - z, w[2 * e], w[2 * e + 1]);
            }
        }
        float* part = (float*)(smem + SM_PART + hw * 256) + g * 4;
        if (t == 0) {
            *(float2*)part = make_float2(d1[0], d1[1]);
            *(float2*)(part + 32) = make_float2(d1[2], d1[3]);
            part[3] = d4[1];
            part[35] = d4[1];
        }
        if (t == (g >> 1)) {
            part[2] = (g & 1) ? d2[1] : d2[0];
            part[34] = (g & 1) ? d3[3] : d3[2];
        }
        bar_sync(1, 192);
        if (hw == 0 && lane < 16) {
            float4 s = *(const float4*)(smem + SM_PART + lane * 16);
#pragma unroll
            for (int w = 1; w < 6; w++) {
                const float4 v = *(const float4*)(smem + SM_PART + w * 256 + lane * 16);
                s.x += v.x; s.y += v.y; s.z += v.z; s.w += v.w;
            }
            const float mean = s.x * (1.f / 576.f);
            const float var = fmaxf(s.z * (1.f / 576.f) - mean * mean, 0.f);
            const uint32_t mm = pack_bf(mean, mean);
            const float mu = bf_lo(mm), sd = bf_round(sqrt_ap(bf_round(bf_round(var) + 1e-5f))), ri = rcpf(sd);
            const uint32_t hi = pack_bf(ri, ri);
            const float rl = ri - bf_lo(hi);
            sts16(S + SM_STA + 2 * lane, mm); sts16(S + SM_STA + 32 + 2 * lane, hi); sts16(S + SM_STA + 64 + 2 * lane, pack_bf(rl, rl));
            const uint32_t rb = pack_bf(0.f, (s.y - mu * s.w) * ri);
            const int row = bid * 16 + lane;
            p.s->stat[row] = (mm & 0xFFFFu) | __float_as_uint(sd) | (tag << 31);
            p.s->key[row] = ((rb ^ (((int)rb >> 31) | 0x80000000u)) & 0xFFFF0000u) | (tag << 15) | (2047 - row);
        }
        bar_sync(1, 192);
        if (tid == 256) mbar_arrive(S + B_P1 * 8);
        {
            const uint2 sm = lds64(S + SM_STA + 8 * t), sh = lds64(S + SM_STA + 32 + 8 * t), sl = lds64(S + SM_STA + 64 + 8 * t);
            const uint32_t at = S + SM_ROWS + (4 * (j >> 1) + (j & 1) + 2 * (mi & 1)) * ROW_STRIDE + 32 * hw + 16 * (mi >> 1);
            uint2* dst = (uint2*)p.s->x + (4 * hw + (g >> 2)) * 2048 + bid * 16 + (g & 3) * 4 + t;
            uint32_t r4[6][4];
#pragma unroll
            for (int n = 5; n >= 0; n--) ldm4t(at + 192 * n, r4[n][0], r4[n][1], r4[n][2], r4[n][3]);
#pragma unroll
            for (int n = 5; n >= 0; n--) {
                uint32_t o[4];
#pragma unroll
                for (int e = 0; e < 4; e++) {
                    const uint32_t v = (e & 1) ? norm2(r4[n][e], sm.y, sh.y, sl.y) : norm2(r4[n][e], sm.x, sh.x, sl.x);
                    o[e] = pack_h(bf_lo(v), bf_hi(v));
                }
                dst[n * 49152] = make_uint2((o[0] & ~1u) | tag, o[1]);
                dst[n * 49152 + 4096] = make_uint2((o[2] & ~1u) | tag, o[3]);
            }
        }
        bar_sync(1, 192);
    }

    if (has) {
        asm volatile("" : "+r"(kp.ldt), "+r"(kp.are), "+r"(kp.aim), "+r"(kp.bre), "+r"(kp.bim), "+r"(kp.cre), "+r"(kp.cim));

        const uint32_t scr = warp < 8 ? S + SM_STG + warp * KG_SCR : S + EX_HAND + hw * KG_SCR;
        kgen(kp, scr, warp < 8 ? scr : S + EX_FAR + hw * 2576, warp < 8 ? 0 : warp & 1, warp < 8 ? 2 : (warp & 1) + 1, rowcta ? S + B_P1 * 8 : 0);
        if (warp >= 8) { __syncwarp(); if (lane == 0) mbar_arrive(S + B_TAB * 8); }
    }
    if (warp < 8 || warp == 15) {
        if (warp < 8 ? has : big) {
            if (warp < 8) bar_sync(4 + slot, 64); else mbar_wait(S + B_TAB * 8, 0);
            ktables(warp < 8 ? S + SM_STG + slot * KG_SCR : S + EX_FAR, warp < 8 ? 4 * KG_SCR : 2576, warp < 8 ? 2 : 4, S + SM_XS + slot * KR_STRIDE,
                    S + (warp < 8 ? SM_KT + slot * KT_STRIDE : EX_KT), S + SM_KINF + slot * 16, warp < 8 ? 1 + (warp >> 2) : 3);
        }
        if (lane == 0) { mbar_arrive(S + B_KG * 8); if (warp == 15) mbar_arrive(S + B_TAB1 * 8); }
    }

    if (!rowcta && warp < 8 && !has) {
        const int w4 = (warp >> 2) * 2 + (warp & 1), i = 32 * w4 + lane;
#pragma unroll 1
        for (int pass = 1; pass < 2; pass++) {
        uint4 k[4];
        if (pass) spin_until(t0, p.tn.t_svc - 1500);
#pragma unroll 1
        for (int it = 0; it < SPIN_LIMIT; it++) {
            if (!pass) {
#pragma unroll
                for (int q = 0; q < 4; q++) k[q] = make_uint4(16 * i + 4 * q, 16 * i + 4 * q + 1, 16 * i + 4 * q + 2, 16 * i + 4 * q + 3);
                break;
            }
            uint32_t bad = 0;
#pragma unroll
            for (int q = 0; q < 4; q++) k[q] = ld_rlx4(&p.s->key[4 * i + 512 * q]);
#pragma unroll
            for (int q = 0; q < 4; q++) bad |= tag ? ~(k[q].x & k[q].y & k[q].z & k[q].w) : (k[q].x | k[q].y | k[q].z | k[q].w);
            if (!(bad & 0x8000u)) break;
            __nanosleep(100);
        }
        const uint32_t sc = S + SM_XS + ((bid & 1) ? 0 : 2) * KR_STRIDE;
        auto pk = [](uint32_t v) { return ((v >> 16) << 11) | (v & 2047u); };
        auto gt = [](uint32_t a, uint32_t b) { return (b - a) >> 31; };
        uint32_t mx = 0;
#pragma unroll
        for (int q = 0; q < 4; q++) {
            k[q] = make_uint4(pk(k[q].x), pk(k[q].y), pk(k[q].z), pk(k[q].w));
            mx = max(max(mx, max(k[q].x, k[q].y)), max(k[q].z, k[q].w));
        }
        bar_sync(1, 128);
        sts32(sc + 4 * i, mx);
        if (i == 0) sts32(sc + 1024, 0u);
        bar_sync(1, 128);
        int rank;
        {
            int c[8] = {0, 0, 0, 0, 0, 0, 0, 0};
#pragma unroll 1
            for (int q = 0; q < 32; q += 4) {
                uint4 v[4];
#pragma unroll
                for (int e = 0; e < 4; e++) v[e] = lds128(sc + 16 * (q + e));
#pragma unroll
                for (int e = 0; e < 4; e++) {
                    c[(2 * e) & 7] += gt(v[e].x, mx); c[(2 * e + 1) & 7] += gt(v[e].y, mx);
                    c[(2 * e + 4) & 7] += gt(v[e].z, mx); c[(2 * e + 5) & 7] += gt(v[e].w, mx);
                }
            }
            rank = ((c[0] + c[1]) + (c[2] + c[3])) + ((c[4] + c[5]) + (c[6] + c[7]));
        }
        if (rank == 7) sts32(sc + 1028, mx);
        bar_sync(1, 128);
        if (rank < 8) {
            const uint32_t lb = lds32(sc + 1028);
            int cq[4];
#pragma unroll
            for (int q = 0; q < 4; q++) cq[q] = (gt(lb, k[q].x) + gt(lb, k[q].y)) + (gt(lb, k[q].z) + gt(lb, k[q].w));
            const int c = 16 - ((cq[0] + cq[1]) + (cq[2] + cq[3]));
            uint32_t pos;
            asm volatile("atom.shared.add.u32 %0, [%1], %2;" : "=r"(pos) : "r"(sc + 1024), "r"(c) : "memory");
            pos = sc + 512 + 4 * pos;
#pragma unroll
            for (int q = 0; q < 4; q++) {
                if (k[q].x >= lb) { sts32(pos, k[q].x); pos += 4; }
                if (k[q].y >= lb) { sts32(pos, k[q].y); pos += 4; }
                if (k[q].z >= lb) { sts32(pos, k[q].z); pos += 4; }
                if (k[q].w >= lb) { sts32(pos, k[q].w); pos += 4; }
            }
        }
        bar_sync(1, 128);
        const int n = lds32(sc + 1024);
        if (i < n) {
            const uint32_t mine = lds32(sc + 512 + 4 * i);
            rank = 0;
#pragma unroll 1
            for (int q = 0; q < n; q += 4) {
                const uint4 v = lds128(sc + 512 + 4 * q);
                rank += ((v.x > mine) + (q + 1 < n && v.y > mine)) + ((q + 2 < n && v.z > mine) + (q + 3 < n && v.w > mine));
            }
            const uint32_t k32 = (mine >> 11) << 16, rb = (k32 ^ ((~(int)k32 >> 31) | 0x80000000u)) & 0xFFFF0000u;
            if (rank < 8 && pass) st_rlx(&p.s->sel[bid - NMAIN][rank], (2047 - (mine & 2047)) | (tag << 15) | (pack_bf(rcpf(1.f + ex2f(-1.4426950408889634f * __uint_as_float(rb))), 0.f) << 16));
        }
        }
    }

    if (warp == 13 || warp == 14) {
        const int i = tid - 416;
        if (i == 0) sts32(S + SM_EPOCH, tag);
        if (rowcta) {
            if (p.tn.t_marg <= 600) {
                const uint32_t back = ld_rlx(p.s->x + 2 * ((4 * hw + 2 + (g >> 2)) * 2048 + bid * 16 + (g & 3) * 4 + t));
                if (back == 0xFFFFFFFFu) __nanosleep(20);
            }
            spin_until(clk32(), p.tn.t_marg);
        } else {
            spin_until(t0, p.tn.t_svc);
        }
        const uint4* xa = (const uint4*)p.s->x + xd * 1024 + i;
        const int e = bid - NDOWN;
        const uint4* xe = (const uint4*)p.s->x + (128 + (e >> 2)) * 1024 + (i >> 1) * 8 + (e & 3) * 2 + (i & 1);
        const uint32_t da = S + SM_X0 + ((i >> 1) & 3) * X0_STRIDE + ((i & 1) ? X0_ODD : 0) + 128 + 16 * (i >> 3);
        const uint32_t de = S + SM_EX + ((i & 1) ? X0_ODD : 0) + 128 + 16 * (i >> 1);
        uint4 v[2][10];
        auto fetch = [&](int half) {
#pragma unroll
            for (int k = 0; k < 10; k++) {
                v[half][k].x = v[half][k].z = tag;
                if (k < 8 || big) v[half][k] = ld_rlx4(k < 8 ? xa + 512 * half + 64 * k : xe + 512 * half + 256 * (k - 8));
            }
        };
        fetch(0); fetch(1);
#pragma unroll
        for (int half = 0; half < 2; half++) {
#pragma unroll 1
            for (int it = 0; it < SPIN_LIMIT; it++) {
                uint32_t bad = 0;
#pragma unroll
                for (int k = 0; k < 10; k++) bad |= (v[half][k].x ^ tag) | (v[half][k].z ^ tag);
                if (!(bad & 1)) break;
                __nanosleep(60);
                fetch(half);
            }
#pragma unroll
            for (int k = 0; k < 10; k++)
                if (k < 8 || big) sts128(k < 8 ? da + 1024 * half + 128 * k : de + 1024 * half + 512 * (k - 8), v[half][k].x & ~1u, v[half][k].y, v[half][k].z & ~1u, v[half][k].w);
            __syncwarp();
            if (lane == 0) mbar_arrive(S + (B_X0 + half) * 8);
        }
    }

    if (warp < 12) {
        const bool cw = warp >= 8;
        if (has) {
            const uint32_t xb = S + (cw ? SM_EX : SM_X0 + slot * X0_STRIDE), kt = S + (cw ? EX_KT : SM_KT + slot * KT_STRIDE);
            const int g0 = cw ? warp - 8 : 0, g1 = cw ? warp - 7 : 4;
            const uint32_t park = (cw ? S + EX_HAND + g0 * 2048 : kt) + lane * 16;
            if (cw) mbar_wait(S + B_TAB1 * 8, 0);
            const uint4 ki = lds128(S + SM_KINF + slot * 16);
            const float inv = __uint_as_float(ki.x);
            if (warp >= 4) {
                const uint32_t fa = S + (cw ? EX_FAR : SM_FAR + slot * FAR_STRIDE);
                mbar_wait(S + (cw ? B_X1 : B_X0) * 8, 0);
                mbar_wait(S + B_KG * 8, 0);
#pragma unroll 1
                for (int rho = cw ? g0 : 0; rho < (cw ? 7 : 4); rho += cw ? 4 : 1) box_round(xb, fa, (!cw && rho == 3) ? 6 : rho, lane);
                if (cw) bar_sync(2, 128); else __syncwarp();
                const int dd = g - 2 * t, gf = g0 ? g0 : 1;
                const uint32_t tb0 = dd == -5 ? ki.z : (dd == -4 ? ki.z << 16 : 0u), tb1 = dd == 3 ? ki.z : (dd == 4 ? ki.z << 16 : 0u);
                uint32_t tad = xb + (mi == 1 ? 144 : mi == 2 ? 128 : X0_ODD + 128) + 16 * j + 512 * gf - 1024;
                uint32_t ad8 = fa + (mi == 0 ? FB9E : mi == 1 ? FB7O : mi == 2 ? FB9O + 16 : FB7E) + 112 - 16 * j + 512 * gf - 768;
                uint32_t ad4 = fa + ((mi & 1) ? FB3 : FB5) + 240 + 16 * (8 * (mi >> 1) - j) + 1024 * gf - 640;
                const uint32_t p4 = kt + KT_P4 + 16 * (g + t), p8 = kt + KT_P8 + 8 * (g + 2 * t);
#pragma unroll 1
                for (int grp = gf; grp < g1; grp++) {
                    float a[4][4], e[2][4], o[2][4];
#pragma unroll
                    for (int k = 0; k < 4; k++) a[0][k] = a[1][k] = a[2][k] = a[3][k] = e[0][k] = e[1][k] = o[0][k] = o[1][k] = 0.f;
                    {
                        if (!cw && grp == 2) {
                            mbar_wait(S + B_X1 * 8, 0);
#pragma unroll 1
                            for (int rho = 3; rho < 6; rho++) box_round(xb, fa, rho, lane);
                            __syncwarp();
                        }
                        {
                            uint4 A4[10];
#pragma unroll
                            for (int s = 0; s < 10; s++) A4[s] = lds128(p4 + 64 * s);
                            auto s4 = [&](int m) {
                                uint32_t b[4];
                                ldm4t(ad4 - 256 * m, b[0], b[1], b[2], b[3]);
#pragma unroll
                                for (int h = 1; h >= 0; h--)
#pragma unroll
                                    for (int i = 0; i < 4; i++) {
                                        const int s = 2 * m - 2 + 2 * i + (1 - h), k = m + (i & 2);
                                        if (k <= 5 && k >= ((i & 1) ? 0 : 1) && !((i & 1) && k == 5)) mma_h(a[i], A4[s >= 0 && s < 10 ? s : 0].x, A4[s >= 0 && s < 10 ? s : 0].y, A4[s >= 0 && s < 10 ? s : 0].z, A4[s >= 0 && s < 10 ? s : 0].w, b[2 * h], b[2 * h + 1]);
                                    }
                            };
                            auto tap = [&](int i) {
                                uint32_t b[4];
                                ldm4(tad + 128 * i, b[0], b[1], b[2], b[3]);
                                mma_h(a[i], b[0], b[1], b[2], b[3], tb1, tb0);
                            };
                            s4(1); s4(0); s4(2); s4(-1); tap(3); s4(-2);
                            if (grp >= 2) { s4(3); tap(0); s4(4); tap(1); s4(5); tap(2); }
                        }
                        {
                            uint32_t A8[9][4];
#pragma unroll
                            for (int k = 0; k < 9; k++) { A8[k][0] = lds32(p8 + 64 * k); A8[k][1] = lds32(p8 + 64 * k + 64); A8[k][2] = lds32(p8 + 64 * k + 4); A8[k][3] = lds32(p8 + 64 * k + 68); }
                            auto s8 = [&](int m) {
                                uint32_t b[4];
                                ldm4t(ad8 - 128 * m, b[0], b[1], b[2], b[3]);
                                mma_h(e[1], A8[m + 2][0], A8[m + 2][1], A8[m + 2][2], A8[m + 2][3], b[0], b[1]);
                                mma_h(o[1], A8[m + 2][0], A8[m + 2][1], A8[m + 2][2], A8[m + 2][3], b[2], b[3]);
                                if (m >= 0) {
                                    mma_h(e[0], A8[m >= 0 ? m : 0][0], A8[m >= 0 ? m : 0][1], A8[m >= 0 ? m : 0][2], A8[m >= 0 ? m : 0][3], b[0], b[1]);
                                    mma_h(o[0], A8[m >= 0 ? m : 0][0], A8[m >= 0 ? m : 0][1], A8[m >= 0 ? m : 0][2], A8[m >= 0 ? m : 0][3], b[2], b[3]);
                                }
                            };
                            s8(-2);
                            if (grp >= 2) {
                                s8(-1); s8(0); s8(1); s8(2);
                                if (grp >= 3) { s8(3); s8(4); s8(5); s8(6); }
                            }
                        }
                    }
                    tad += 512; ad8 += 512; ad4 += 1024;
#pragma unroll
                    for (int pp = 0; pp < 2; pp++) {
                        if (!cw) {
#pragma unroll 1
                            for (int it = 0; it < SPIN_LIMIT && !__all_sync(~0u, lds32v(park + (2 * pp + 1) * 512) == SLOT_FREE); it++) __nanosleep(32);
                        }
#pragma unroll
                        for (int i = 0; i < 2; i++)
                            sts128(park + (2 * pp + i) * 512, __float_as_uint((a[2 * pp + i][0] + e[pp][2 * i]) * inv), __float_as_uint((a[2 * pp + i][1] + e[pp][2 * i + 1]) * inv),
                                   __float_as_uint((a[2 * pp + i][2] + o[pp][2 * i]) * inv), __float_as_uint((a[2 * pp + i][3] + o[pp][2 * i + 1]) * inv));
                    }
                }
            }
            if ((warp & 12) != 4) {
                uint32_t R[66], x[5];
#pragma unroll
                for (int i = 0; i < 66; i++) R[i] = lds32(kt + 4 * (8 + g - 2 * t) + 32 * i);
                float w[5][4];
#pragma unroll
                for (int i = 0; i < 5; i++) w[i][0] = w[i][1] = w[i][2] = w[i][3] = 0.f;
                uint32_t xa = xb + ((lane & 8) ? X0_ODD + 16 : 16) + 16 * j + 512 * g0;
                uint2* yo = (uint2*)p.s->y + (32 * g0 + g) * 2304 + ch * 4 + t;
                mbar_wait(S + B_X0 * 8, 0);
                const uint32_t ytag = lds32(S + SM_EPOCH);
                if (g0 == 0) {
                    const uint32_t x01 = lds32(xb + 128);
                    const float c0 = lane == 31 ? __uint_as_float(ki.y) * inv * h_lo(x01) : 0.f, c1 = lane == 31 ? c0 + __uint_as_float(ki.y) * inv * h_hi(x01) : 0.f;
                    __syncwarp();
#pragma unroll
                    for (int i = 0; i < 4; i++) sts128(park + i * 512, 0u, 0u, i == 3 ? __float_as_uint(c0) : 0u, i == 3 ? __float_as_uint(c1) : 0u);
                }
                ldm2(xa - 16, x[1], x[0]);
                ldm2(xa, x[1], x[2]);
                ldm2(xa + 16, x[3], x[4]);
                uint32_t zz = z, pk = park;
                float sc = inv;
                const bool direct = g0 == 0;
                uint32_t dir = direct;
                asm volatile("" : "+r"(pk));
#pragma unroll 1
                for (int gq = g0; gq < g1; gq++) {
                    uint32_t pa = pk;
#pragma unroll 1
                    for (int n = 4; n > 0; n--) {
                        asm volatile("" : "+r"(zz), "+f"(sc), "+r"(pa), "+r"(dir));
                        sweep_steps<1, 5>(w, R, xa, x, zz);
                        uint4 v = lds128v(pa | (x[4] & zz));
                        sweep_steps<6, 8>(w, R, xa, x, zz);
                        xa += 128;
                        if (__any_sync(~0u, v.x == SLOT_FREE)) {
#pragma unroll 1
                            for (int it = 0; it < SPIN_LIMIT; it++) {
                                v = lds128v(pa);
                                if (!__any_sync(~0u, v.x == SLOT_FREE)) break;
                            }
                        }
                        const float y0 = fmaf(w[0][0], sc, __uint_as_float(v.x)), y1 = fmaf(w[0][1], sc, __uint_as_float(v.y));
                        const float y2 = fmaf(w[0][2], sc, __uint_as_float(v.z)), y3 = fmaf(w[0][3], sc, __uint_as_float(v.w));
                        if (dir) {
                            *yo = make_uint2((pack_bf(y0, y1) & ~1u) | ytag, pack_bf(y2, y3));
                            sts32(pa, SLOT_FREE);
                        } else {
                            sts128(pa, __float_as_uint(y0), __float_as_uint(y1), __float_as_uint(y2), __float_as_uint(y3));
                        }
                        yo += 18432;
                        pa += 512;
                    }
                    if (direct && lane == 0) red_add(&p.s->cnt[(8 + gq) * 32]);
                }
                __syncwarp();
                if (lane == 0) mbar_arrive(S + (direct ? B_EM : B_SP + g0) * 8);
                if (cw && g0 < 3) {
                    mbar_wait(S + (B_SP + g0 + 1) * 8, 0);
#pragma unroll
                    for (int i = 0; i < 4; i++) {
                        const uint4 v = lds128(park + 2048 + i * 512);
                        yo[i * 18432] = make_uint2((pack_bf(fmaf(w[i + 1][0], inv, __uint_as_float(v.x)), fmaf(w[i + 1][1], inv, __uint_as_float(v.y))) & ~1u) | ytag,
                                                   pack_bf(fmaf(w[i + 1][2], inv, __uint_as_float(v.z)), fmaf(w[i + 1][3], inv, __uint_as_float(v.w))));
                    }
                    if (lane == 0) red_add(&p.s->cnt[(8 + g0 + 1) * 32]);
                }
            }
        }
        if (rowcta && (warp & 12) == 4) {
            bar_sync(10, 128);
            const int i = tid - 128, rb0 = 16 * (bid >> 2), c0 = 144 * (bid & 3);
            if (i == 0) mbar_arrive(S + B_FD * 8);
#pragma unroll 3
            for (int v = i; v < 1152; v += 128) {
                const int row = (v * 3641) >> 16, vv = v - 18 * row;
                cp16(S + SM_ROWS + row * 304 + 16 * vv, (const uint4*)(p.u + (size_t)(512 * (row >> 4) + rb0 + (row & 15)) * D_ + c0) + vv);
            }
            if (i < 64) {
                const uint32_t sw = ld_stat(&p.s->stat[512 * (i >> 4) + rb0 + (i & 15)], lds32(S + SM_EPOCH));
                const float ri = rcpf(bf_hi(sw));
                const uint32_t hi = pack_bf(ri, ri);
                const float rl = ri - bf_lo(hi);
                sts128(S + SM_KT + KT_P4 + 16 * i, prmt(sw, sw, 0x1010), hi, pack_bf(rl, rl), 0u);
            }
            asm volatile("cp.async.wait_all;" ::: "memory");
            __syncwarp();
            if (lane == 0) mbar_arrive(S + B_OUT * 8);
        }
        if (!rowcta) return;

        const int rb0 = 16 * (bid >> 2), c0 = 144 * (bid & 3);
        mbar_wait(S + B_OUT * 8, 0);
        mbar_wait(S + B_XS * 8, 0);
        const uint32_t otag = lds32(S + SM_EPOCH) * 0x00010001u;
        const uint2 skip = lds64(S + SM_SKIP);
        const int pi_g = (g & 1) + 8 * ((g >> 1) & 1) + 2 * (g >> 2), pi_j = (j & 1) + 8 * ((j >> 1) & 1) + 2 * (j >> 2);
#pragma unroll 1
        for (int un = warp; un < 36; un += 12) {
            const int q = (un * 57) >> 9, cu = un - 9 * q;
            const uint32_t rw = S + SM_ROWS + 16 * q * 304 + 32 * cu;
            const uint32_t ad = rw + (pi_j + 4 * (mi & 1)) * 304 + 16 * (mi >> 1);
            const uint32_t dk0 = __ldg((const uint32_t*)p.dskip + (c0 >> 1) + 8 * cu + t), dk1 = __ldg((const uint32_t*)p.dskip + (c0 >> 1) + 8 * cu + 4 + t);
            const uint4 sa = lds128(S + SM_KT + KT_P4 + 16 * (16 * q + pi_g)), sb = lds128(S + SM_KT + KT_P4 + 16 * (16 * q + 4 + pi_g));
            uint32_t x[4], tt[4], gt[4], y[4];
            ldm4(ad, x[0], x[1], x[2], x[3]);
#pragma unroll
            for (int e = 0; e < 4; e++) {
                const uint4 s = (e & 1) ? sb : sa;
                const uint32_t xn = norm2(x[e], s.x, s.y, s.z);
                tt[e] = bmul(xn, e < 2 ? dk0 : dk1);
                gt[e] = pack_bf(silu_f(bf_lo(xn)), silu_f(bf_hi(xn)));
            }
            mbar_wait(S + (B_YIN + q) * 8, 0);
            const uint32_t yb = S + SM_STG + q * 4608 + 512 * cu;
#pragma unroll 1
            for (int it = 0; it < SPIN_LIMIT; it++) {
                ldm4t(yb + (8 * (mi >> 1) + j) * 32 + 16 * (mi & 1), y[0], y[1], y[2], y[3]);
                const uint32_t bad = ((y[0] ^ otag) | (y[1] ^ otag) | (y[2] ^ otag) | (y[3] ^ otag)) & 0x00010001u;
                if (!__any_sync(~0u, (g & 3) == 0 && bad)) break;
                const uint4 v = ld_rlx4((const uint4*)(p.s->y + (32 * q + (bid >> 2)) * 4608 + (bid & 3) * 1152 + 128 * cu) + lane);
                __syncwarp();
                sts128(yb + 16 * lane, v.x, v.y, v.z, v.w);
                __syncwarp();
            }
#pragma unroll
            for (int e = 0; e < 4; e++) y[e] = badd(x[e], bmul(badd(y[e], tt[e]), gt[e]));
            stm4(ad, y[0], y[1], y[2], y[3]);
            __syncwarp();
            const int row = lane >> 1;
            const uint4 o = lds128(rw + row * 304 + 16 * (lane & 1));
            if (!((((q & 2) ? skip.y : skip.x) >> (16 * (q & 1) + row)) & 1))
                *((uint4*)(p.out + (size_t)(512 * q + rb0 + row) * D_ + c0 + 16 * cu) + (lane & 1)) = o;
        }
        return;
    }

    {
        const int fw = warp - 13;
        if (fw < nsl) {
            st_rlx(&p.s->h[tag ^ 1][(32 * (sl0 + fw) + 16 * r) * 4 + lane], 0u);
            st_rlx(&p.s->h[tag ^ 1][(32 * (sl0 + fw) + 16 * r) * 4 + 32 + lane], 0u);
        }
        if (fw == 2) {
            spin_until(t0, p.tn.t_xs);
            uint32_t sv = 0;
#pragma unroll 1
            for (int it = 0; it < SPIN_LIMIT; it++) {
                sv = ld_rlx(&p.s->sel[bid & 3][j]);
                if (__all_sync(~0u, ((sv >> 15) & 1) == tag)) break;
                __nanosleep(40);
            }
            mbar_wait(S + B_KG * 8, 0);
            if (lane == 0) { fence_async(); mbar_expect(S + B_BOX * 8, 8 * 1152); }
            __syncwarp();
            if (lane < 8) bulk_g2s(S + SM_XS + lane * ROW_STRIDE, p.u + (size_t)(sv & 2047) * D_, 1152, S + B_BOX * 8);
            const uint32_t st = ld_stat(&p.s->stat[sv & 2047], tag);
            const float ri = rcpf(bf_hi(st));
            const uint32_t hi = pack_bf(ri, ri);
            const float rl = ri - bf_lo(hi);
            if (lane == 0) sts64(S + SM_SKIP, 0u, 0u);
            __syncwarp();
            if (lane < 8) {
                const int row = sv & 2047;
                if (((row >> 4) & 31) == (bid >> 2)) asm volatile("red.shared.or.b32 [%0], %1;" ::"r"(S + SM_SKIP + 4 * (row >> 10)), "r"(1u << (16 * ((row >> 9) & 1) + (row & 15))) : "memory");
                sts32(S + SM_XS + 8 * ROW_STRIDE + 4 * lane, sv);
                sts128(S + SM_RP + 16 * lane, prmt(st, st, 0x1010), hi, pack_bf(rl, rl), 0u);
            }
        }
        asm volatile("barrier.cluster.wait.aligned;" ::: "memory");
        bar_sync(9, 96);
        mbar_wait(S + B_BOX * 8, 0);
#pragma unroll
        for (int k = 0; k < 6; k++) {
            const int v = tid - 416 + 96 * k, tk = (v * 911) >> 16;
            const uint4 x = lds128(S + SM_XS + 16 * (v + tk)), st = lds128(S + SM_RP + 16 * tk);
            sts128(S + SM_XS + 16 * (v + tk), norm2(x.x, st.x, st.y, st.z), norm2(x.y, st.x, st.y, st.z), norm2(x.z, st.x, st.y, st.z), norm2(x.w, st.x, st.y, st.z));
        }
        bar_sync(9, 96);
        if (tid == 416) mbar_arrive(S + B_XS * 8);
        const uint32_t ob = mapa(S, r ^ 1);
        if (fw == 2) {
            if (elect()) {
#pragma unroll 1
                for (int st = 0; st < (down ? 24 : 6 * nsl); st++) {
                    if (st == 12 && down) break;
                    mbar_wait(S + (B_W + st) * 8, 0);
                    if (st % 3 == 2) mbar_arrive(S + (B_GU + st / 3) * 8);
                }
            }
            __syncwarp();
        }
        if (fw < 2) {
            const uint32_t bad = S + SM_XS + j * ROW_STRIDE + mi * 16;
            uint32_t aad = (SW + (8 * (mi >> 1) + j) * 64 + 16 * ((mi & 1) ^ (j >> 1))) ^ ((r ^ fw) * 32);
            uint32_t b[18][4];
#pragma unroll
            for (int k = 0; k < 18; k++) ldm4(bad + 64 * k, b[k][0], b[k][1], b[k][2], b[k][3]);
#pragma unroll 1
            for (int u = 0; u < nsl; u++) {
                float d[4][4];
#pragma unroll
                for (int i = 0; i < 4; i++) d[i][0] = d[i][1] = d[i][2] = d[i][3] = 0.f;
#pragma unroll
                for (int hf = 0; hf < 2; hf++) {
                    mbar_wait(S + (B_GU + 2 * u + hf) * 8, 0);
#pragma unroll
                    for (int sub = 0; sub < 3; sub++) {
                        uint32_t a[6][4];
#pragma unroll
                        for (int k = 0; k < 6; k++) ldm4t(aad + 1024 * k, a[k][0], a[k][1], a[k][2], a[k][3]);
#pragma unroll
                        for (int k = 0; k < 6; k++) {
                            const int kb = 9 * hf + 3 * sub + (k >> 1);
                            mma_bf(d[k & 3], a[k][0], a[k][1], a[k][2], a[k][3], b[kb][2 * (k & 1)], b[kb][2 * (k & 1) + 1]);
                        }
                        aad += STAGE;
                    }
                }
                const uint32_t k0 = pack_bf((d[0][0] + d[1][0]) + (d[2][0] + d[3][0]), (d[0][1] + d[1][1]) + (d[2][1] + d[3][1]));
                const uint32_t k1 = pack_bf((d[0][2] + d[1][2]) + (d[2][2] + d[3][2]), (d[0][3] + d[1][3]) + (d[2][3] + d[3][3]));
                if (fw == 1) {
                    asm volatile("st.async.shared::cluster.mbarrier::complete_tx::bytes.v2.b32 [%0], {%1, %2}, [%3];" ::"r"(ob + SM_PART + u * 256 + lane * 8), "r"(k0), "r"(k1), "r"(ob + (B_GX + u) * 8) : "memory");
                } else {
                    mbar_wait(S + (B_GX + u) * 8, 0);
                    const uint2 o = lds64(S + SM_PART + u * 256 + lane * 8);
#pragma unroll
                    for (int i = 0; i < 2; i++) {
                        const uint32_t mine = i ? k1 : k0, other = i ? o.y : o.x, gb = r ? other : mine, ub = r ? mine : other;
                        uint32_t hv = bmul(pack_bf(silu_f(bf_lo(gb)), silu_f(bf_hi(gb))), ub);
                        if ((hv & 0xFFFFu) == 0) hv |= 0x8000u;
                        if ((hv >> 16) == 0) hv |= 0x80000000u;
                        st_rlx(&p.s->h[tag][(32 * (sl0 + u) + 16 * r) * 4 + 32 * i + lane], hv);
                    }
                    __syncwarp();
                    if (lane < 8) red_add(&p.s->cnt[lane * 32]);
                }
            }
        }
        if (!down) return;

        const int fi = 32 * fw + lane, tok = 4 * r + ((fi >> 4) & 3), cc = 16 * pr + (fi & 15);
        const uint32_t sel = lds32(S + SM_XS + 8 * ROW_STRIDE + 4 * tok);
        const int row = sel & 2047;
        const uint32_t* ya = p.s->y + (row >> 4) * 4608 + cc * 8 + (row & 6);
        const float xraw = __bfloat162float(p.u[(size_t)row * D_ + cc]), dsk = __bfloat162float(p.dskip[cc]);
        const float xn = bf_lo(lds16(S + SM_XS + tok * ROW_STRIDE + 2 * cc));
        if (fw == 0) {
#pragma unroll 1
            for (int st = 12; st < 24; st++) mbar_wait(S + (B_W + st) * 8, 0);
        }
        if (fw == 2 && elect()) wait_count(&p.s->cnt[(bid & 7) * 32], epoch * 288u);
        bar_sync(9, 96);
        float dn[4][4];
        uint2 yv2 = make_uint2(tag ^ 1, 0u);
#pragma unroll 1
        for (int ph = 0; ph < 64; ph++) {
            if (fw == 2 && elect()) {
                fence_async();
                fence_async_g();
                mbar_expect(S + B_H * 8, 36864);
                bulk_g2s(SW, (const char*)p.s->h[tag] + r * 36864, 36864, S + B_H * 8);
            }
            asm volatile("ld.relaxed.gpu.global.v2.u32 {%0,%1}, [%2];" : "=r"(yv2.x), "=r"(yv2.y) : "l"(ya) : "memory");
            mbar_wait(S + B_H * 8, ph & 1);
#pragma unroll
            for (int i = 0; i < 4; i++) dn[i][0] = dn[i][1] = dn[i][2] = dn[i][3] = 0.f;
            uint32_t bq[4] = {~0u, ~0u, ~0u, ~0u};
            const int fr = j + 8 * (mi >> 1);
            uint32_t wa = SW + 12 * STAGE + fw * 2048 + fr * 32 + (((mi & 1) ^ ((fr >> 2) & 1)) << 4), ha = SW + fw * 1024 + lane * 16;
#pragma unroll 1
            for (int s0 = 0; s0 < 12; s0 += 3) {
                uint32_t a[6][8], b[6][4];
#pragma unroll
                for (int s = 0; s < 3; s++) {
                    if (s == 2 && s0 == 9) wa += S + SM_W_LAST - (SW + 23 * STAGE);
#pragma unroll
                    for (int e = 0; e < 2; e++) {
                        ldm4t(ha + e * 512, b[2 * s + e][0], b[2 * s + e][1], b[2 * s + e][2], b[2 * s + e][3]);
                        ldm4t(wa + e * 1024, a[2 * s + e][0], a[2 * s + e][1], a[2 * s + e][2], a[2 * s + e][3]);
                        ldm4t(wa + e * 1024 + 512, a[2 * s + e][4], a[2 * s + e][5], a[2 * s + e][6], a[2 * s + e][7]);
                    }
                    wa += STAGE; ha += 3072;
                }
#pragma unroll
                for (int k = 0; k < 6; k++) {
                    mma_bf(dn[2 * (k & 1)], a[k][0], a[k][1], a[k][2], a[k][3], b[k][0], b[k][1]);
                    mma_bf(dn[2 * (k & 1) + 1], a[k][4], a[k][5], a[k][6], a[k][7], b[k][2], b[k][3]);
#pragma unroll
                    for (int q = 0; q < 4; q++) bq[q] = __vminu2(bq[q], b[k][q]);
                }
            }
            const uint32_t bm = __vminu2(__vminu2(bq[0], bq[1]), __vminu2(bq[2], bq[3])), bd = (bm - 0x00010001u) & ~bm;
            uint32_t anybad;
            asm volatile("{.reg .pred p, q; setp.ne.u32 p, %1, 0; bar.red.or.pred q, 9, 96, p; selp.u32 %0, 1, 0, q;}" : "=r"(anybad) : "r"(bd & 0x80008000u) : "memory");
            if (!anybad) break;
        }
        float* red = (float*)(smem + SM_RED + fw * 512);
        red[(2 * t) * 16 + g] = (dn[0][0] + dn[1][0]) + (dn[2][0] + dn[3][0]);
        red[(2 * t + 1) * 16 + g] = (dn[0][1] + dn[1][1]) + (dn[2][1] + dn[3][1]);
        red[(2 * t) * 16 + g + 8] = (dn[0][2] + dn[1][2]) + (dn[2][2] + dn[3][2]);
        red[(2 * t + 1) * 16 + g + 8] = (dn[0][3] + dn[1][3]) + (dn[2][3] + dn[3][3]);
        bar_sync(9, 96);
        if (fw < 2) {
            const float* rs = (const float*)(smem + SM_RED);
            const int mine = 64 * r + fi, other = mine ^ 64;
            st_async32(ob + SM_RP + 4 * fi, __float_as_uint(rs[other] + rs[128 + other] + rs[256 + other]), ob + B_RED * 8);
            const float s = rs[mine] + rs[128 + mine] + rs[256 + mine];
#pragma unroll 1
            for (int it = 0; it < SPIN_LIMIT && (yv2.x & 1) != tag; it++)
                asm volatile("ld.relaxed.gpu.global.v2.u32 {%0,%1}, [%2];" : "=r"(yv2.x), "=r"(yv2.y) : "l"(ya) : "memory");
            const uint32_t yw = (row & 8) ? yv2.y : yv2.x;
            const float sg = bf_round(((row & 1) ? bf_hi(yw) : bf_lo(yw)) + bf_round(xn * dsk));
            mbar_wait(S + B_RED * 8, 0);
            const float o = *(const float*)(smem + SM_RP + 4 * fi);
            const float yv = bf_round(bf_round(r == 0 ? s + o : o + s) * bf_hi(sel));
            p.out[(size_t)row * D_ + cc] = __float2bfloat16(xraw + bf_round(sg * bf_round(silu_f(bf_round(xn + yv)))));
            if (bid == 0 && fi == 0) st_rlx(&p.s->cnt[16 * 32], epoch);
        }
    }
}

typedef CUresult (*EncodeFn)(CUtensorMap*, CUtensorMapDataType, cuuint32_t, void*, const cuuint64_t*, const cuuint64_t*, const cuuint32_t*,
                             const cuuint32_t*, CUtensorMapInterleave, CUtensorMapSwizzle, CUtensorMapL2promotion, CUtensorMapFloatOOBfill);

static void make2d(EncodeFn enc, CUtensorMap* m, const void* base, uint64_t cols, uint64_t rows, uint32_t bc, uint32_t br, CUtensorMapSwizzle sw) {
    cuuint64_t gd[2] = {cols, rows};
    cuuint64_t gs[1] = {cols * 2};
    cuuint32_t bd[2] = {bc, br}, es[2] = {1, 1};
    enc(m, CU_TENSOR_MAP_DATA_TYPE_BFLOAT16, 2, const_cast<void*>(base), gd, gs, bd, es, CU_TENSOR_MAP_INTERLEAVE_NONE, sw,
        CU_TENSOR_MAP_L2_PROMOTION_L2_128B, CU_TENSOR_MAP_FLOAT_OOB_FILL_NONE);
}

static Tune g_tune = {2000, 9000, 3, 5, 8, 5000, 7500, 0, 9000, 1, 0, 0};


static void launch(void* const* d_in, void* d_out) {
    static EncodeFn enc = nullptr;
    static Scratch* gs = nullptr;
    if (!enc) {
        void* fn = nullptr;
        cudaDriverEntryPointQueryResult qr;
        cudaGetDriverEntryPoint("cuTensorMapEncodeTiled", &fn, cudaEnableDefault, &qr);
        enc = (EncodeFn)fn;
        cudaFuncSetAttribute(fused_kernel, cudaFuncAttributeMaxDynamicSharedMemorySize, SM_TOTAL);
        cudaGetSymbolAddress((void**)&gs, g_s);
    }
    Hot p;
    Maps m;
    auto in = [&](int i) { return (const __nv_bfloat16*)d_in[i]; };
    p.u = in(0); p.are = in(1); p.aim = in(2); p.bre = in(3); p.bim = in(4); p.cre = in(5); p.cim = in(6);
    p.logdt = in(7); p.dskip = in(8); p.wr = in(10); p.pwg = in(11); p.pwu = in(12); p.pwd = in(13);
    p.out = (__nv_bfloat16*)d_out;
    p.tn = g_tune;
    p.s = gs;
    make2d(enc, &m.wg, p.pwg, F_, D_, 32, 96, CU_TENSOR_MAP_SWIZZLE_64B);
    make2d(enc, &m.wu, p.pwu, F_, D_, 32, 96, CU_TENSOR_MAP_SWIZZLE_64B);
    make2d(enc, &m.wd, p.pwd, D_, F_, 16, 192, CU_TENSOR_MAP_SWIZZLE_32B);
    fused_kernel<<<NCTA, NTHREADS, SM_TOTAL>>>(p, m);
}

}

extern "C" void kernel_launch(void* const* d_in, const int* in_sizes, int n_in, void* d_out, int out_size) {
    static int clusters = -1;
    if (clusters < 0) clusters = v3::max_clusters();
    if (clusters < 15 || !v3::launch(d_in, d_out)) v2::launch(d_in, d_out);
}
```

```cpp
#include <cuda_runtime.h>
#include <cuda_bf16.h>
#include <cuda_fp16.h>
#include <cuda.h>
#include <stdint.h>
#include <stddef.h>
#include <type_traits>


namespace v3 {

constexpr bool LD4 = false, ZZ = true;

constexpr int D_ = 576, F_ = 4608;
constexpr int NCTA = 120, NTHREADS = 512;
constexpr int SPIN_LIMIT = 1 << 16;

enum { B_Y = 0, B_X = 8, B_TOP = 10, B_XS = 12, B_UP = 13, B_RAW = 15, B_FULL = 16, B_FIN = 43, B_SEL = 44, B_ST = 45, B_EMPTY = 38  , B_ROWS = 66, B_WR = 67 };
constexpr int SM_SKIP = 544, SM_SEL = 576;
constexpr int SM_ST = 640;
constexpr int SM_RAW = 2688, PITCH = 80;
constexpr int SM_CH = SM_RAW + 256 * PITCH, CH = 18304;
constexpr int TAB = 0, FT = 3072, XX = 3712, BOX = 8064, YIN = 14208;
constexpr int SM_B = SM_CH + 5 * CH, BP = 1168;
constexpr int SM_CAND = SM_B + 8 * BP, SM_PROG = SM_CAND + 256, SM_DUMP = SM_PROG + 128;
constexpr int NRING = 12, SM_W = SM_B + 10240, SM_FIN = SM_W + NRING * 8192, SM_TOTAL = 232448;
static_assert(SM_W % 1024 == 0 && SM_FIN + 8192 <= SM_TOTAL && SM_TOTAL - 18432 >= SM_W + 10 * 8192, "smem");

struct Tune { int t_tile, stag, tail, win0, s0, t_rows, da, ns0, zero; };

struct Scratch {
    uint32_t h[8 * 2304];
    uint2 stat[2048];
    uint32_t ep[NCTA * 8];
};
__device__ __align__(1024) Scratch g_s;

struct Hot {
    const __nv_bfloat16* u;
    int bre, bim, cre, cim, are, aim, logdt, dskip, wr, ep;
    Scratch* s;
    __nv_bfloat16* out;
    Tune tn;
};
struct Maps { CUtensorMap w[3], u; };

__device__ __forceinline__ uint32_t smem_u32(const void* p) { return (uint32_t)__cvta_generic_to_shared(p); }
__device__ __forceinline__ void mbar_init(uint32_t b, int c) { asm volatile("mbarrier.init.shared::cta.b64 [%0], %1;" ::"r"(b), "r"(c) : "memory"); }
__device__ __forceinline__ void mbar_expect(uint32_t b, int bytes) { asm volatile("mbarrier.arrive.expect_tx.shared::cta.b64 _, [%0], %1;" ::"r"(b), "r"(bytes) : "memory"); }
__device__ __forceinline__ void mbar_arrive(uint32_t b) { asm volatile("mbarrier.arrive.shared::cta.b64 _, [%0];" ::"r"(b) : "memory"); }
__device__ __forceinline__ bool elect() { uint32_t d; asm volatile("{.reg .pred p; elect.sync _|p, 0xffffffff; selp.u32 %0,1,0,p;}" : "=r"(d)); return d; }
__device__ __forceinline__ void mbar_wait(uint32_t b, int par) {
    asm volatile("{\n.reg .pred p;\nLW:\nmbarrier.try_wait.parity.shared::cta.b64 p, [%0], %1, 2000;\n@!p bra LW;\n}" ::"r"(b), "r"(par) : "memory");
}
__device__ __forceinline__ void mbar_wait_short(uint32_t b) {
    asm volatile("{\n.reg .pred p;\nLW:\nmbarrier.try_wait.parity.shared::cta.b64 p, [%0], 0;\n@!p bra LW;\n}" ::"r"(b) : "memory");
}
__device__ __forceinline__ uint32_t mapa(uint32_t a, uint32_t rank) { uint32_t d; asm("mapa.shared::cluster.u32 %0, %1, %2;" : "=r"(d) : "r"(a), "r"(rank)); return d; }
__device__ __forceinline__ void tma2d(uint32_t dst, const CUtensorMap* m, int c0, int c1, uint32_t bar) {
    asm volatile("cp.async.bulk.tensor.2d.shared::cluster.global.mbarrier::complete_tx::bytes [%0], [%1, {%3, %4}], [%2];" ::"r"(dst), "l"(m), "r"(bar), "r"(c0), "r"(c1) : "memory");
}
__device__ __forceinline__ void bulk_g2s(uint32_t dst, const void* src, int bytes, uint32_t bar) {
    asm volatile("cp.async.bulk.shared::cluster.global.mbarrier::complete_tx::bytes [%0], [%1], %2, [%3];" ::"r"(dst), "l"(src), "r"(bytes), "r"(bar) : "memory");
}
__device__ __forceinline__ void bulk_mc(uint32_t dst, const void* src, int bytes, uint32_t bar) {
    asm volatile("cp.async.bulk.shared::cluster.global.mbarrier::complete_tx::bytes.multicast::cluster [%0], [%1], %2, [%3], %4;"
                 ::"r"(dst), "l"(src), "r"(bytes), "r"(bar), "h"((uint16_t)255) : "memory");
}
__device__ __forceinline__ void bar_sync(int id, int n) { asm volatile("bar.sync %0, %1;" ::"r"(id), "r"(n) : "memory"); }
__device__ __forceinline__ void bar_arrive(int id, int n) { asm volatile("bar.arrive %0, %1;" ::"r"(id), "r"(n) : "memory"); }
__device__ __forceinline__ uint4 ld_rlx4(const void* p) { uint4 v; asm volatile("ld.relaxed.gpu.global.v4.u32 {%0,%1,%2,%3}, [%4];" : "=r"(v.x), "=r"(v.y), "=r"(v.z), "=r"(v.w) : "l"(p) : "memory"); return v; }
__device__ __forceinline__ uint2 ld_rlx2(const void* p) { uint2 v; asm volatile("ld.relaxed.gpu.global.v2.u32 {%0,%1}, [%2];" : "=r"(v.x), "=r"(v.y) : "l"(p) : "memory"); return v; }
__device__ __forceinline__ uint32_t ld_rlx(const void* p) { uint32_t v; asm volatile("ld.relaxed.gpu.global.u32 %0, [%1];" : "=r"(v) : "l"(p) : "memory"); return v; }
__device__ __forceinline__ void st_rlx(void* p, uint32_t v) { asm volatile("st.relaxed.gpu.global.u32 [%0], %1;" ::"l"(p), "r"(v) : "memory"); }
__device__ __forceinline__ void st_rlx2(void* p, uint32_t x, uint32_t y) { asm volatile("st.relaxed.gpu.global.v2.u32 [%0], {%1,%2};" ::"l"(p), "r"(x), "r"(y) : "memory"); }
__device__ __forceinline__ uint4 ldg4(const void* p) { uint4 v; asm volatile("ld.global.nc.v4.u32 {%0,%1,%2,%3}, [%4];" : "=r"(v.x), "=r"(v.y), "=r"(v.z), "=r"(v.w) : "l"(p)); return v; }
__device__ __forceinline__ uint32_t ldg1(const void* p) { uint32_t v; asm volatile("ld.global.nc.u32 %0, [%1];" : "=r"(v) : "l"(p)); return v; }
__device__ __forceinline__ uint32_t ldg16(const void* p) { uint16_t v; asm volatile("ld.global.nc.u16 %0, [%1];" : "=h"(v) : "l"(p)); return v; }
__device__ __forceinline__ const void* at256(const void* b, int o) { const void* r; asm("mad.wide.s32 %0, %1, 256, %2;" : "=l"(r) : "r"(o), "l"(b)); return r; }
__device__ __forceinline__ int laneid() { int v; asm volatile("mov.u32 %0, %%laneid;" : "=r"(v)); return v; }
__device__ __forceinline__ int ctaid() { int v; asm volatile("mov.u32 %0, %%ctaid.x;" : "=r"(v)); return v; }
__device__ __forceinline__ uint32_t lds32(uint32_t a) { uint32_t v; asm volatile("ld.shared.u32 %0, [%1];" : "=r"(v) : "r"(a) : "memory"); return v; }
__device__ __forceinline__ uint32_t lds32v(uint32_t a) { uint32_t v; asm volatile("ld.volatile.shared.u32 %0, [%1];" : "=r"(v) : "r"(a) : "memory"); return v; }
__device__ __forceinline__ uint32_t lds16(uint32_t a) { uint16_t v; asm volatile("ld.shared.u16 %0, [%1];" : "=h"(v) : "r"(a) : "memory"); return v; }
__device__ __forceinline__ uint2 lds64(uint32_t a) { uint2 v; asm volatile("ld.shared.v2.u32 {%0,%1}, [%2];" : "=r"(v.x), "=r"(v.y) : "r"(a) : "memory"); return v; }
__device__ __forceinline__ uint4 lds128(uint32_t a) { uint4 v; asm volatile("ld.shared.v4.u32 {%0,%1,%2,%3}, [%4];" : "=r"(v.x), "=r"(v.y), "=r"(v.z), "=r"(v.w) : "r"(a) : "memory"); return v; }
__device__ __forceinline__ void sts16(uint32_t a, uint32_t v) { asm volatile("st.shared.u16 [%0], %1;" ::"r"(a), "h"((uint16_t)v) : "memory"); }
__device__ __forceinline__ void sts32(uint32_t a, uint32_t v) { asm volatile("st.shared.u32 [%0], %1;" ::"r"(a), "r"(v) : "memory"); }
__device__ __forceinline__ void sts32v(uint32_t a, uint32_t v) { asm volatile("st.volatile.shared.u32 [%0], %1;" ::"r"(a), "r"(v) : "memory"); }
__device__ __forceinline__ void sts64(uint32_t a, uint32_t x, uint32_t y) { asm volatile("st.shared.v2.u32 [%0], {%1,%2};" ::"r"(a), "r"(x), "r"(y) : "memory"); }
__device__ __forceinline__ void sts128(uint32_t a, uint32_t x, uint32_t y, uint32_t z, uint32_t w) { asm volatile("st.shared.v4.u32 [%0], {%1,%2,%3,%4};" ::"r"(a), "r"(x), "r"(y), "r"(z), "r"(w) : "memory"); }
__device__ __forceinline__ void sts128f(uint32_t a, float x, float y, float z, float w) { asm volatile("st.shared.v4.f32 [%0], {%1,%2,%3,%4};" ::"r"(a), "f"(x), "f"(y), "f"(z), "f"(w) : "memory"); }
__device__ __forceinline__ void st_async4(uint32_t a, uint32_t x, uint32_t y, uint32_t z, uint32_t w, uint32_t bar) {
    asm volatile("st.async.shared::cluster.mbarrier::complete_tx::bytes.v4.b32 [%0], {%1,%2,%3,%4}, [%5];" ::"r"(a), "r"(x), "r"(y), "r"(z), "r"(w), "r"(bar) : "memory");
}
__device__ __forceinline__ void st_async2(uint32_t a, uint32_t x, uint32_t y, uint32_t bar) {
    asm volatile("st.async.shared::cluster.mbarrier::complete_tx::bytes.v2.b32 [%0], {%1,%2}, [%3];" ::"r"(a), "r"(x), "r"(y), "r"(bar) : "memory");
}
__device__ __forceinline__ void st_async2f(uint32_t a, float x, float y, uint32_t bar) {
    asm volatile("st.async.shared::cluster.mbarrier::complete_tx::bytes.v2.f32 [%0], {%1,%2}, [%3];" ::"r"(a), "f"(x), "f"(y), "r"(bar) : "memory");
}
__device__ __forceinline__ void ldm4(uint32_t a, uint32_t& r0, uint32_t& r1, uint32_t& r2, uint32_t& r3) {
    asm volatile("ldmatrix.sync.aligned.m8n8.x4.shared.b16 {%0,%1,%2,%3}, [%4];" : "=r"(r0), "=r"(r1), "=r"(r2), "=r"(r3) : "r"(a) : "memory");
}
__device__ __forceinline__ void ldm4t(uint32_t a, uint32_t (&r)[4]) {
    asm volatile("ldmatrix.sync.aligned.m8n8.x4.trans.shared.b16 {%0,%1,%2,%3}, [%4];" : "=r"(r[0]), "=r"(r[1]), "=r"(r[2]), "=r"(r[3]) : "r"(a) : "memory");
}
__device__ __forceinline__ void ldm2(uint32_t a, uint32_t& r0, uint32_t& r1) {
    asm volatile("ldmatrix.sync.aligned.m8n8.x2.shared.b16 {%0,%1}, [%2];" : "=r"(r0), "=r"(r1) : "r"(a) : "memory");
}
__device__ __forceinline__ void ldm2t(uint32_t a, uint32_t& r0, uint32_t& r1) {
    asm volatile("ldmatrix.sync.aligned.m8n8.x2.trans.shared.b16 {%0,%1}, [%2];" : "=r"(r0), "=r"(r1) : "r"(a) : "memory");
}
__device__ __forceinline__ void stm4(uint32_t a, uint32_t r0, uint32_t r1, uint32_t r2, uint32_t r3) {
    asm volatile("stmatrix.sync.aligned.m8n8.x4.shared.b16 [%0], {%1,%2,%3,%4};" ::"r"(a), "r"(r0), "r"(r1), "r"(r2), "r"(r3) : "memory");
}
__device__ __forceinline__ void stm4t(uint32_t a, uint32_t r0, uint32_t r1, uint32_t r2, uint32_t r3) {
    asm volatile("stmatrix.sync.aligned.m8n8.x4.trans.shared.b16 [%0], {%1,%2,%3,%4};" ::"r"(a), "r"(r0), "r"(r1), "r"(r2), "r"(r3) : "memory");
}
__device__ __forceinline__ void stm2t(uint32_t a, uint32_t r0, uint32_t r1) {
    asm volatile("stmatrix.sync.aligned.m8n8.x2.trans.shared.b16 [%0], {%1,%2};" ::"r"(a), "r"(r0), "r"(r1) : "memory");
}
__device__ __forceinline__ uint32_t movm(uint32_t a) { uint32_t d; asm volatile("movmatrix.sync.aligned.m8n8.trans.b16 %0, %1;" : "=r"(d) : "r"(a)); return d; }
__device__ __forceinline__ void mma_bf(float (&c)[4], uint32_t a0, uint32_t a1, uint32_t a2, uint32_t a3, uint32_t b0, uint32_t b1) {
    asm volatile("mma.sync.aligned.m16n8k16.row.col.f32.bf16.bf16.f32 {%0,%1,%2,%3},{%4,%5,%6,%7},{%8,%9},{%0,%1,%2,%3};"
                 : "+f"(c[0]), "+f"(c[1]), "+f"(c[2]), "+f"(c[3]) : "r"(a0), "r"(a1), "r"(a2), "r"(a3), "r"(b0), "r"(b1));
}
__device__ __forceinline__ void mma_bf8(float (&c)[4], uint32_t a0, uint32_t a1, uint32_t b0) {
    asm volatile("mma.sync.aligned.m16n8k8.row.col.f32.bf16.bf16.f32 {%0,%1,%2,%3},{%4,%5},{%6},{%0,%1,%2,%3};"
                 : "+f"(c[0]), "+f"(c[1]), "+f"(c[2]), "+f"(c[3]) : "r"(a0), "r"(a1), "r"(b0));
}
__device__ __forceinline__ void mma_h(float (&c)[4], uint32_t a0, uint32_t a1, uint32_t a2, uint32_t a3, uint32_t b0, uint32_t b1) {
    asm volatile("mma.sync.aligned.m16n8k16.row.col.f32.f16.f16.f32 {%0,%1,%2,%3},{%4,%5,%6,%7},{%8,%9},{%0,%1,%2,%3};"
                 : "+f"(c[0]), "+f"(c[1]), "+f"(c[2]), "+f"(c[3]) : "r"(a0), "r"(a1), "r"(a2), "r"(a3), "r"(b0), "r"(b1));
}
__device__ __forceinline__ void mma_h8(float (&c)[4], uint32_t a0, uint32_t a1, uint32_t b0) {
    asm volatile("mma.sync.aligned.m16n8k8.row.col.f32.f16.f16.f32 {%0,%1,%2,%3},{%4,%5},{%6},{%0,%1,%2,%3};"
                 : "+f"(c[0]), "+f"(c[1]), "+f"(c[2]), "+f"(c[3]) : "r"(a0), "r"(a1), "r"(b0));
}
template <int LIM>
__device__ __forceinline__ void mma_hp(int n, float (&d)[4], const float (&c)[4], uint32_t a0, uint32_t a1, uint32_t a2, uint32_t a3, uint32_t b0, uint32_t b1) {
    asm volatile("{.reg .pred p; setp.gt.s32 p, %14, %15;\n"
                 "@p mma.sync.aligned.m16n8k16.row.col.f32.f16.f16.f32 {%0,%1,%2,%3},{%4,%5,%6,%7},{%8,%9},{%10,%11,%12,%13};}"
                 : "+f"(d[0]), "+f"(d[1]), "+f"(d[2]), "+f"(d[3])
                 : "r"(a0), "r"(a1), "r"(a2), "r"(a3), "r"(b0), "r"(b1), "f"(c[0]), "f"(c[1]), "f"(c[2]), "f"(c[3]), "r"(n), "n"(LIM));
}
template <int LIM>
__device__ __forceinline__ void mma_hq(int n, float (&d)[4], uint32_t a0, uint32_t a1, uint32_t a2, uint32_t a3, uint32_t b0, uint32_t b1) {
    asm volatile("{.reg .pred p; setp.gt.s32 p, %10, %11;\n"
                 "@p mma.sync.aligned.m16n8k16.row.col.f32.f16.f16.f32 {%0,%1,%2,%3},{%4,%5,%6,%7},{%8,%9},{%0,%1,%2,%3};}"
                 : "+f"(d[0]), "+f"(d[1]), "+f"(d[2]), "+f"(d[3]) : "r"(a0), "r"(a1), "r"(a2), "r"(a3), "r"(b0), "r"(b1), "r"(n), "n"(LIM));
}
__device__ __forceinline__ void mma_hc(float (&d)[4], const float (&c)[4], uint32_t a0, uint32_t a1, uint32_t a2, uint32_t a3, uint32_t b0, uint32_t b1) {
    asm volatile("mma.sync.aligned.m16n8k16.row.col.f32.f16.f16.f32 {%0,%1,%2,%3},{%4,%5,%6,%7},{%8,%9},{%10,%11,%12,%13};"
                 : "=f"(d[0]), "=f"(d[1]), "=f"(d[2]), "=f"(d[3]) : "r"(a0), "r"(a1), "r"(a2), "r"(a3), "r"(b0), "r"(b1), "f"(c[0]), "f"(c[1]), "f"(c[2]), "f"(c[3]));
}
__device__ __forceinline__ uint32_t pack_bf(float lo, float hi) { uint32_t r; asm("cvt.rn.bf16x2.f32 %0, %1, %2;" : "=r"(r) : "f"(hi), "f"(lo)); return r; }
__device__ __forceinline__ uint32_t pack_h(float lo, float hi) { uint32_t r; asm("cvt.rn.f16x2.f32 %0, %1, %2;" : "=r"(r) : "f"(hi), "f"(lo)); return r; }
__device__ __forceinline__ float bf_lo(uint32_t w) { return __uint_as_float(w << 16); }
__device__ __forceinline__ float bf_hi(uint32_t w) { return __uint_as_float(w & 0xFFFF0000u); }
__device__ __forceinline__ float bf_round(float x) { return __uint_as_float(pack_bf(0.f, x)); }
__device__ __forceinline__ uint32_t badd(uint32_t a, uint32_t b) { uint32_t r; asm("add.rn.bf16x2 %0, %1, %2;" : "=r"(r) : "r"(a), "r"(b)); return r; }
__device__ __forceinline__ uint32_t bsub(uint32_t a, uint32_t b) { uint32_t r; asm("sub.rn.bf16x2 %0, %1, %2;" : "=r"(r) : "r"(a), "r"(b)); return r; }
__device__ __forceinline__ uint32_t bmul(uint32_t a, uint32_t b) { uint32_t r; asm("mul.rn.bf16x2 %0, %1, %2;" : "=r"(r) : "r"(a), "r"(b)); return r; }
__device__ __forceinline__ uint32_t bfma(uint32_t a, uint32_t b, uint32_t c) { uint32_t r; asm("fma.rn.bf16x2 %0, %1, %2, %3;" : "=r"(r) : "r"(a), "r"(b), "r"(c)); return r; }
__device__ __forceinline__ uint32_t hadd(uint32_t a, uint32_t b) { uint32_t r; asm("add.rn.f16x2 %0, %1, %2;" : "=r"(r) : "r"(a), "r"(b)); return r; }
__device__ __forceinline__ uint32_t prmt(uint32_t a, uint32_t b, uint32_t s) { uint32_t r; asm("prmt.b32 %0, %1, %2, %3;" : "=r"(r) : "r"(a), "r"(b), "r"(s)); return r; }
__device__ __forceinline__ uint32_t lop_ne(uint32_t a, uint32_t b, uint32_t c) { uint32_t r; asm("lop3.b32 %0, %1, %2, %3, 0x7E;" : "=r"(r) : "r"(a), "r"(b), "r"(c)); return r; }
__device__ __forceinline__ float ex2f(float x) { float r; asm("ex2.approx.ftz.f32 %0, %1;" : "=f"(r) : "f"(x)); return r; }
__device__ __forceinline__ float rcpf(float x) { float r; asm("rcp.approx.ftz.f32 %0, %1;" : "=f"(r) : "f"(x)); return r; }
__device__ __forceinline__ float sqrt_ap(float x) { float r; asm("sqrt.approx.ftz.f32 %0, %1;" : "=f"(r) : "f"(x)); return r; }
__device__ __forceinline__ float tanh_ap(float x) { float r; asm("tanh.approx.f32 %0, %1;" : "=f"(r) : "f"(x)); return r; }
__device__ __forceinline__ float sigm(float x) { return rcpf(1.f + ex2f(-1.4426950408889634f * x)); }
__device__ __forceinline__ float silu_half(float h) { return fmaf(h, tanh_ap(h), h); }
__device__ __forceinline__ uint32_t clk32() { uint32_t c; asm volatile("mov.u32 %0, %%clock;" : "=r"(c)); return c; }
__device__ __forceinline__ void spin_until(uint32_t t0, int dt) {
#pragma unroll 1
    while ((int)(clk32() - t0) < dt) __nanosleep(32);
}
__device__ __forceinline__ void cp16(uint32_t dst, const void* src) { asm volatile("cp.async.cg.shared.global [%0], [%1], 16;" ::"r"(dst), "l"(src) : "memory"); }

__device__ __forceinline__ uint32_t xslot(int s, int h) { return XX + 32 * (s & ~1) + 16 * ((2 * h + (s & 1)) ^ ((s >> 1) & 2)); }

struct cf { float x, y; };
__device__ __forceinline__ cf cmul(cf a, cf b) { return {a.x * b.x - a.y * b.y, a.x * b.y + a.y * b.x}; }
__device__ __forceinline__ cf csq(cf a) { return {a.x * a.x - a.y * a.y, (a.x + a.x) * a.y}; }
__device__ __forceinline__ cf cpow_direct(float zr2, float zi, float l) {
    const float mag = ex2f(zr2 * l), th = zi * l;
    return {mag * __cosf(th), mag * __sinf(th)};
}
struct hp { uint32_t re, im; };
__device__ __forceinline__ hp mk2(cf a, cf b) { return {pack_h(a.x, b.x), pack_h(a.y, b.y)}; }
__device__ __forceinline__ hp his(hp a, hp b) { return {prmt(a.re, b.re, 0x7632), prmt(a.im, b.im, 0x7632)}; }
__device__ __forceinline__ hp operator*(hp a, hp b) {
    hp r;
    asm("{.reg .b32 t, u;\nmul.rn.f16x2 t, %3, %5;\nneg.f16x2 t, t;\nfma.rn.f16x2 %0, %2, %4, t;\nmul.rn.f16x2 u, %3, %4;\nfma.rn.f16x2 %1, %2, %5, u;}"
        : "=&r"(r.re), "=r"(r.im) : "r"(a.re), "r"(a.im), "r"(b.re), "r"(b.im));
    return r;
}
struct KParams { uint32_t are, aim, bre, bim, cre, cim, ldt, dsk; };

__device__ __forceinline__ uint32_t kgen(KParams kp, uint32_t scr, uint32_t oth, int bar, int lane, float (&d)[5][4], float& k0, int nc, uint32_t pause) {
    const float dt = bf_round(ex2f(bf_lo(kp.ldt) * 1.4426950408889634f));
    cf w = cmul({bf_lo(kp.cre), bf_lo(kp.cim)}, {dt * bf_lo(kp.bre), dt * bf_lo(kp.bim)});
    cf w1 = cmul({bf_hi(kp.cre), bf_hi(kp.cim)}, {dt * bf_hi(kp.bre), dt * bf_hi(kp.bim)});
    const float dk = bf_lo(kp.dsk);
    uint32_t z = prmt(kp.are, kp.aim, 0x5410), z1 = prmt(kp.are, kp.aim, 0x7632);
    uint32_t eb = __reduce_max_sync(~0u, __float_as_uint(fmaxf(fmaxf(fmaxf(fabsf(w.x), fabsf(w.y)), fmaxf(fabsf(w1.x), fabsf(w1.y))), fabsf(dk) * 0x1p-20f)));
    k0 = fmaf(dk, 1.f / 64.f, w.x + w1.x);
#pragma unroll
    for (int o = 16; o > 0; o >>= 1) k0 += __shfl_xor_sync(~0u, k0, o);
    const uint32_t sa = scr + 16 * lane;
    sts128(oth + 2048 + 16 * lane, __float_as_uint(w1.x), __float_as_uint(w1.y), z1, __float_as_uint(k0));
    sts32(oth + 2560, eb);
    bar_sync(bar, 64);
    const uint4 ov = lds128(sa + 2048);
    eb = min(max(max(eb, lds32(scr + 2560)) & 0x7F800000u, 0x00800000u), 0x7A000000u);
    const float sc = __uint_as_float(0x7B000000u - eb);
    k0 = (k0 + __uint_as_float(ov.w)) * sc;
#pragma unroll
    for (int i = 0; i < 5; i++) d[i][0] = d[i][1] = d[i][2] = d[i][3] = 0.f;
    const int mi = lane >> 3, j = lane & 7;
    const uint32_t la = scr + 1024 * (mi & 1) + 512 * (mi >> 1) + 16 * j, lb = scr + 512 * (mi & 1) + 128 * (mi >> 1) + 16 * j;
    auto st = [&](int grp, hp a, hp b, hp c, hp e) { sts128(sa + 1024 * grp, a.re, b.re, c.re, e.re); sts128(sa + 1024 * grp + 512, a.im, b.im, c.im, e.im); };
#pragma unroll 1
    do {
        const float zr2 = dt * bf_lo(z) * 1.4426950408889634f, zi = dt * bf_hi(z);
        const cf ws = {w.x * sc, w.y * sc};
        z = z1; w = w1;
        z1 = ov.z; w1 = {__uint_as_float(ov.x), __uint_as_float(ov.y)};
        const cf a1 = cpow_direct(zr2, zi, 1.f), a256 = cpow_direct(zr2, zi, 256.f);
        uint32_t a[4][4];
        {
            const cf b1 = cpow_direct(-zr2, zi, -16.f), b2 = csq(b1), b4 = csq(b2), b8 = csq(b4);
            const hp m2 = mk2(b2, b2), m4 = mk2(b4, b4), m8 = mk2(b8, b8);
            const hp u0 = mk2({1.f, 0.f}, b1), u1 = u0 * m2, u2 = u0 * m4, u3 = u1 * m4;
            __syncwarp();
            st(0, u0, u1, u2, u3);
            st(1, u0 * m8, u1 * m8, u2 * m8, u3 * m8);
            __syncwarp();
#pragma unroll
            for (int k = 0; k < 4; k++) ldm4t(la + 128 * k, a[k]);
        }
        auto tile = [&](int T, int grp) {
#pragma unroll
            for (int e = 0; e < 2; e++) {
                uint32_t b[4];
                ldm4t(lb + 1024 * grp + 256 * e, b);
                mma_h(d[T], a[2 * e][0], a[2 * e][1], a[2 * e][2], a[2 * e][3], b[0], b[1]);
                mma_h(d[T], a[2 * e + 1][0], a[2 * e + 1][1], a[2 * e + 1][2], a[2 * e + 1][3], b[2], b[3]);
            }
        };
        const cf a2 = csq(a1), a4 = csq(a2), a8 = csq(a4), a512 = csq(a256), a1024 = csq(a512);
        const hp m2 = mk2(a2, a2), m4 = mk2(a4, a4), m8 = mk2(a8, a8), m256 = mk2(a256, a256), m512 = mk2(a512, a512);
        const hp v1 = mk2(cmul(ws, a1), cmul(ws, a2)), v3 = v1 * m2, v5 = v1 * m4, v7 = v3 * m4, v15 = v7 * m8;
        const hp e1 = his(v1, v3) * m256, e2 = e1 * m4;
        __syncwarp();
        st(0, v1, v5, v1 * m8, v5 * m8);
        st(1, v3, v7, v3 * m8, v15);
        st(2, e1, e2, e1 * m8, e2 * m8);
        __syncwarp();
        tile(0, 0); tile(1, 1); tile(2, 2);
        const hp f1 = his(v3, v7) * m512, f2 = f1 * m8, g1 = his(v7, v15) * mk2(a1024, a1024), g2 = g1 * m256;
        __syncwarp();
        st(0, f1, f2, f1 * m256, f2 * m256);
        st(1, g1, g2, g1 * m512, g2 * m512);
        __syncwarp();
        tile(3, 0); tile(4, 1);
        if (pause) mbar_wait_short(pause);
    } while (--nc);
    return eb;
}

__device__ __forceinline__ void near_lags(uint32_t S, int k, uint32_t yo, uint32_t eb) {
    const int lane = threadIdx.x & 31, g = lane >> 2, t = lane & 3, mi = lane >> 3, j = lane & 7, warp = k;
    const uint32_t cb = S + SM_CH + k * CH;
    uint32_t R[66], x[5];
#pragma unroll
    for (int i = 0; i < 66; i++) R[i] = lds32(cb + TAB + 4 * (7 + g - 2 * t) + 32 * i);
    bar_arrive(1 + k, 64);
    float w[5][4];
#pragma unroll
    for (int i = 0; i < 5; i++) w[i][0] = w[i][1] = w[i][2] = w[i][3] = 0.f;
    uint32_t xa[8], xo = cb;
    {
        const uint32_t v = xslot(lane & 15, lane >> 4);
#pragma unroll
        for (int i = 0; i < 8; i++) xa[i] = __shfl_sync(~0u, v, LD4 ? j + i + (mi == 1 ? 17 : (mi == 2 ? 16 : 1)) : j + 2 * (lane & 8) + i);
    }
    uint32_t fa = xa[0], idm = 0;
    uint32_t ya = S + SM_DUMP + 8 * lane, ybar = S + 61 * 8, dy = 0, db = 0;
    const uint32_t sc = prmt(eb + 0x04800000u, 0, 0x3232);
    uint32_t z = lds32(cb + XX + 4 * lane);
    int n = 16;
    mbar_wait(S + B_X * 8, 0);
    uint32_t A[3][4];
    if (LD4) {
        ldm4(xo + xa[0], A[0][0], A[0][1], A[0][2], A[0][3]);
        ldm4(xo + xa[1], A[1][0], A[1][1], A[1][2], A[1][3]);
    } else {
        ldm2(xo + xa[0], x[1], x[0]);
        ldm2(xo + xa[1], x[1], x[2]);
        ldm2(xo + xa[2], x[3], x[4]);
    }
    auto send = [&]() { st_async2(ya, bmul(pack_bf(w[0][0], w[0][1]), sc), bmul(pack_bf(w[0][2], w[0][3]), sc), ybar); };
    auto tile = [&](auto nj) {
        constexpr int NJ = decltype(nj)::value;
        asm volatile("" : "+r"(z), "+r"(xo));
        uint32_t f0, f1;
        ldm2(xo + fa, f0, f1);
        send();
#pragma unroll
        for (int q = 1; q <= 8; q++) {
            uint32_t n0, n1, a2, a3;
            if (LD4) {
                ldm4(xo + xa[(q + 1) & 7] + 32 * ((q + 1) & 8), A[2][0], A[2][1], A[2][2], A[2][3]);
                x[1] = A[0][0]; x[2] = A[0][1]; a2 = A[0][2]; a3 = A[0][3];
#pragma unroll
                for (int e = 0; e < 4; e++) { A[0][e] = A[1][e]; A[1][e] = A[2][e]; }
            } else {
                ldm2(xo + xa[(q + 2) & 7] + 32 * ((q + 2) & 8), n0, n1);
                a2 = x[0] | z; a3 = x[1] | z;
            }
#pragma unroll
            for (int i = 0; i < NJ; i++) {
                const int s = 16 * i + 16 - 2 * q;
                if (q == 1) mma_hc(w[i], w[i + 1], x[1], x[2], a2, a3, R[s], R[s + 1]);
                else mma_h(w[i], x[1], x[2], a2, a3, R[s], R[s + 1]);
            }
            if (q == 4) mma_h8(w[1], f0, f1, idm);
            if (q == 7 && ZZ) {
                const uint32_t zz = x[1] & z;
                ya += dy + zz; ybar += db + zz; dy = 512 - dy; db = 8 - db;
            }
            if (q == 8 && NJ == 4) {
                const float zero[4] = {0.f, 0.f, 0.f, 0.f};
                mma_hc(w[4], zero, x[1], x[2], a2, a3, R[64], R[65]);
            }
            if (!LD4) { x[0] = x[2]; x[1] = x[3]; x[2] = x[4]; x[3] = n0; x[4] = n1; }
        }
        xo += 256; if (!ZZ) { ya += dy; ybar += db; dy = 512 - dy; db = 8 - db; }
    };
    int lim = 15;
#pragma unroll 1
    for (;;) {
        n -= lim;
#pragma unroll 1
        do tile(std::integral_constant<int, 4>()); while (--n);
        n = lim;
        if (n < 5) break;
        const int lane = laneid(), g = lane >> 2, t = lane & 3;
        if (n == 15) {
            ybar = mapa(S + B_Y * 8, g >> 1);
            db = dy = mapa(S + B_Y * 8, 4 + (g >> 1)) - ybar;
            ya = ybar - B_Y * 8 + SM_CH + k * CH + YIN + (yo ^ (8 * (lane & 7)));
        }
        if (n == 13) { fa = TAB - 768 + 16 * (lane & 15); idm = g == 2 * t ? 0x3C00u : (g == 2 * t + 1 ? 0x3C000000u : 0u); }
#pragma unroll 1
        while ((lim = lds32v(S + SM_PROG + 4 * k)) >= n) __nanosleep(40);
        if (n == 15) lim = 13;
    }
#pragma unroll 1
    for (; n > 0; n--) tile(std::integral_constant<int, 2>());
    send();
}

__global__ void __cluster_dims__(8, 1, 1) __launch_bounds__(NTHREADS, 1) fused_kernel(const Hot p, const __grid_constant__ Maps m) {
    extern __shared__ __align__(1024) char smem[];
    const uint32_t t0 = clk32();
    const int tid = threadIdx.x, lane = tid & 31, bx = blockIdx.x;
    const int g = lane >> 2, t = lane & 3, mi = lane >> 3, j = lane & 7;
    const uint32_t role = __shfl_sync(~0u, (tid >> 5) | ((uint32_t)((bx < 24 ? 0x5776666632103210ull : 0x5436666621043210ull) >> ((tid >> 3) & 60)) & 15) << 8 |
                                               max(4 * (bx >> 3), 5 * (bx >> 3) - 3) << 16 | bx << 24, 0);
    const int warp = role & 255, k = (role >> 8) & 255, cbase = (role >> 13) & 0x7F8, bid = role >> 24, r = bid & 7, cl = role >> 27;
    const int pair = cl > 2, nch = 4 + pair;
    uint32_t S = smem_u32(smem);
    asm volatile("" : "+r"(S));

    const int half = warp >= nch;
    const bool two = cl == 1 || cl == 2, extra = two && k == 7, svcwarp = (warp >> 2) == 2;
    KParams kp;
    uint32_t epoch;
    if (k < nch) {
        const uint32_t ch = cbase + 8 * k + r;
        const char* pb = (const char*)p.u + (ch * 256 + half * 128 + lane * 4);
        kp.bre = ldg1(at256(pb, p.bre)); kp.bim = ldg1(at256(pb, p.bim));
        kp.cre = ldg1(at256(pb, p.cre)); kp.cim = ldg1(at256(pb, p.cim));
        kp.ldt = ldg16(at256(p.u + ch, lane & 1 ? p.dskip : p.logdt));
        kp.are = ldg1(at256(pb, p.are)); kp.aim = ldg1(at256(pb, p.aim));
        sts128(S + SM_CH + k * CH + 16 * lane + (half ? FT : (lane < 2 ? TAB : (lane < 8 ? TAB + 2048 : FT + 384))), 0u, 0u, 0u, 0u);
        sts32(S + SM_PROG + 4 * k, 13);
    } else if (warp == 12) {
        if (elect()) {
            mbar_init(S + B_WR * 8, 1);
            mbar_init(S + B_ROWS * 8, 1);
            mbar_expect(S + B_WR * 8, 1152);
            bulk_g2s(S + SM_B + 2048, (const char*)p.u + p.wr * 256ll, 1152, S + B_WR * 8);
            while ((int)(clk32() - t0) < p.tn.t_rows) {}
            mbar_expect(S + B_ROWS * 8, two ? 36864 : 18432);
            const __nv_bfloat16* src = p.u + (8 * (cl & 14) + 2 * r + (cl & 1)) * 9216;
            bulk_g2s(S + SM_TOTAL - 18432, src, 18432, S + B_ROWS * 8);
            if (two) bulk_g2s(S + SM_CH + 4 * CH - 128, p.u + (113 + 2 * r) * 9216, 18432, S + B_ROWS * 8);
        }
    } else if (svcwarp) {
        if (elect()) {
#pragma unroll
            for (int i = 0; i < 16; i++) mbar_init(S + (warp & 3) * 128 + i * 8, warp > (i < 14 ? 10 : 9) ? 4 : 1);
            asm volatile("fence.mbarrier_init.release.cluster;" ::: "memory");
        }
        __syncwarp();
        sts128(S + SM_B + 16 * tid, 0x3F803F80u, 0x3F803F80u, 0x3F803F80u, 0x3F803F80u);
        if (tid < 256 + B_RAW) mbar_expect(S + lane * 8, (uint32_t)(0x0808490101180804ull >> (8 * max(lane - 7, 0)) & 255) * (lane < B_TOP ? 128 * nch : 128));
    }
    if (svcwarp || extra) epoch = ld_rlx(at256(p.u + bid * 16, p.ep));
    __syncthreads();
    asm volatile("barrier.cluster.arrive.relaxed.aligned;" ::: "memory");
    const uint2* sp = &p.s->stat[256 * r + 2 * (tid & 127)];
    uint4 sw;
    if (svcwarp) sw = ld_rlx4(sp);
    if (svcwarp || extra) {
        const uint32_t tag = ~epoch & 1;
        const int tile = extra ? 15 : cl, wj = extra ? warp + 2 * cl - 15 : warp & 3;
        float d2[4] = {0, 0, 0, 0}, d3[4] = {0, 0, 0, 0}, d4[4] = {0, 0, 0, 0}, d5[4] = {0, 0, 0, 0}, d6[4] = {0, 0, 0, 0}, d7[4] = {0, 0, 0, 0};
        const uint32_t xa = S + (extra ? SM_CH + 4 * CH - 128 : SM_TOTAL - 18432) + (8 * (mi >> 1) + 2 * wj + (mi & 1)) * 1152 + 16 * j;
        const uint32_t wa = S + SM_B + 4104 - 2056 * (g & 1) + 64 * (g >> 2) + 16 * t + 2 * (g & 2), ones = 0x3F803F80u;
        uint32_t wv[18];
        mbar_wait_short(S + B_WR * 8);
#pragma unroll
        for (int i = 0; i < 18; i++) wv[i] = lds32(wa + 128 * (i >> 1) + 8 * (i & 1));
#pragma unroll
        for (int i = 0; i < 9; i++) mma_bf(d5, ones, ones, ones, ones, wv[2 * i], wv[2 * i + 1]);
        float wsum = d5[1] + __shfl_xor_sync(~0u, d5[1], 1);
        wsum += __shfl_xor_sync(~0u, wsum, 2);
        mbar_wait_short((S + B_ROWS * 8) | (__float_as_uint(wsum) & p.tn.zero));
        __syncwarp();
#pragma unroll
        for (int i = 0; i < 9; i++) {
            const uint4 x = lds128(xa + 128 * i);
            mma_bf8(d3, x.x, x.y, x.x);
            mma_bf8(d4, x.x, x.y, x.y);
            mma_bf8(d6, x.z, x.w, x.z);
            mma_bf8(d7, x.z, x.w, x.w);
            mma_bf(d2, x.x, x.y, x.z, x.w, wv[2 * i], wv[2 * i + 1]);
        }
        float sx = d2[0] + d2[2], sq = (g & 1) ? (d3[1] + d4[3]) + (d6[1] + d7[3]) : (d3[0] + d4[2]) + (d6[0] + d7[2]);
        float dot = (t & 1) ? d2[3] : d2[1];
        sx += __shfl_xor_sync(~0u, sx, 4);
        sq = __shfl_sync(~0u, sq, 9 * mi) + __shfl_sync(~0u, sq, 9 * mi + 4);
        dot += __shfl_xor_sync(~0u, dot, 1);
        dot += __shfl_xor_sync(~0u, dot, 6);
        const float mean = sx * (1.f / 576.f), var = fmaxf(sq * (1.f / 576.f) - mean * mean, 0.f);
        const float mu = bf_round(mean), sd = bf_round(sqrt_ap(bf_round(bf_round(var) + 1e-5f)));
        const uint32_t idx = 2047 - (128 * (tile & 14) + 32 * r + 16 * (tile & 1) + 8 * (mi >> 1) + 2 * wj + (mi & 1));
        const uint32_t rb = pack_bf(0.f, (dot - mu * wsum) * rcpf(sd));
        uint2 v = make_uint2((__float_as_uint(mu) >> 16) | __float_as_uint(sd), (((rb ^ (((int)rb >> 31) | 0x80000000u)) >> 1) & 0x7FFF8000u) | (tag << 31) | idx);
        uint2* const dst = &p.s->stat[256 * r + 16 * tile];
        if (extra) {
            if (j == 0) st_rlx2(dst + 4 * wj + mi, v.x, v.y);
            bar_arrive(13, 224);
        } else {
        const uint32_t ga = S + SM_B + 3200 + 32 * wj;
        if (j == 0) sts64(ga + 8 * mi, v.x, v.y);
        bar_sync(15, 128);
        if (tid < 272) {
            v = lds64(ga + 8 * lane);
            st_rlx2(dst + lane, v.x, v.y);
        }
        if (lane == 0) mbar_arrive(S + (B_EMPTY + 10) * 8);
        }
    }

    if (k < nch) {
        const uint32_t cb = S + SM_CH + k * CH, scr = cb + BOX + 3072 * half, oth = cb + BOX + 3072 - 3072 * half;
        float d[5][4], k0;
        kp.dsk = __shfl_sync(~0u, kp.ldt, 1);
        kp.ldt = __shfl_sync(~0u, kp.ldt, 0);
        const uint32_t eb = kgen(kp, scr, oth, 1 + k, lane, d, k0, k > 7 - nch ? 3 - 2 * half : 2, ((p.tn.stag >> warp) & 1) ? S + (B_EMPTY + 10) * 8 : 0);
        __syncwarp();
#pragma unroll
        for (int i = 0; i < 5; i++)
            if (half == (i < 3)) sts128f(scr + i * 512 + lane * 16, d[i][0], d[i][1], d[i][2], d[i][3]);
        bar_sync(1 + k, 64);
        auto both = [&](int i, uint32_t& w0, uint32_t& w1) {
            const uint4 v = lds128(oth + i * 512 + lane * 16);
            w0 = pack_h(d[i][0] + __uint_as_float(v.x), d[i][1] + __uint_as_float(v.y));
            w1 = pack_h(d[i][2] + __uint_as_float(v.z), d[i][3] + __uint_as_float(v.w));
        };
        if (half) {
            uint32_t a0, a1, b0, b1;
            both(3, a0, a1); both(4, b0, b1);
            const uint32_t o = cb + FT + 56 + 128 * (t >> 1) + 8 * g + 4 * (t & 1), q = cb + FT + 376 + 64 * t + 4 * g;
            sts32(o, a0); sts32(o + 64, a1); sts32(q, b0); sts32(q + 32, b1);
        } else {
            {
                uint32_t a[2], b[2], c[2], last = pack_h(k0, k0);
                both(0, a[0], a[1]); both(1, b[0], b[1]); both(2, c[0], c[1]);
                const uint32_t o = cb + TAB + 32 + 16 * lane;
                sts16(cb + TAB + 28, last);
#pragma unroll
                for (int h = 0; h < 4; h++) {
                    const uint32_t e = h < 2 ? b[h] : c[h - 2], pv = __shfl_sync(~0u, lane == 31 ? last : e, lane - 1);
                    if (h < 2) sts128(o + 512 * h, prmt(a[h], pv, 0x7610), prmt(a[h], 0, 0x1032), prmt(e, a[h], 0x7610), prmt(e, 0, 0x1032));
                    else sts128(o + 512 * h, prmt(pv, 0, 0x3232), prmt(e, pv, 0x7610), prmt(e, 0, 0x1032), prmt(e, 0, 0x3232));
                    last = e;
                }
                if (lane == 31) sts128(o + 1552, prmt(last, 0, 0x3232), prmt(last, 0, 0x3232), last & 0xFFFF0000u, 0u);
                __syncwarp();
            }
            near_lags(S, k, 64 * r + 16 * ((2 * k + (cbase >> 2) + (r >> 2)) & 3), eb);
            return;
        }
    }

    const int ph0 = pair & ~r, f0 = pair ? 32 * (bid & ~1) + 768 : 64 * bid;
    if (warp == 12) {
        if (elect()) {
            asm volatile("prefetch.tensormap [%0];" ::"l"(&m.u) : "memory");
            spin_until(t0, p.tn.t_tile);
            mbar_expect(S + B_RAW * 8, 256 * PITCH);
            asm volatile("cp.async.bulk.tensor.5d.shared::cluster.global.mbarrier::complete_tx::bytes [%0], [%1, {%3, 0, %4, 0, 0}], [%2];"
                         ::"r"(S + SM_RAW), "l"(&m.u), "r"(S + B_RAW * 8), "r"(cbase), "r"(4 * r) : "memory");
            uint32_t bar = S + B_FULL * 8, dst = S + SM_W, em = 0x1249400u, wm = ~(1u << p.tn.s0) << (p.tn.win0 + 2 - 2 * pair), wb = bar;
#pragma unroll 1
            for (int ph = ph0; ph < 3; ph += 1 + (pair & r)) {
                const int c0 = ph < 2 ? f0 : cbase, c1 = ph < 2 ? 0 : 576 * r;
#pragma unroll 1
                for (int n = 0; n < 576; n += 64) {
                    if (wm & 1) { mbar_wait(wb, 0); wb += 8; }
                    if (em & 1) mbar_wait(bar + 8 * (B_EMPTY - B_FULL), 0);
                    mbar_expect(bar, ph < 2 ? 8192 : 128 * 40);
                    tma2d(dst, m.w + ph, c0, c1 + n, bar);
                    bar += 8; em >>= 1; wm >>= 1;
                    dst = dst == S + SM_W + (NRING - 1) * 8192 ? S + SM_W : dst + 8192;
                }
            }
        }
        return;
    }

    if (warp == 15) {
        asm volatile("barrier.cluster.wait.aligned;" ::: "memory");
        sts32(S + SM_SKIP + 4 * j, 0u);
        const uint32_t ob = mapa(S, g);
        bar_sync(13, two ? 224 : 160);
        const uint4 ka = lds128(S + SM_B + 256 + 16 * lane), kb = lds128(S + SM_B + 768 + 16 * lane);
        uint32_t k0 = ka.x, k1 = ka.y, mine = 0, c = 0;
        int rank = lane;
#pragma unroll 1
        for (int pass = 0;; pass++) {
#pragma unroll 1
            for (int n = 0; n < (pass < 2 ? 4 : 8); n++) {
                const uint32_t a = __viaddmin_u32(k0, c, __viaddmin_u32(k1, c, ka.z + c)), b = __viaddmin_u32(ka.w, c, __viaddmin_u32(kb.x, c, kb.y + c));
                c += ~__reduce_min_sync(~0u, __vimin3_u32(a, b, __viaddmin_u32(kb.z, c, kb.w + c)));
                if ((pass < 2 ? t : j) == n) mine = c;
            }
            if (pass == 2) break;
            asm volatile("st.async.shared::cluster.mbarrier::complete_tx::bytes.b32 [%0], %1, [%2];" ::"r"(ob + SM_CAND + 128 * pass + 16 * r + 4 * t), "r"(~mine), "r"(ob + (B_TOP + pass) * 8) : "memory");
            mbar_wait_short(S + (B_TOP + pass) * 8);
            const uint32_t v = lds32(S + SM_CAND + 4 * lane);
            if (pass) {
                k0 = v; k1 = lds32(S + SM_CAND + 128 + 4 * lane); c = 0;
            } else {
                uint32_t cn[4] = {0, 0, 0, 0};
#pragma unroll 4
                for (int e = 0; e < 128; e += 16) {
                    const uint4 o = lds128(S + SM_CAND + e);
                    cn[0] += (o.x - v) >> 31; cn[1] += (o.y - v) >> 31; cn[2] += (o.z - v) >> 31; cn[3] += (o.w - v) >> 31;
                }
                const int rk = (cn[0] + cn[1]) + (cn[2] + cn[3]);
                if (!__any_sync(~0u, t == 3 && rk < 8)) { rank = rk; mine = ~v; break; }
            }
        }
        const uint32_t row = ~mine & 2047, ix = (row & 0xE0) * 8 + ((row >> 3) & 0xE0) + (row & 0x11) + ((row >> 2) & 2) + (row & 6) * 2;
        const bool own = rank < 8 && (ix >> 8) == r;
        const uint32_t m2 = 2 * mine, rb = (m2 ^ ((~(int)m2 >> 31) | 0x80000000u)) & 0xFFFF0000u;
        if (rank < 8) sts64(S + SM_SEL + 8 * rank, ix | rb, row);
        if (own) asm volatile("red.shared.or.b32 [%0], %1;" ::"r"(S + SM_SKIP + 4 * (ix & 7)), "r"(1u << ((ix >> 3) & 31)) : "memory");
        const uint32_t mr = __reduce_or_sync(~0u, rank == r ? row | ix << 16 : 0u);
        const int no = __popc(__ballot_sync(~0u, own));
        if (lane < 2) mbar_expect(S + (B_FIN + lane) * 8, lane ? 0 : no * (nch - 2) * 256);
        if (elect()) {
            bulk_mc(S + SM_B + BP * r, p.u + (mr & 2047) * D_, 1152, S + B_XS * 8);
            asm volatile("fence.proxy.async.global;" ::: "memory");
            bulk_mc(S + SM_B + BP * r + 1152, (const uint4*)p.s->stat + (mr >> 17), 16, S + B_XS * 8);
        }
    }

    if (svcwarp) {
        const uint32_t tag = ~epoch & 1;
        const int fw = warp & 3, i = tid & 127;
        asm volatile("barrier.cluster.wait.aligned;" ::: "memory");
        mbar_wait_short(S + B_RAW * 8);
#pragma unroll 1
        for (int it = 0; it < SPIN_LIMIT && (int)((sw.y ^ -tag) | (sw.w ^ -tag)) < 0; it++) sw = ld_rlx4(sp);
        sts64(S + SM_B + 256 + 8 * i, ~sw.y, ~sw.w);
        {
            const float r0 = 0.5f * rcpf(bf_hi(sw.x)), r1 = 0.5f * rcpf(bf_hi(sw.z));
            sts128f(S + SM_ST + 16 * (i & 0x71) + 32 * (i & 6) + 4 * (i & 8), r0, -bf_lo(sw.x) * r0, r1, -bf_lo(sw.z) * r1);
        }
        bar_sync(13, two ? 224 : 160);
        if (i == 0) {
            mbar_arrive(S + B_ST * 8);
            st_rlx(&p.s->ep[bid * 8], epoch + 1);
        }
    }
    if (svcwarp || (k >= pair && k < nch)) {
        {
            const int fw = svcwarp ? warp & 3 : k & 3, u0 = svcwarp ? 0 : p.tn.ns0, q0 = 2 * u0 + (fw >> 1);
            const uint32_t xb = mapa(S, g);
            uint32_t xd = xb + SM_CH + xslot(8 + 2 * r + (t >> 1), t & 1) + 512 * q0, xbar = xb + B_X * 8 + (svcwarp ? 0 : 8);
            uint32_t ra = S + SM_RAW + (64 * mi + j + 8 * q0) * PITCH, sa = S + SM_ST + 16 * t + 256 * q0;
            if (!svcwarp) mbar_wait(S + B_ST * 8, 0);
#pragma unroll 1
            for (int u = fw + u0; u < fw + (svcwarp ? p.tn.ns0 : 4); u++) {
                uint4 s[4];
#pragma unroll
                for (int e = 0; e < 4; e++) s[e] = lds128(sa + 64 * e);
#pragma unroll 1
                for (int n = u & 1; n < nch; n += 2) {
                    uint32_t a[4];
                    ldm4t(ra + 16 * n, a);
#pragma unroll
                    for (int e = 0; e < 4; e++)
                        a[e] = pack_h(fmaf(bf_lo(a[e]), __uint_as_float(s[e].x), __uint_as_float(s[e].y)), fmaf(bf_hi(a[e]), __uint_as_float(s[e].z), __uint_as_float(s[e].w)));
                    st_async4(xd + n * CH, a[0], a[1], a[2], a[3], xbar);
                }
                xd += 1024; ra += 16 * PITCH; sa += 512; xbar |= 8;
            }
        }
    }
    if (svcwarp) {
        const uint32_t tag = ~epoch & 1;
        const int fw = warp & 3, i = tid & 127;
        mbar_wait_short(S + B_SEL * 8);
        const uint2 sv = lds64(S + SM_SEL + 8 * j);
        const uint32_t bw = S + SM_B + BP * j + 16 * (i >> 3);
        {
            mbar_wait_short(S + B_XS * 8);
            const uint32_t s1 = lds32(S + SM_B + BP * j + 1152 + 8 * (sv.x & 1));
            uint4 v = lds128(bw);
            const float ri = rcpf(bf_hi(s1));
            const uint32_t mu = prmt(s1, 0, 0x1010), hi = pack_bf(ri, ri), lo = pack_bf(ri - bf_lo(hi), ri - bf_lo(hi));
            auto nrm = [&](uint32_t x) { const uint32_t e = bsub(x, mu); return bfma(e, hi, bmul(e, lo)); };
#pragma unroll 1
            for (int n = 0; n < 1152 - 64 * fw; n += 256) {
                const uint4 x = v;
                v = lds128(bw + n + 256);
                sts128(bw + n, nrm(x.x), nrm(x.y), nrm(x.z), nrm(x.w));
            }
        }
        const uint32_t tx = clk32();
        const int mt = (fw + 3) & 3;
        const uint32_t* const hp = p.s->h + 2304 * r + 4 * i;
        uint32_t bar = S + B_FULL * 8, of = 0;
        const uint32_t aa = S + SM_W + (8 * (mi >> 1) + j) * 128 + (((2 * mt + (mi & 1)) ^ j) << 4);
        float d[4][4];
#pragma unroll 1
        for (int ph = ph0;; ph++) {
            if (ph == 2) {
                bar_sync(15, 128);
                spin_until(tx, p.tn.da);
                uint4 v[5];
                const uint32_t tm = -tag;
#pragma unroll 1
                for (int it = 0; it < SPIN_LIMIT; it++) {
                    uint32_t bad = 0;
#pragma unroll
                    for (int n = 0; n < 5; n++) v[n] = ld_rlx4(hp + (n < 4 ? 512 * n : 1792));
#pragma unroll
                    for (int n = 0; n < 5; n++) bad |= lop_ne(v[n].x, v[n].z, tm);
                    if (!(bad & 1)) break;
                }
#pragma unroll
                for (int n = 0; n < 5; n++) sts128(bw + (n < 4 ? 256 * n : 896), v[n].x, v[n].y, v[n].z, v[n].w);
            }
            if (ph == ph0 || ph == 2) bar_sync(15, 128);
            if (ph == 2 && mt >= nch - 2) break;
#pragma unroll
            for (int e = 0; e < 4; e++) d[0][e] = d[1][e] = d[2][e] = d[3][e] = 0.f;
#pragma unroll 1
            for (int n = 0; n < 1152; n += 384) {
                uint32_t a[12][4], b[24];
                mbar_wait(bar + 8 * min(lane, 2), 0);
                __syncwarp();
#pragma unroll
                for (int e = 0; e < 12; e++) {
                    if (!(e & 1)) ldm4(S + SM_B + BP * j + 16 * mi + n + 32 * e, b[2 * e], b[2 * e + 1], b[2 * e + 2], b[2 * e + 3]);
                    ldm4t(aa + of + 2048 * e, a[e]);
                }

#pragma unroll
                for (int e = 0; e < 12; e++) mma_bf(d[e & 3], a[e][0], a[e][1], a[e][2], a[e][3], b[2 * e], b[2 * e + 1]);
                if (lane == 0) mbar_arrive(min(bar + (B_EMPTY + NRING - B_FULL) * 8, S + 63 * 8));
                bar += 24;
                of = of == 8192 * (NRING - 3) ? 0 : of + 24576;
            }
#pragma unroll
            for (int e = 0; e < 4; e++) d[0][e] = (d[0][e] + d[1][e]) + (d[2][e] + d[3][e]);
            uint32_t k0 = pack_bf(d[0][0], d[0][1]), k1 = pack_bf(d[0][2], d[0][3]);
            const uint32_t ea = SM_FIN + 6144 + 8 * i, eb = B_UP * 8;
            if (ph == 0) {
                const uint32_t ob = mapa(S, r & ~pair);
                st_async2(ob + ea, k0, k1, ob + eb);
                ph += pair;
                continue;
            }
            if (ph == 1) {
                k0 = pack_bf(silu_half(0.5f * bf_lo(k0)), silu_half(0.5f * bf_hi(k0))); k1 = pack_bf(silu_half(0.5f * bf_lo(k1)), silu_half(0.5f * bf_hi(k1)));
                mbar_wait_short((S + eb) | (k0 & k1 & p.tn.zero));
                const uint2 v = lds64(S + ea);
                k0 = bmul(k0, v.x); k1 = bmul(k1, v.y);
                __syncwarp();
            }
            k0 = movm(k0); k1 = movm(k1);
            if (ph == 2) {
                const uint32_t ob = mapa(S, (__shfl_sync(~0u, sv.x, g) >> 8) & 7);
                st_async2(ob + SM_FIN + 768 * g + 96 * r + 32 * mt + 8 * t, k0, k1, ob + B_FIN * 8);
                break;
            }
            const uint32_t o = __shfl_xor_sync(~0u, (lane & 1) ? k0 : k1, 1);
            st_rlx2(p.s->h + 4 * f0 + 64 * mt + 31 * (lane & 1) + lane, (((lane & 1) ? o : k0) & ~1u) | tag, (lane & 1) ? k1 : o);
        }
        const int l = min(lane, 4 * nch - 1);
        int n = fw;
#pragma unroll 1
        for (uint32_t own = __ballot_sync(~0u, ((sv.x >> 8) & 7) == r) & 255; own; own &= own - 1) {
            if (n-- & 3) continue;
            const int tk = __ffs(own) - 1;
            const uint2 e = lds64(S + SM_SEL + 8 * tk), st = lds64(S + SM_ST + 8 * (e.x & 0xE3) + 16 * (e.x & 12) + 2 * (e.x & 16));
            const uint32_t ix = e.x, x = lds32(S + SM_RAW + (16 * (ix & 12) + ((ix >> 2) & 60) + (ix & 3)) * PITCH + 4 * l);
            const uint32_t yb = S + SM_CH + YIN + (l >> 2) * CH + 16 * (ix & 0xE0) + 128 * (l & 3) + 16 * (((ix >> 3) ^ ((l >> 1) + (cbase >> 2))) & 3) + 2 * (ix & 7);
            const float sg = 0.5f * sigm(bf_hi(ix));
            const uint32_t hx = pack_bf(fmaf(bf_lo(x), __uint_as_float(st.x), __uint_as_float(st.y)), fmaf(bf_hi(x), __uint_as_float(st.x), __uint_as_float(st.y))), sg2 = pack_bf(sg, sg);
            mbar_wait((S + B_FIN * 8) | (hx & sg2 & p.tn.zero), 0);
            float a[2] = {0.f, 0.f}, b[2] = {0.f, 0.f};
#pragma unroll
            for (int q = 0; q < 8; q++) {
                const uint32_t v = lds32(S + SM_FIN + 768 * tk + 96 * q + 4 * (l & 24) + 8 * (l & 3) + (l & 4));
                a[q & 1] += bf_lo(v); b[q & 1] += bf_hi(v);
            }
            const uint32_t hv = badd(hx, bmul(pack_bf(a[0] + a[1], b[0] + b[1]), sg2)), gt = pack_bf(silu_half(bf_lo(hv)), silu_half(bf_hi(hv)));
            mbar_wait((S + B_Y * 8 + ((ix >> 2) & 56)) | (gt & p.tn.zero), 0);
            *(uint32_t*)(p.out + e.y * D_ + cbase + 2 * l) = bfma(lds16(yb) | (lds16(yb + 64) << 16), gt, x);
        }
        return;
    }

    mbar_wait(S + B_X * 8, 0);
    if (k < nch) {
        const uint32_t cb = S + SM_CH + k * CH, bx = cb + BOX + 16;
        bar_sync(1 + k, 64);
        float u[4][4], v[4][4], w[4][4];
#pragma unroll
        for (int i = 0; i < 4; i++) v[i][0] = v[i][1] = v[i][2] = v[i][3] = w[i][0] = w[i][1] = w[i][2] = w[i][3] = 0.f;
        uint2 T4[10];
        const uint32_t ta = cb + FT + 4 * (g - t);
#pragma unroll
        for (int e = 0; e < 10; e++) T4[e] = lds64(ta + 24 + 32 * e + 4 * (g - t));
        const uint32_t tb = prmt(lds32(cb + FT + 308), 0, g == 2 * t ? 0x4432 : (g == 2 * t + 1 ? 0x3244 : 0x4444));
        const uint32_t a0 = bx + 576 * (j & 1) + 16 * (j >> 1), a4 = a0 + (mi == 1 ? 1152 : (mi == 2 ? 1136 : 0));
        const uint32_t a8 = a0 + 2304 + 1152 * (mi & 1) + 64 * (mi >> 1), at = bx + 4608 + 576 * (mi & 1) + 128 * (mi >> 1) + 16 * j;
        const uint32_t hb = bx + (lane < 2 ? 1152 + 576 * lane : 2896), o = bx + 16 * lane;
        uint32_t xi = cb + xslot(8 + lane, 0), xp = cb + xslot(7 + lane, 0), hs = cb + XX;
#pragma unroll 1
        for (int n = 9; n > 0; n -= 4) {
            {
                const uint4 hv = lds128(hs);
                hs = hb + 496;
                const uint2 v0 = lds64(xp + 8);
                const uint4 v1 = lds128(xp ^ 32), v2 = lds128(xi), v3 = lds128(xi ^ 32);
                xi += 1024; xp += 1024;
                __syncwarp();
                if (lane < 3) sts128(hb - 16, hv.x, hv.y, hv.z, hv.w);
                const uint32_t P[13] = {v0.x, v0.y, v1.x, v1.y, v1.z, v1.w, v2.x, v2.y, v2.z, v2.w, v3.x, v3.y, v3.z};
                uint32_t Q[12], s2[12], s4[10], b3[11], b5[9];
#pragma unroll
                for (int e = 0; e < 12; e++) { Q[e] = prmt(P[e], P[e + 1], 0x5432); s2[e] = hadd(P[e], Q[e]); }
#pragma unroll
                for (int e = 0; e < 11; e++) b3[e] = hadd(Q[e], s2[e + 1]);
#pragma unroll
                for (int e = 0; e < 10; e++) s4[e] = hadd(s2[e], s2[e + 1]);
#pragma unroll
                for (int e = 0; e < 9; e++) b5[e] = hadd(s4[e + 1], P[e + 3]);
                sts128(o, b3[3], b3[4], b3[5], b3[6]);
                sts128(o + 1152, b3[7], b3[8], b3[9], b3[10]);
                sts128(o + 576, b5[0], b5[1], b5[2], b5[3]);
                sts128(o + 1728, b5[4], b5[5], b5[6], b5[7]);
                if (n > 4) {
                    sts128(o + 4608, s2[4], s2[5], s2[6], s2[7]);
                    sts128(o + 5184, s2[8], s2[9], s2[10], s2[11]);
                    sts128(o + 2304, hadd(b3[0], s4[2]), hadd(b3[1], s4[3]), hadd(b3[2], s4[4]), hadd(b3[3], s4[5]));
                    sts128(o + 3456, hadd(b3[4], s4[6]), hadd(b3[5], s4[7]), hadd(b3[6], s4[8]), hadd(b3[7], s4[9]));
                    sts128(o + 4032, hadd(s4[0], b5[1]), hadd(s4[1], b5[2]), hadd(s4[2], b5[3]), hadd(s4[3], b5[4]));
                    sts128(o + 2896, hadd(s4[4], b5[5]), hadd(s4[5], b5[6]), hadd(s4[6], b5[7]), hadd(s4[7], b5[8]));
                }
                __syncwarp();
            }
            uint32_t A[8][4];
#pragma unroll
            for (int e = 0; e < 8; e++) ldm4t(a4 + 64 * e, A[e]);
#pragma unroll
            for (int e = 0; e < 8; e++)
#pragma unroll
                for (int b = 3; b >= e / 2; b--) {
                    const uint2 T = T4[2 * (b - e / 2) + 1 - (e & 1)];
                    if (e == 0) mma_hc(u[b], v[b], A[e][0], A[e][1], A[e][2], A[e][3], T.x, T.y);
                    else mma_h(u[b], A[e][0], A[e][1], A[e][2], A[e][3], T.x, T.y);
                }
            if (n == 9) mbar_wait_short(S + (B_X + 1) * 8);
#pragma unroll
            for (int e = 0; e < 2; e++)
                stm4t(cb + TAB + 2304 - 256 * n + 512 * e + 16 * lane, pack_h(u[2 * e][0], u[2 * e][1]), pack_h(u[2 * e][2], u[2 * e][3]),
                      pack_h(u[2 * e + 1][0], u[2 * e + 1][1]), pack_h(u[2 * e + 1][2], u[2 * e + 1][3]));
            __syncwarp();
            sts32v(S + SM_PROG + 4 * k, n > 1 ? n : p.tn.tail);
            if (n == 1) break;
            uint32_t C[4][4], E[2][4], T8[16];
#pragma unroll
            for (int e = 0; e < 4; e++) ldm4t(a8 + 128 * e, C[e]);
#pragma unroll
            for (int e = 0; e < 2; e++) ldm4t(at + 256 * e, E[e]);
#pragma unroll
            for (int e = 0; e < 8; e++) T8[e] = lds32(ta + 376 + 32 * (e >> 1) - 16 * (e & 1));
#pragma unroll
            for (int e = 7; e >= 0; e--)
#pragma unroll
                for (int b = 0; b <= e / 2; b++) {
                    const uint2 T = T4[2 * (4 + b - e / 2) + 1 - (e & 1)];
                    if (e == 7) mma_hc(v[b], w[b], A[e][0], A[e][1], A[e][2], A[e][3], T.x, T.y);
                    else mma_h(v[b], A[e][0], A[e][1], A[e][2], A[e][3], T.x, T.y);
                }
#pragma unroll
            for (int e = 3; e >= 0; e--) {
                mma_h8(v[e], E[e >> 1][2 * (e & 1)], E[e >> 1][2 * (e & 1) + 1], tb);
#pragma unroll
                for (int b = 3; b >= e; b--) mma_h(v[b], C[e][0], C[e][1], C[e][2], C[e][3], T8[2 * (b - e)], T8[2 * (b - e) + 1]);
            }
            if (n == 9) {
#pragma unroll
                for (int e = 8; e < 16; e++) T8[e] = lds32(ta + 376 + 32 * (e >> 1) - 16 * (e & 1));
#pragma unroll
                for (int e = 3; e >= 0; e--)
#pragma unroll
                    for (int b = 0; b < 4; b++) mma_h(w[b], C[e][0], C[e][1], C[e][2], C[e][3], T8[2 * (4 + b - e)], T8[2 * (4 + b - e) + 1]);
            }
        }
    }

  {
    int lane;
    asm volatile("mov.u32 %0, %%laneid;" : "=r"(lane));
    const int g = lane >> 2, t = lane & 3, mi = lane >> 3, j = lane & 7, sh = (cbase >> 3) & 1;
    mbar_wait_short(S + B_SEL * 8);
    if (k < 2 * nch - 4) {
        const int q0 = k & 1, kk = (k & 6) - sh;
        uint32_t xa = S + SM_RAW + (16 * (g & 4) + (g & 3) + 8 * q0) * PITCH + 8 * t + 16 * kk, sa = S + SM_ST + 16 * (g & 4) + 8 * (g & 3) + 256 * q0, bar = S + (B_Y + q0) * 8;
        uint32_t ya = S + SM_CH + YIN + ((j >> 2) + kk) * CH + 128 * (j & 2) + 128 * (mi & 1) + 64 * (j & 1) + 16 * ((mi >> 1) ^ (j >> 1)) + 512 * q0;
        uint32_t sk = (unsigned)(kk + (t >> 1)) < (unsigned)nch ? lds32(S + SM_SKIP + 4 * g) >> (4 * q0) : ~0u;
        char* o = (char*)p.out + ((256 * q0 + 32 * r + 4 * (g & 2) + 2 * (g >> 2) + (g & 1)) * D_ + cbase + 8 * kk + 4 * t) * 2;
#pragma unroll 1
        for (int n = 0; n < 4; n++) {
            uint2 x[4];
            uint32_t gt[8], y[2][4];
#pragma unroll
            for (int e = 0; e < 4; e++) {
                x[e] = lds64(xa + (128 * (e & 1) + 2 * (e & 2)) * PITCH);
                const uint2 s = lds64(sa + 128 * (e & 1) + 16 * (e & 2));
                const float a = __uint_as_float(s.x), b = __uint_as_float(s.y);
                gt[2 * e] = pack_bf(silu_half(fmaf(bf_lo(x[e].x), a, b)), silu_half(fmaf(bf_hi(x[e].x), a, b)));
                gt[2 * e + 1] = pack_bf(silu_half(fmaf(bf_lo(x[e].y), a, b)), silu_half(fmaf(bf_hi(x[e].y), a, b)));
            }
            mbar_wait(bar | (((gt[0] | gt[1] | gt[2]) | (gt[3] | gt[4] | gt[5]) | (gt[6] | gt[7])) & p.tn.zero), 0);
            ldm4t(ya, y[0]);
            ldm4t(ya ^ 32, y[1]);
#pragma unroll
            for (int e = 0; e < 4; e++)
                asm volatile("{.reg .pred p; setp.eq.u32 p, %3, 0;\n@p st.global.v2.u32 [%0], {%1, %2};}" ::"l"(o + (8 * (e & 1) + 16 * (e & 2)) * D_),
                             "r"(bfma(y[e >> 1][2 * (e & 1)], gt[2 * e], x[e].x)), "r"(bfma(y[e >> 1][2 * (e & 1) + 1], gt[2 * e + 1], x[e].y)), "r"(sk & (1 << e)) : "memory");
            xa += 16 * PITCH; sa += 512; ya += 1024; bar += 16; sk >>= 8; o += 1024 * D_;
        }
    }
  }
}

typedef CUresult (*EncodeFn)(CUtensorMap*, CUtensorMapDataType, cuuint32_t, void*, const cuuint64_t*, const cuuint64_t*, const cuuint32_t*,
                             const cuuint32_t*, CUtensorMapInterleave, CUtensorMapSwizzle, CUtensorMapL2promotion, CUtensorMapFloatOOBfill);

static void make2d(EncodeFn enc, CUtensorMap* m, const void* base, uint64_t cols, uint64_t rows, uint32_t bc = 64) {
    cuuint64_t gd[2] = {cols, rows};
    cuuint64_t gs[1] = {cols * 2};
    cuuint32_t bd[2] = {bc, 64}, es[2] = {1, 1};
    enc(m, CU_TENSOR_MAP_DATA_TYPE_BFLOAT16, 2, const_cast<void*>(base), gd, gs, bd, es, CU_TENSOR_MAP_INTERLEAVE_NONE, CU_TENSOR_MAP_SWIZZLE_128B,
        CU_TENSOR_MAP_L2_PROMOTION_L2_128B, CU_TENSOR_MAP_FLOAT_OOB_FILL_NONE);
}

static void make5d(EncodeFn enc, CUtensorMap* m, const void* base, uint32_t cols, CUtensorMapSwizzle sw) {
    cuuint64_t gd[5] = {D_, 2, 32, 8, 4};
    cuuint64_t gs[4] = {D_ * 2, D_ * 16, D_ * 512, D_ * 4};
    cuuint32_t bd[5] = {cols, 2, 4, 8, 4}, es[5] = {1, 1, 1, 1, 1};
    enc(m, CU_TENSOR_MAP_DATA_TYPE_BFLOAT16, 5, const_cast<void*>(base), gd, gs, bd, es, CU_TENSOR_MAP_INTERLEAVE_NONE, sw,
        CU_TENSOR_MAP_L2_PROMOTION_NONE, CU_TENSOR_MAP_FLOAT_OOB_FILL_NONE);
}

static Tune g_tune = {2200, 255, 2, 2, 4, 700, 4200, 2, 0};

static int max_clusters() {
    cudaFuncSetAttribute(fused_kernel, cudaFuncAttributeMaxDynamicSharedMemorySize, SM_TOTAL);
    cudaLaunchConfig_t cfg = {};
    cudaLaunchAttribute at[1];
    at[0].id = cudaLaunchAttributeClusterDimension;
    at[0].val.clusterDim.x = 8; at[0].val.clusterDim.y = 1; at[0].val.clusterDim.z = 1;
    cfg.gridDim = dim3(NCTA); cfg.blockDim = dim3(NTHREADS); cfg.dynamicSmemBytes = SM_TOTAL; cfg.attrs = at; cfg.numAttrs = 1;
    int n = 0;
    if (cudaOccupancyMaxActiveClusters(&n, fused_kernel, &cfg) != cudaSuccess) { cudaGetLastError(); n = 0; }
    return n;
}

static bool launch(void* const* d_in, void* d_out) {
    static EncodeFn enc = nullptr;
    static Scratch* gs = nullptr;
    if (!enc) {
        void* fn = nullptr;
        cudaDriverEntryPointQueryResult qr;
        cudaGetDriverEntryPoint("cuTensorMapEncodeTiled", &fn, cudaEnableDefault, &qr);
        enc = (EncodeFn)fn;
        cudaFuncSetAttribute(fused_kernel, cudaFuncAttributeMaxDynamicSharedMemorySize, SM_TOTAL);
        cudaGetSymbolAddress((void**)&gs, g_s);
    }
    Hot p;
    Maps m;
    auto in = [&](int i) { return (const __nv_bfloat16*)d_in[i]; };
    bool ok = true;
    auto off = [&](const void* q) {
        const long long d = (const char*)q - (const char*)d_in[0];
        ok = ok && d / 256 * 256 == d && (int)(d / 256) == d / 256;
        return (int)(d / 256);
    };
    p.u = in(0); p.are = off(in(1)); p.aim = off(in(2)); p.bre = off(in(3)); p.bim = off(in(4)); p.cre = off(in(5)); p.cim = off(in(6));
    p.logdt = off(in(7)); p.dskip = off(in(8)); p.wr = off(in(10)); p.ep = off(gs->ep);
    if (!ok) return false;
    p.out = (__nv_bfloat16*)d_out;
    p.tn = g_tune;
    p.s = gs;
    make2d(enc, &m.w[0], in(12), F_, D_);
    make2d(enc, &m.w[1], in(11), F_, D_);
    make2d(enc, &m.w[2], in(13), D_, F_, 40);
    make5d(enc, &m.u, in(0), 40, CU_TENSOR_MAP_SWIZZLE_NONE);
    fused_kernel<<<NCTA, NTHREADS, SM_TOTAL>>>(p, m);
    return true;
}

}

namespace v2 {

constexpr int L_ = 2048, D_ = 576, F_ = 4608;
constexpr int NDOWN = 72, NMAIN = 128, NCTA = 132, NTHREADS = 512;
constexpr int SPIN_LIMIT = 1 << 16;
constexpr uint32_t SLOT_FREE = 0x7FFFABCDu;

constexpr int SM_PART = 544;
constexpr int SM_RED = SM_PART;
constexpr int SM_STA = 2080;
constexpr int SM_ONES = 2176;
constexpr int SM_KINF = 2192;
constexpr int SM_RP = 2272;
constexpr int SM_XS = 2704;
constexpr int KR_STRIDE = 1296;
constexpr int SM_X0 = 12080, X0_STRIDE = 4512, X0_ODD = 2240;
constexpr int SM_KT = 30128, KT_STRIDE = 3584, KT_P4 = 2144, KT_P8 = 2896;
constexpr int SM_FAR = 44544, FAR_STRIDE = 11328;
constexpr int FB5 = 0, FB3 = 3328, FB9E = 6656, FB9O = 7824, FB7E = 8992, FB7O = 10160;
constexpr int SM_ROWS = SM_FAR, ROW_STRIDE = 1168;
constexpr int SM_STG = SM_FAR + 19968;
constexpr int KG_SCR = 3072;
constexpr int SM_EX = 89856;
constexpr int EX_KT = SM_EX + X0_STRIDE, EX_FAR = EX_KT + KT_STRIDE, EX_HAND = 109312;
constexpr int SM_W_DOWN = 90112, SM_W_BIG = 121856, STAGE = 6144;
constexpr int SM_W_LAST = 12288;
constexpr int SM_TOTAL = 232448;
constexpr int SM_EPOCH = 2528, SM_SKIP = 2536;
static_assert(SM_STG + 8 * KG_SCR <= SM_EX && SM_STG % 128 == 0 && EX_HAND % 128 == 0 && EX_FAR + FAR_STRIDE <= EX_HAND && EX_HAND + 12288 <= SM_W_BIG, "scratch");

enum { B_ROWS = 0, B_KG, B_X0, B_X1, B_BOX  , B_TAB, B_EM = 6, B_SP = 10, B_OUT = 14, B_H = 15, B_RED = 16, B_TAB1 = 17, B_XS = 18, B_GX = 19, B_YIN = 22, B_P1 = 26, B_FD, B_GU = 28, B_W = 34, B_COUNT = 58 };

struct Tune { short f_start, f_t3, w2, w2b, w3, t_xs, t_svc, t_marg, f_t2, w1, zero, pad; };

struct Scratch {
    uint32_t x[144 * 4096];
    uint32_t y[128 * 4608];
    uint32_t h[2][F_ * 4];
    uint32_t key[L_];
    uint32_t stat[L_];
    uint32_t sel[4][32];
    uint32_t cnt[17 * 32];
};
__device__ __align__(1024) Scratch g_s;

struct Hot {
    const __nv_bfloat16* u;
    Scratch* s;
    const __nv_bfloat16 *wr, *are, *aim, *bre, *bim, *cre, *cim, *logdt;
    Tune tn;
    const __nv_bfloat16 *dskip, *pwg, *pwu, *pwd;
    __nv_bfloat16* out;
};
struct Maps { CUtensorMap wg, wu, wd; };

__device__ __forceinline__ uint32_t smem_u32(const void* p) { return (uint32_t)__cvta_generic_to_shared(p); }
__device__ __forceinline__ void mbar_init(uint32_t b, int c) { asm volatile("mbarrier.init.shared::cta.b64 [%0], %1;" ::"r"(b), "r"(c) : "memory"); }
__device__ __forceinline__ void mbar_expect(uint32_t b, int bytes) { asm volatile("mbarrier.arrive.expect_tx.shared::cta.b64 _, [%0], %1;" ::"r"(b), "r"(bytes) : "memory"); }
__device__ __forceinline__ void mbar_arrive(uint32_t b) { asm volatile("mbarrier.arrive.shared::cta.b64 _, [%0];" ::"r"(b) : "memory"); }
__device__ __forceinline__ bool elect() { uint32_t d; asm volatile("{.reg .pred p; elect.sync _|p, 0xffffffff; selp.u32 %0,1,0,p;}" : "=r"(d)); return d; }
__device__ __forceinline__ bool mbar_test(uint32_t b, int par) {
    uint32_t d;
    asm volatile("{.reg .pred p; mbarrier.test_wait.parity.shared::cta.b64 p, [%1], %2; selp.u32 %0,1,0,p;}" : "=r"(d) : "r"(b), "r"(par) : "memory");
    return d;
}
#define WAIT_LOOP(ins) "{\n.reg .pred p;\n.reg .u32 n;\nmov.u32 n, 0;\nLW:\n" ins " p, [%0], %1;\n@p bra LD;\nadd.u32 n, n, 1;\nsetp.lt.u32 p, n, 16384;\n@p bra LW;\nLD:\n}"
__device__ __forceinline__ void mbar_wait(uint32_t b, int par) { asm volatile(WAIT_LOOP("mbarrier.try_wait.parity.shared::cta.b64")::"r"(b), "r"(par) : "memory"); }
__device__ __forceinline__ uint32_t mapa(uint32_t a, uint32_t rank) { uint32_t d; asm("mapa.shared::cluster.u32 %0, %1, %2;" : "=r"(d) : "r"(a), "r"(rank)); return d; }
__device__ __forceinline__ void bulk_g2s(uint32_t dst, const void* src, int bytes, uint32_t bar) {
    asm volatile("cp.async.bulk.shared::cluster.global.mbarrier::complete_tx::bytes [%0], [%1], %2, [%3];" ::"r"(dst), "l"(src), "r"(bytes), "r"(bar) : "memory");
}
__device__ __forceinline__ void tma2d(uint32_t dst, const CUtensorMap* m, int c0, int c1, uint32_t bar) {
    asm volatile("cp.async.bulk.tensor.2d.shared::cluster.global.mbarrier::complete_tx::bytes [%0], [%1, {%3, %4}], [%2];" ::"r"(dst), "l"(m), "r"(bar), "r"(c0), "r"(c1) : "memory");
}
__device__ __forceinline__ void pf_tmap(const CUtensorMap* m) { asm volatile("prefetch.tensormap [%0];" ::"l"(m) : "memory"); }
__device__ __forceinline__ void bar_sync(int id, int n) { asm volatile("bar.sync %0, %1;" ::"r"(id), "r"(n) : "memory"); }
__device__ __forceinline__ uint4 ld_rlx4(const void* p) { uint4 v; asm volatile("ld.relaxed.gpu.global.v4.u32 {%0,%1,%2,%3}, [%4];" : "=r"(v.x), "=r"(v.y), "=r"(v.z), "=r"(v.w) : "l"(p) : "memory"); return v; }
__device__ __forceinline__ uint32_t ld_rlx(const void* p) { uint32_t v; asm volatile("ld.relaxed.gpu.global.u32 %0, [%1];" : "=r"(v) : "l"(p) : "memory"); return v; }
__device__ __forceinline__ void st_rlx(void* p, uint32_t v) { asm volatile("st.relaxed.gpu.global.u32 [%0], %1;" ::"l"(p), "r"(v) : "memory"); }
__device__ __forceinline__ uint32_t lds32(uint32_t a) { uint32_t v; asm volatile("ld.shared.u32 %0, [%1];" : "=r"(v) : "r"(a) : "memory"); return v; }
__device__ __forceinline__ uint32_t lds32v(uint32_t a) { uint32_t v; asm volatile("ld.volatile.shared.u32 %0, [%1];" : "=r"(v) : "r"(a) : "memory"); return v; }
__device__ __forceinline__ uint4 lds128v(uint32_t a) { uint4 v; asm volatile("ld.volatile.shared.v4.u32 {%0,%1,%2,%3}, [%4];" : "=r"(v.x), "=r"(v.y), "=r"(v.z), "=r"(v.w) : "r"(a) : "memory"); return v; }
__device__ __forceinline__ uint32_t lds16(uint32_t a) { uint16_t v; asm volatile("ld.shared.u16 %0, [%1];" : "=h"(v) : "r"(a) : "memory"); return v; }
__device__ __forceinline__ uint2 lds64(uint32_t a) { uint2 v; asm volatile("ld.shared.v2.u32 {%0,%1}, [%2];" : "=r"(v.x), "=r"(v.y) : "r"(a) : "memory"); return v; }
__device__ __forceinline__ uint4 lds128(uint32_t a) { uint4 v; asm volatile("ld.shared.v4.u32 {%0,%1,%2,%3}, [%4];" : "=r"(v.x), "=r"(v.y), "=r"(v.z), "=r"(v.w) : "r"(a) : "memory"); return v; }
__device__ __forceinline__ void sts16(uint32_t a, uint32_t v) { asm volatile("st.shared.u16 [%0], %1;" ::"r"(a), "h"((uint16_t)v) : "memory"); }
__device__ __forceinline__ void sts32(uint32_t a, uint32_t v) { asm volatile("st.shared.u32 [%0], %1;" ::"r"(a), "r"(v) : "memory"); }
__device__ __forceinline__ void sts64(uint32_t a, uint32_t x, uint32_t y) { asm volatile("st.shared.v2.u32 [%0], {%1,%2};" ::"r"(a), "r"(x), "r"(y) : "memory"); }
__device__ __forceinline__ void sts128(uint32_t a, uint32_t x, uint32_t y, uint32_t z, uint32_t w) { asm volatile("st.shared.v4.u32 [%0], {%1,%2,%3,%4};" ::"r"(a), "r"(x), "r"(y), "r"(z), "r"(w) : "memory"); }
__device__ __forceinline__ void st_async32(uint32_t a, uint32_t v, uint32_t bar) {
    asm volatile("st.async.shared::cluster.mbarrier::complete_tx::bytes.b32 [%0], %1, [%2];" ::"r"(a), "r"(v), "r"(bar) : "memory");
}
__device__ __forceinline__ void ldm4(uint32_t a, uint32_t& r0, uint32_t& r1, uint32_t& r2, uint32_t& r3) {
    asm volatile("ldmatrix.sync.aligned.m8n8.x4.shared.b16 {%0,%1,%2,%3}, [%4];" : "=r"(r0), "=r"(r1), "=r"(r2), "=r"(r3) : "r"(a) : "memory");
}
__device__ __forceinline__ void ldm4t(uint32_t a, uint32_t& r0, uint32_t& r1, uint32_t& r2, uint32_t& r3) {
    asm volatile("ldmatrix.sync.aligned.m8n8.x4.trans.shared.b16 {%0,%1,%2,%3}, [%4];" : "=r"(r0), "=r"(r1), "=r"(r2), "=r"(r3) : "r"(a) : "memory");
}
__device__ __forceinline__ void ldm2(uint32_t a, uint32_t& r0, uint32_t& r1) {
    asm volatile("ldmatrix.sync.aligned.m8n8.x2.shared.b16 {%0,%1}, [%2];" : "=r"(r0), "=r"(r1) : "r"(a) : "memory");
}
__device__ __forceinline__ void stm4(uint32_t a, uint32_t r0, uint32_t r1, uint32_t r2, uint32_t r3) {
    asm volatile("stmatrix.sync.aligned.m8n8.x4.shared.b16 [%0], {%1,%2,%3,%4};" ::"r"(a), "r"(r0), "r"(r1), "r"(r2), "r"(r3) : "memory");
}
__device__ __forceinline__ void mma_bf(float& c0, float& c1, float& c2, float& c3, uint32_t a0, uint32_t a1, uint32_t a2, uint32_t a3, uint32_t b0, uint32_t b1) {
    asm volatile("mma.sync.aligned.m16n8k16.row.col.f32.bf16.bf16.f32 {%0,%1,%2,%3},{%4,%5,%6,%7},{%8,%9},{%0,%1,%2,%3};"
                 : "+f"(c0), "+f"(c1), "+f"(c2), "+f"(c3) : "r"(a0), "r"(a1), "r"(a2), "r"(a3), "r"(b0), "r"(b1));
}
__device__ __forceinline__ void mma_bf(float (&c)[4], uint32_t a0, uint32_t a1, uint32_t a2, uint32_t a3, uint32_t b0, uint32_t b1) { mma_bf(c[0], c[1], c[2], c[3], a0, a1, a2, a3, b0, b1); }
__device__ __forceinline__ void mma_h(float (&c)[4], uint32_t a0, uint32_t a1, uint32_t a2, uint32_t a3, uint32_t b0, uint32_t b1) {
    asm volatile("mma.sync.aligned.m16n8k16.row.col.f32.f16.f16.f32 {%0,%1,%2,%3},{%4,%5,%6,%7},{%8,%9},{%0,%1,%2,%3};"
                 : "+f"(c[0]), "+f"(c[1]), "+f"(c[2]), "+f"(c[3]) : "r"(a0), "r"(a1), "r"(a2), "r"(a3), "r"(b0), "r"(b1));
}
__device__ __forceinline__ void mma_bf8(float (&c)[4], uint32_t a0, uint32_t a1, uint32_t b0) {
    asm volatile("mma.sync.aligned.m16n8k8.row.col.f32.bf16.bf16.f32 {%0,%1,%2,%3},{%4,%5},{%6},{%0,%1,%2,%3};"
                 : "+f"(c[0]), "+f"(c[1]), "+f"(c[2]), "+f"(c[3]) : "r"(a0), "r"(a1), "r"(b0));
}
__device__ __forceinline__ uint32_t pack_bf(float lo, float hi) { uint32_t r; asm("cvt.rn.bf16x2.f32 %0, %1, %2;" : "=r"(r) : "f"(hi), "f"(lo)); return r; }
__device__ __forceinline__ uint32_t pack_h(float lo, float hi) { uint32_t r; asm("cvt.rn.f16x2.f32 %0, %1, %2;" : "=r"(r) : "f"(hi), "f"(lo)); return r; }
__device__ __forceinline__ float bf_lo(uint32_t w) { return __uint_as_float(w << 16); }
__device__ __forceinline__ float bf_hi(uint32_t w) { return __uint_as_float(w & 0xFFFF0000u); }
__device__ __forceinline__ float bf_round(float x) { return bf_lo(pack_bf(x, 0.f)); }
__device__ __forceinline__ uint32_t badd(uint32_t a, uint32_t b) { uint32_t r; asm("add.rn.bf16x2 %0, %1, %2;" : "=r"(r) : "r"(a), "r"(b)); return r; }
__device__ __forceinline__ uint32_t bsub(uint32_t a, uint32_t b) { uint32_t r; asm("sub.rn.bf16x2 %0, %1, %2;" : "=r"(r) : "r"(a), "r"(b)); return r; }
__device__ __forceinline__ uint32_t bmul(uint32_t a, uint32_t b) { uint32_t r; asm("mul.rn.bf16x2 %0, %1, %2;" : "=r"(r) : "r"(a), "r"(b)); return r; }
__device__ __forceinline__ uint32_t bfma(uint32_t a, uint32_t b, uint32_t c) { uint32_t r; asm("fma.rn.bf16x2 %0, %1, %2, %3;" : "=r"(r) : "r"(a), "r"(b), "r"(c)); return r; }
__device__ __forceinline__ uint32_t prmt(uint32_t a, uint32_t b, uint32_t s) { uint32_t r; asm("prmt.b32 %0, %1, %2, %3;" : "=r"(r) : "r"(a), "r"(b), "r"(s)); return r; }
__device__ __forceinline__ float ex2f(float x) { float r; asm("ex2.approx.ftz.f32 %0, %1;" : "=f"(r) : "f"(x)); return r; }
__device__ __forceinline__ float rcpf(float x) { float r; asm("rcp.approx.ftz.f32 %0, %1;" : "=f"(r) : "f"(x)); return r; }
__device__ __forceinline__ float silu_f(float x) { return x * rcpf(1.f + ex2f(-1.4426950408889634f * x)); }
__device__ __forceinline__ uint32_t norm2(uint32_t x, uint32_t m, uint32_t hi, uint32_t lo) { uint32_t d = bsub(x, m); return bfma(d, hi, bmul(d, lo)); }
__device__ __forceinline__ uint32_t clk32() { uint32_t c; asm volatile("mov.u32 %0, %%clock;" : "=r"(c)); return c; }
__device__ __forceinline__ void spin_until(uint32_t t0, int dt) {
#pragma unroll 1
    while ((int)(clk32() - t0) < dt) __nanosleep(32);
}
__device__ __forceinline__ float sqrt_ap(float x) { float r; asm("sqrt.approx.ftz.f32 %0, %1;" : "=f"(r) : "f"(x)); return r; }

__device__ __forceinline__ void cp16(uint32_t dst, const void* src) { asm volatile("cp.async.cg.shared.global [%0], [%1], 16;" ::"r"(dst), "l"(src) : "memory"); }
__device__ __forceinline__ void pf_l2(const void* p) { asm volatile("cp.async.bulk.prefetch.L2.global [%0], 16;" ::"l"(p) : "memory"); }
__device__ __forceinline__ void bulk_s2g(void* dst, uint32_t src, int bytes) {
    asm volatile("cp.async.bulk.global.shared::cta.bulk_group [%0], [%1], %2;" ::"l"(dst), "r"(src), "r"(bytes) : "memory");
}
__device__ __forceinline__ uint32_t ld_acq(const void* p) { uint32_t v; asm volatile("ld.acquire.gpu.global.u32 %0, [%1];" : "=r"(v) : "l"(p) : "memory"); return v; }
__device__ __forceinline__ void red_add(void* p) { asm volatile("red.relaxed.gpu.global.add.u32 [%0], 1;" ::"l"(p) : "memory"); }
__device__ __forceinline__ void fence_async() { asm volatile("fence.proxy.async.shared::cta;" ::: "memory"); }
__device__ __forceinline__ void fence_async_g() { asm volatile("fence.proxy.async.global;" ::: "memory"); }
__device__ __forceinline__ void red_rel(void* p) { asm volatile("red.release.gpu.global.add.u32 [%0], 1;" ::"l"(p) : "memory"); }
__device__ __forceinline__ void wait_count(const uint32_t* p, uint32_t want) {
#pragma unroll 1
    for (int it = 0; it < SPIN_LIMIT && ld_rlx(p) != want; it++) __nanosleep(20);
}
__device__ __forceinline__ uint32_t ld_stat(const uint32_t* p, uint32_t tag) {
    uint32_t v = 0;
#pragma unroll 1
    for (int it = 0; it < SPIN_LIMIT; it++) {
        v = ld_rlx(p);
        if ((v >> 31) == tag) break;
    }
    return v & 0x7FFFFFFFu;
}
__device__ __forceinline__ uint32_t hadd(uint32_t a, uint32_t b) { uint32_t r; asm("add.rn.f16x2 %0, %1, %2;" : "=r"(r) : "r"(a), "r"(b)); return r; }
__device__ __forceinline__ float h_lo(uint32_t w) { return __half2float(__ushort_as_half((unsigned short)w)); }
__device__ __forceinline__ float h_hi(uint32_t w) { return __half2float(__ushort_as_half((unsigned short)(w >> 16))); }
__device__ __forceinline__ uint32_t x0_chunk(uint32_t xb, int c) { return xb + ((c & 1) ? X0_ODD + 120 : 128) + 8 * c; }

struct cf { float x, y; };
__device__ __forceinline__ cf cmul(cf a, cf b) { return {a.x * b.x - a.y * b.y, a.x * b.y + a.y * b.x}; }
__device__ __forceinline__ cf csq(cf a) { return {a.x * a.x - a.y * a.y, (a.x + a.x) * a.y}; }
__device__ __forceinline__ cf cpow_direct(float zr2, float zi, float l) {
    const float mag = ex2f(zr2 * l), th = zi * l;
    return {mag * __cosf(th), mag * __sinf(th)};
}
__device__ __forceinline__ __half2 as_h2(uint32_t v) { return *reinterpret_cast<__half2*>(&v); }
__device__ __forceinline__ uint32_t as_u32(__half2 v) { return *reinterpret_cast<uint32_t*>(&v); }
struct hm { uint32_t v, s; };
__device__ __forceinline__ hm mk_hm(cf a) {
    const uint32_t v = pack_h(a.x, a.y);
    return {v, prmt(v, v, 0x1032) ^ 0x8000u};
}
__device__ __forceinline__ uint32_t hcmul(uint32_t x, hm y) {
    const __half2 xx = as_h2(x);
    return as_u32(__hfma2(__high2half2(xx), as_h2(y.s), __hmul2(__low2half2(xx), as_h2(y.v))));
}

struct KParams { uint32_t are, aim, bre, bim, cre, cim, ldt; };
__device__ __forceinline__ KParams kgen_load(const Hot& p, int ch, int half, int lane) {
    const uint32_t po = ch * 64 + half * 32 + lane;
    KParams k;
    k.are = __ldg((const uint32_t*)p.are + po); k.aim = __ldg((const uint32_t*)p.aim + po);
    k.bre = __ldg((const uint32_t*)p.bre + po); k.bim = __ldg((const uint32_t*)p.bim + po);
    k.cre = __ldg((const uint32_t*)p.cre + po); k.cim = __ldg((const uint32_t*)p.cim + po);
    k.ldt = __ldg((const uint16_t*)p.logdt + ch + (lane & p.tn.zero));
    return k;
}

__device__ __forceinline__ void kgen(KParams kp, uint32_t scr, uint32_t os, int c0, int c1, uint32_t pause) {
    const int lane = threadIdx.x & 31;
    const float dt = bf_round(ex2f(bf_lo(kp.ldt) * 1.4426950408889634f));
    const cf w0 = cmul({bf_lo(kp.cre), bf_lo(kp.cim)}, {dt * bf_lo(kp.bre), dt * bf_lo(kp.bim)});
    const cf w1 = cmul({bf_hi(kp.cre), bf_hi(kp.cim)}, {dt * bf_hi(kp.bre), dt * bf_hi(kp.bim)});
    uint32_t eb = __reduce_max_sync(~0u, __float_as_uint(fmaxf(fmaxf(fabsf(w0.x), fabsf(w0.y)), fmaxf(fabsf(w1.x), fabsf(w1.y))))) & 0x7F800000u;
    eb = min(max(eb, 0x00800000u), 0x7E800000u);
    const float sc = __uint_as_float(0x7F000000u - eb);
    float k0 = c0 ? 0.f : w0.x + w1.x;
#pragma unroll
    for (int o = 16; o > 0; o >>= 1) k0 += __shfl_xor_sync(~0u, k0, o);
    float d[5][4];
#pragma unroll
    for (int i = 0; i < 5; i++) d[i][0] = d[i][1] = d[i][2] = d[i][3] = 0.f;
    const int mi = lane >> 3, j = lane & 7;
    const uint32_t st0 = scr + mi * 128 + ((j ^ mi) << 4), st1 = st0 ^ 64;
    const uint32_t la = scr + (lane & 15) * 128 + (((lane >> 4) ^ j) << 4), lb = scr + j * 128 + ((mi ^ j) << 4);
    auto st = [&](int row, uint32_t a, uint32_t b, uint32_t c, uint32_t e) { stm4(((row & 4) ? st1 : st0) + row * 128, a, b, c, e); };
#pragma unroll 1
    for (int c = c0; c < c1; c++) {
        if (c > c0 && pause) mbar_wait(pause, 0);
        const float zr2 = dt * (c ? bf_hi(kp.are) : bf_lo(kp.are)) * 1.4426950408889634f;
        const float zi = dt * (c ? bf_hi(kp.aim) : bf_lo(kp.aim));
        const cf w = {(c ? w1.x : w0.x) * sc, (c ? w1.y : w0.y) * sc};
        const cf a1 = cpow_direct(zr2, zi, 1.f), a256 = cpow_direct(zr2, zi, 256.f);
        uint32_t a[4][4];
        {
            const cf a16 = cpow_direct(-zr2, zi, -16.f);
            const cf a32 = csq(a16), a48 = cmul(a32, a16), a64 = csq(a32), a128 = csq(a64), a192 = cmul(a128, a64);
            const uint32_t p1 = pack_h(a16.x, a16.y), p2 = pack_h(a32.x, a32.y), p3 = pack_h(a48.x, a48.y);
            const hm q1 = mk_hm(a64), q2 = mk_hm(a128), q3 = mk_hm(a192);
            __syncwarp();
            st(0, 0x00003C00u, p1, p2, p3);
            st(4, q1.v, hcmul(p1, q1), hcmul(p2, q1), hcmul(p3, q1));
            st(8, q2.v, hcmul(p1, q2), hcmul(p2, q2), hcmul(p3, q2));
            st(12, q3.v, hcmul(p1, q3), hcmul(p2, q3), hcmul(p3, q3));
            __syncwarp();
#pragma unroll
            for (int k = 0; k < 4; k++) ldm4(la ^ (k * 32), a[k][0], a[k][1], a[k][2], a[k][3]);
        }
        auto tile = [&](int T, int row) {
#pragma unroll
            for (int kp2 = 0; kp2 < 2; kp2++) {
                uint32_t b0, b1, b2, b3;
                ldm4((lb ^ (kp2 * 64)) + row * 128, b0, b1, b2, b3);
                mma_h(d[T], a[2 * kp2][0], a[2 * kp2][1], a[2 * kp2][2], a[2 * kp2][3], b0, b1);
                mma_h(d[T], a[2 * kp2 + 1][0], a[2 * kp2 + 1][1], a[2 * kp2 + 1][2], a[2 * kp2 + 1][3], b2, b3);
            }
        };
        const cf a2 = csq(a1), a4 = csq(a2), a8 = csq(a4), a12 = cmul(a8, a4);
        const cf u1 = cmul(w, a1), u2 = cmul(w, a2), u3 = cmul(u2, a1), u4 = cmul(w, a4);
        uint32_t v[16];
        v[0] = pack_h(u1.x, u1.y); v[1] = pack_h(u2.x, u2.y); v[2] = pack_h(u3.x, u3.y); v[3] = pack_h(u4.x, u4.y);
        const hm m4 = mk_hm(a4), m8 = mk_hm(a8), m12 = mk_hm(a12);
#pragma unroll
        for (int i = 0; i < 4; i++) { v[4 + i] = hcmul(v[i], m4); v[8 + i] = hcmul(v[i], m8); v[12 + i] = hcmul(v[i], m12); }
        const hm m256 = mk_hm(a256);
        __syncwarp();
#pragma unroll
        for (int i = 0; i < 4; i++) st(4 * i, v[4 * i], v[4 * i + 1], v[4 * i + 2], v[4 * i + 3]);
        st(16, hcmul(v[1], m256), hcmul(v[3], m256), hcmul(v[5], m256), hcmul(v[7], m256));
        st(20, hcmul(v[9], m256), hcmul(v[11], m256), hcmul(v[13], m256), hcmul(v[15], m256));
        __syncwarp();
        tile(0, 0); tile(1, 8); tile(2, 16);
        const cf a512 = csq(a256), a768 = cmul(a512, a256), a1024 = csq(a512);
        const cf a1280 = cmul(a1024, a256), a1536 = csq(a768), a1792 = cmul(a1024, a768);
        const hm m512 = mk_hm(a512), m768 = mk_hm(a768);
        const hm n0 = mk_hm(a1024), n1 = mk_hm(a1280), n2 = mk_hm(a1536), n3 = mk_hm(a1792);
        __syncwarp();
        st(0, hcmul(v[3], m512), hcmul(v[7], m512), hcmul(v[11], m512), hcmul(v[15], m512));
        st(4, hcmul(v[3], m768), hcmul(v[7], m768), hcmul(v[11], m768), hcmul(v[15], m768));
        st(8, hcmul(v[7], n0), hcmul(v[15], n0), hcmul(v[7], n1), hcmul(v[15], n1));
        st(12, hcmul(v[7], n2), hcmul(v[15], n2), hcmul(v[7], n3), hcmul(v[15], n3));
        __syncwarp();
        tile(3, 0); tile(4, 8);
    }
    __syncwarp();
#pragma unroll
    for (int i = 0; i < 5; i++) sts128(os + i * 512 + lane * 16, __float_as_uint(d[i][0]), __float_as_uint(d[i][1]), __float_as_uint(d[i][2]), __float_as_uint(d[i][3]));
    sts64(os + 2560, eb, __float_as_uint(k0));
}

__device__ __forceinline__ void ktables(uint32_t os, int ostep, int np, uint32_t kr, uint32_t kt, uint32_t kinf, int part) {
    const int lane = threadIdx.x & 31, g = lane >> 2, t = lane & 3;
    uint32_t eb = 0;
    float k0 = 0.f, f[4];
#pragma unroll
    for (int q = 0; q < 4; q++) {
        uint2 v = make_uint2(0u, 0u);
        if (q < np) v = lds64(os + q * ostep + 2560);
        eb = max(eb, v.x);
        k0 += __uint_as_float(v.y);
        f[q] = __uint_as_float(v.x);
    }
    const float rs = __uint_as_float(0x7F000000u - eb);
#pragma unroll
    for (int q = 0; q < 4; q++) f[q] *= rs;
#pragma unroll 1
    for (int i = (part & 1) ? 0 : 2; i < ((part & 2) ? 5 : 3); i++) {
        float a0 = 0.f, a1 = 0.f, a2 = 0.f, a3 = 0.f;
        uint4 v[4];
#pragma unroll
        for (int q = 0; q < 4; q++) {
            v[q] = make_uint4(0u, 0u, 0u, 0u);
            if (q < np) v[q] = lds128(os + q * ostep + i * 512 + lane * 16);
        }
#pragma unroll
        for (int q = 0; q < 4; q++) { a0 += __uint_as_float(v[q].x) * f[q]; a1 += __uint_as_float(v[q].y) * f[q]; a2 += __uint_as_float(v[q].z) * f[q]; a3 += __uint_as_float(v[q].w) * f[q]; }
        const int sg = 32 >> max(i - 1, 0);
        const uint32_t o = kr + 4 + (i < 2 ? 16 * i : 256 * i) + sg * g + (i < 3 ? 8 : 128) * (t >> 1) + (i < 4 ? 4 : 64) * (t & 1);
        sts32(o, pack_h(a0, a1));
        sts32(o + 8 * sg, pack_h(a2, a3));
    }
    sts32(kr, pack_h(0.f, k0 * rs));
    __syncwarp();
    if (part & 1) {
        uint32_t w0[4], w1[4], a[2], b[2];
#pragma unroll
        for (int r = 0; r < 4; r++) { w0[r] = lds32(kr + 4 * lane + 128 * r); w1[r] = lds32(kr + 4 * lane + 128 * r + 4); }
#pragma unroll
        for (int r = 0; r < 2; r++) { a[r] = lds32(kr + 512 + 4 * lane + 128 * r); b[r] = lds32(kr + 516 + 4 * lane + 128 * r); }
#pragma unroll
        for (int r = 0; r < 4; r++) sts64(kt + 8 * lane + 256 * r + 32, prmt(w0[r], w0[r], 0x1032), prmt(w0[r], w1[r], 0x3254));
        if (lane == 31) b[1] = pack_h(h_lo(b[1]) - h_hi(b[1]), 0.f);
#pragma unroll
        for (int r = 0; r < 2; r++)
            sts128(kt + 4 * 264 + 16 * lane + 512 * r, prmt(a[r], a[r], (r == 0 && lane == 0) ? 0x1032 : 0x3232), prmt(a[r], a[r], 0x3232), prmt(a[r], b[r], 0x3254), prmt(b[r], b[r], 0x1032));
        if (lane < 24) sts32(kt + 4 * (lane < 8 ? lane : 512 + lane), 0u);
    }
    if (part & 2) {
        const uint32_t k512 = lds16(kr + 2 * 385), k1024 = lds16(kr + 2 * 513);
        if (lane == 0) {
            sts128(kinf, eb, __float_as_uint(h_lo(k512)), k1024, 0u);
            sts16(kr + 2 * 512, pack_h(h_lo(lds16(kr + 2 * 512)) - h_lo(k1024), 0.f));
        }
#pragma unroll
        for (int r = 0; r < 3; r++)
            if (r < 2 || lane < 26) sts128(kt + KT_P4 + 16 * lane + 512 * r, 0u, 0u, 0u, 0u);
        __syncwarp();
        uint32_t x0[5], x1[5], y0[5], y1[5];
#pragma unroll
        for (int r = 0; r < 5; r++) {
            const int m = min(126 + lane + 32 * r, 256);
            x0[r] = lds16(kr + 2 * (257 + m)); x1[r] = lds16(kr + 2 * (259 + m)); y0[r] = lds16(kr + 2 * (385 + m)); y1[r] = lds16(kr + 2 * (387 + m));
        }
#pragma unroll
        for (int r = 0; r < 5; r++) {
            const int m = 126 + lane + 32 * r;
            if (m < 128) x0[r] = y0[r] = 0;
            if (m > 253) x1[r] = 0;
            if (m > 254) y1[r] = 0;
            if (m < 256) sts32(kt + KT_P4 + 4 * (((m - 96) & ~3) | ((m & 1) << 1) | ((m >> 1) & 1)), x0[r] | (x1[r] << 16));
            if (m < 257) sts32(kt + KT_P8 + 4 * (m - 96), y0[r] | (y1[r] << 16));
        }
    }
    __syncwarp();
}

__device__ __forceinline__ void mma_hc(float (&d)[4], const float (&c)[4], uint32_t a0, uint32_t a1, uint32_t a2, uint32_t a3, uint32_t b0, uint32_t b1) {
    asm volatile("mma.sync.aligned.m16n8k16.row.col.f32.f16.f16.f32 {%0,%1,%2,%3},{%4,%5,%6,%7},{%8,%9},{%10,%11,%12,%13};"
                 : "=f"(d[0]), "=f"(d[1]), "=f"(d[2]), "=f"(d[3]) : "r"(a0), "r"(a1), "r"(a2), "r"(a3), "r"(b0), "r"(b1), "f"(c[0]), "f"(c[1]), "f"(c[2]), "f"(c[3]));
}
template <int Q0, int Q1>
__device__ __forceinline__ void sweep_steps(float (&w)[5][4], const uint32_t (&R)[66], uint32_t xa, uint32_t (&x)[5], uint32_t z) {
#pragma unroll
    for (int q = Q0; q <= Q1; q++) {
        uint32_t n0, n1;
        ldm2(xa + 16 * (q + 1), n0, n1);
        const uint32_t a2 = x[0] | z, a3 = x[1] | z;
#pragma unroll
        for (int j = 0; j < 4; j++) {
            const int s = 8 * j + 8 - q;
            if (q == 1) mma_hc(w[j], w[j + 1], x[1], x[2], a2, a3, R[2 * s], R[2 * s + 1]);
            else mma_h(w[j], x[1], x[2], a2, a3, R[2 * s], R[2 * s + 1]);
        }
        if (q == 8) {
            const float zero[4] = {0.f, 0.f, 0.f, 0.f};
            mma_hc(w[4], zero, x[1], x[2], a2, a3, R[64], R[65]);
        }
        x[0] = x[2]; x[1] = x[3]; x[2] = x[4]; x[3] = n0; x[4] = n1;
    }
}

__device__ __forceinline__ void box_round(uint32_t xb, uint32_t fa, int rho, int lane) {
    if (rho == 6) {
        const int a = lane >> 3, j = lane & 7;
        sts128(fa + 3328 * (lane >> 4) + 16 * ((lane & 15) < 15 ? (lane & 15) : 207), 0u, 0u, 0u, 0u);
        sts128(fa + FB9E + 1168 * a + 16 * (j < 7 ? j : 71 + (a & 1)), 0u, 0u, 0u, 0u);
        __syncwarp();
    }
    const int c = rho < 6 ? 32 * rho + lane : -1;
    const uint4 pv = lds128(x0_chunk(xb, c - 1)), ow = lds128(x0_chunk(xb, c));
    const uint2 nx = lds64(x0_chunk(xb, c + 1));
    const uint32_t P[9] = {pv.y, pv.z, pv.w, ow.x, ow.y, ow.z, ow.w, nx.x, nx.y};
    uint32_t Q[8], b3[6], b5[4];
#pragma unroll
    for (int k = 0; k < 8; k++) Q[k] = prmt(P[k], P[k + 1], 0x5432);
#pragma unroll
    for (int k = 0; k < 6; k++) b3[k] = hadd(hadd(Q[k], Q[k + 1]), P[k + 1]);
#pragma unroll
    for (int k = 0; k < 4; k++) b5[k] = hadd(b3[k + 2], hadd(P[k + 2], P[k + 4]));
    sts128(fa + FB5 + 240 + 16 * c, b5[0], b5[1], b5[2], b5[3]);
    sts128(fa + FB3 + 240 + 16 * c, b3[0], b3[1], b3[2], b3[3]);
    if (rho < 4 || rho == 6) {
        uint32_t b7[4], b9[4];
#pragma unroll
        for (int k = 0; k < 4; k++) {
            b7[k] = hadd(b5[k], hadd(Q[k + 1], Q[k + 4]));
            b9[k] = hadd(b7[k], hadd(P[k + 1], P[k + 5]));
        }
        const uint32_t ad = fa + ((c & 1) ? FB9O + 120 : FB9E + 112) + 8 * c;
        sts128(ad, b9[0], b9[1], b9[2], b9[3]);
        sts128(ad + (FB7E - FB9E), b7[0], b7[1], b7[2], b7[3]);
    }
}

__global__ void __cluster_dims__(2, 1, 1) __launch_bounds__(NTHREADS, 1) fused_kernel(const Hot p, const __grid_constant__ Maps m) {
    extern __shared__ __align__(1024) char smem[];
    const uint32_t t0 = clk32();
    const int tid = (threadIdx.x + 32 * 0) & (NTHREADS - 1), lane = tid & 31, warp = __shfl_sync(~0u, tid >> 5, 0), bid = blockIdx.x;
    const uint32_t S = smem_u32(smem), z = (uint32_t)p.tn.zero;
    const bool down = bid < NDOWN, rowcta = bid < NMAIN, big = rowcta && !down;
    const int xd = rowcta ? bid : 142 + ((bid - NMAIN) >> 1);
    const int slot = warp < 8 ? (warp & 3) : 4;
    const bool has = warp < 8 ? (rowcta || (slot >> 1) == (bid & 1)) : (big && warp < 12);
    const int ch = slot < 4 ? 4 * xd + slot : 512 + bid - NDOWN;
    KParams kp;
    if (has) kp = kgen_load(p, ch, warp < 8 ? warp >> 2 : (warp >> 1) & 1, lane);
    if (elect()) {
#pragma unroll 1
        for (int i = warp; i < B_COUNT; i += 16) {
            const uint32_t c = i < 16 ? (uint32_t)((big ? 0x1411115555412290ull : 0x1411114444412290ull) >> (4 * i)) & 15 : 1;
            mbar_init(S + i * 8, c ? c : NTHREADS);
        }
        asm volatile("fence.mbarrier_init.release.cluster;" ::: "memory");
    }
    if (rowcta) {
#pragma unroll 1
        for (int i = tid; i < 1224; i += NTHREADS)
            cp16(S + SM_ROWS + 16 * (i + min((i * 911) >> 16, 16)), i < 1152 ? (const uint4*)p.u + bid * 1152 + i : (const uint4*)p.wr + (i - 1152));
    }
    if (tid >= 256 && tid < 336) {
        const int i = tid - 256;
        if (i < 64 || big) sts128(S + (i < 64 ? SM_X0 + (i >> 4) * X0_STRIDE : SM_EX) + ((i & 8) ? X0_ODD : 0) + 16 * (i & 7), 0u, 0u, 0u, 0u);
    }
    if (tid == 447) sts128(S + SM_ONES, 0x3F803F80u, 0x3F803F80u, 0x3F803F80u, 0x3F803F80u);
    __syncthreads();
    if (rowcta) asm volatile("cp.async.mbarrier.arrive.noinc.shared::cta.b64 [%0];" ::"r"(S + B_ROWS * 8) : "memory");
    if (warp == 15 && lane < 4) mbar_expect(S + (lane < 3 ? B_GX + lane : B_RED) * 8, 256);
    asm volatile("barrier.cluster.arrive.relaxed.aligned;" ::: "memory");
    const int g = lane >> 2, t = lane & 3, mi = lane >> 3, j = lane & 7;
    const uint32_t SW = S + (down ? SM_W_DOWN : SM_W_BIG);
    const int pr = bid >> 1, r = bid & 1, nsl = pr >= 54 ? 3 : 2, sl0 = pr < 54 ? 2 * pr : 3 * pr - 54;

    if (warp == 12) {
        if (elect()) {
            const int ng = 6 * nsl, ns = down ? 24 : ng;
            const CUtensorMap* mg = r ? &m.wu : &m.wg;
            pf_tmap(mg);
            if (down) pf_tmap(&m.wd);
            const uint32_t epoch = ld_rlx(&p.s->cnt[16 * 32]) + 1;
            spin_until(t0, p.tn.f_start);
            int done = 0;
#pragma unroll 1
            for (int s = 0; s < ns; s++) {
                if (s == ng) spin_until(t0, p.tn.f_t3);
                #pragma unroll 1
                for (int it = 0; it < SPIN_LIMIT; it++) {
                    const int w = s >= ng ? p.tn.w3 : ((int)(clk32() - t0) < p.tn.f_t2 ? p.tn.w1 : (nsl == 3 ? p.tn.w2b : p.tn.w2));
                    if (s - done < w) break;
                    if (mbar_test(S + (B_W + done) * 8, 0)) done++;
                    else __nanosleep(32);
                }
                const uint32_t bar = S + (B_W + s) * 8;
                uint32_t dst = SW + s * STAGE;
                if (s == 23) { mbar_wait(S + B_EM * 8, 0); fence_async(); dst = S + SM_W_LAST; }
                mbar_expect(bar, STAGE);
                const int u = (s * 43) >> 8;
                if (s < ng) tma2d(dst, mg, 32 * (sl0 + u), 96 * (s - 6 * u), bar);
                else tma2d(dst, &m.wd, 16 * pr, r * 2304 + 192 * (s - 12), bar);
            }
            if (rowcta) {
                mbar_wait(S + B_FD * 8, 0);
                fence_async();
#pragma unroll 1
                for (int q = 0; q < 4; q++) {
                    wait_count(&p.s->cnt[(8 + q) * 32], epoch * (uint32_t)D_);
                    fence_async_g();
                    mbar_expect(S + (B_YIN + q) * 8, 4608);
                    bulk_g2s(S + SM_STG + q * 4608, p.s->y + (32 * q + (bid >> 2)) * 4608 + (bid & 3) * 1152, 4608, S + (B_YIN + q) * 8);
                }
            }
        }
        return;
    }

    uint32_t epoch = 0;
    if (warp >= 8 || !rowcta) epoch = ld_rlx(&p.s->cnt[16 * 32] + (lane & z)) + 1;
    const uint32_t tag = epoch & 1;
    const int hw = warp < 12 ? warp - 8 : warp - 9;

    if (rowcta && warp >= 8 && warp < 15) {
        const uint32_t ad = S + SM_ROWS + (lane & 15) * ROW_STRIDE + 192 * hw + 16 * (lane >> 4);
        uint32_t wd = j ? S + SM_ROWS + 16 * ROW_STRIDE + 192 * hw + 16 * mi : S + SM_ONES;
        const uint32_t wstep = j ? 64 : 0, ones = 0x3F803F80u | z;
        float d1[4] = {0, 0, 0, 0}, d2[4] = {0, 0, 0, 0}, d3[4] = {0, 0, 0, 0}, d4[4] = {0, 0, 0, 0};
        mbar_wait(S + B_ROWS * 8, 0);
#pragma unroll
        for (int kk = 0; kk < 3; kk++) {
            uint32_t w[4];
            ldm4(wd, w[0], w[1], w[2], w[3]);
            wd += wstep;
#pragma unroll
            for (int e = 0; e < 2; e++) {
                uint32_t a0, a1, a2, a3;
                ldm4(ad + 64 * kk + 32 * e, a0, a1, a2, a3);
                mma_bf(d1, a0, a1, a2, a3, w[2 * e], w[2 * e + 1]);
                mma_bf(d2, a0, a1, a2, a3, a0, a2);
                mma_bf(d3, a0, a1, a2, a3, a1, a3);
                mma_bf(d4, ones, ones ^ z, ones + z, ones - z, w[2 * e], w[2 * e + 1]);
            }
        }
        float* part = (float*)(smem + SM_PART + hw * 256) + g * 4;
        if (t == 0) {
            *(float2*)part = make_float2(d1[0], d1[1]);
            *(float2*)(part + 32) = make_float2(d1[2], d1[3]);
            part[3] = d4[1];
            part[35] = d4[1];
        }
        if (t == (g >> 1)) {
            part[2] = (g & 1) ? d2[1] : d2[0];
            part[34] = (g & 1) ? d3[3] : d3[2];
        }
        bar_sync(1, 192);
        if (hw == 0 && lane < 16) {
            float4 s = *(const float4*)(smem + SM_PART + lane * 16);
#pragma unroll
            for (int w = 1; w < 6; w++) {
                const float4 v = *(const float4*)(smem + SM_PART + w * 256 + lane * 16);
                s.x += v.x; s.y += v.y; s.z += v.z; s.w += v.w;
            }
            const float mean = s.x * (1.f / 576.f);
            const float var = fmaxf(s.z * (1.f / 576.f) - mean * mean, 0.f);
            const uint32_t mm = pack_bf(mean, mean);
            const float mu = bf_lo(mm), sd = bf_round(sqrt_ap(bf_round(bf_round(var) + 1e-5f))), ri = rcpf(sd);
            const uint32_t hi = pack_bf(ri, ri);
            const float rl = ri - bf_lo(hi);
            sts16(S + SM_STA + 2 * lane, mm); sts16(S + SM_STA + 32 + 2 * lane, hi); sts16(S + SM_STA + 64 + 2 * lane, pack_bf(rl, rl));
            const uint32_t rb = pack_bf(0.f, (s.y - mu * s.w) * ri);
            const int row = bid * 16 + lane;
            p.s->stat[row] = (mm & 0xFFFFu) | __float_as_uint(sd) | (tag << 31);
            p.s->key[row] = ((rb ^ (((int)rb >> 31) | 0x80000000u)) & 0xFFFF0000u) | (tag << 15) | (2047 - row);
        }
        bar_sync(1, 192);
        if (tid == 256) mbar_arrive(S + B_P1 * 8);
        {
            const uint2 sm = lds64(S + SM_STA + 8 * t), sh = lds64(S + SM_STA + 32 + 8 * t), sl = lds64(S + SM_STA + 64 + 8 * t);
            const uint32_t at = S + SM_ROWS + (4 * (j >> 1) + (j & 1) + 2 * (mi & 1)) * ROW_STRIDE + 32 * hw + 16 * (mi >> 1);
            uint2* dst = (uint2*)p.s->x + (4 * hw + (g >> 2)) * 2048 + bid * 16 + (g & 3) * 4 + t;
            uint32_t r4[6][4];
#pragma unroll
            for (int n = 5; n >= 0; n--) ldm4t(at + 192 * n, r4[n][0], r4[n][1], r4[n][2], r4[n][3]);
#pragma unroll
            for (int n = 5; n >= 0; n--) {
                uint32_t o[4];
#pragma unroll
                for (int e = 0; e < 4; e++) {
                    const uint32_t v = (e & 1) ? norm2(r4[n][e], sm.y, sh.y, sl.y) : norm2(r4[n][e], sm.x, sh.x, sl.x);
                    o[e] = pack_h(bf_lo(v), bf_hi(v));
                }
                dst[n * 49152] = make_uint2((o[0] & ~1u) | tag, o[1]);
                dst[n * 49152 + 4096] = make_uint2((o[2] & ~1u) | tag, o[3]);
            }
        }
        bar_sync(1, 192);
    }

    if (has) {
        asm volatile("" : "+r"(kp.ldt), "+r"(kp.are), "+r"(kp.aim), "+r"(kp.bre), "+r"(kp.bim), "+r"(kp.cre), "+r"(kp.cim));

        const uint32_t scr = warp < 8 ? S + SM_STG + warp * KG_SCR : S + EX_HAND + hw * KG_SCR;
        kgen(kp, scr, warp < 8 ? scr : S + EX_FAR + hw * 2576, warp < 8 ? 0 : warp & 1, warp < 8 ? 2 : (warp & 1) + 1, rowcta ? S + B_P1 * 8 : 0);
        if (warp >= 8) { __syncwarp(); if (lane == 0) mbar_arrive(S + B_TAB * 8); }
    }
    if (warp < 8 || warp == 15) {
        if (warp < 8 ? has : big) {
            if (warp < 8) bar_sync(4 + slot, 64); else mbar_wait(S + B_TAB * 8, 0);
            ktables(warp < 8 ? S + SM_STG + slot * KG_SCR : S + EX_FAR, warp < 8 ? 4 * KG_SCR : 2576, warp < 8 ? 2 : 4, S + SM_XS + slot * KR_STRIDE,
                    S + (warp < 8 ? SM_KT + slot * KT_STRIDE : EX_KT), S + SM_KINF + slot * 16, warp < 8 ? 1 + (warp >> 2) : 3);
        }
        if (lane == 0) { mbar_arrive(S + B_KG * 8); if (warp == 15) mbar_arrive(S + B_TAB1 * 8); }
    }

    if (!rowcta && warp < 8 && !has) {
        const int w4 = (warp >> 2) * 2 + (warp & 1), i = 32 * w4 + lane;
#pragma unroll 1
        for (int pass = 1; pass < 2; pass++) {
        uint4 k[4];
        if (pass) spin_until(t0, p.tn.t_svc - 1500);
#pragma unroll 1
        for (int it = 0; it < SPIN_LIMIT; it++) {
            if (!pass) {
#pragma unroll
                for (int q = 0; q < 4; q++) k[q] = make_uint4(16 * i + 4 * q, 16 * i + 4 * q + 1, 16 * i + 4 * q + 2, 16 * i + 4 * q + 3);
                break;
            }
            uint32_t bad = 0;
#pragma unroll
            for (int q = 0; q < 4; q++) k[q] = ld_rlx4(&p.s->key[4 * i + 512 * q]);
#pragma unroll
            for (int q = 0; q < 4; q++) bad |= tag ? ~(k[q].x & k[q].y & k[q].z & k[q].w) : (k[q].x | k[q].y | k[q].z | k[q].w);
            if (!(bad & 0x8000u)) break;
            __nanosleep(100);
        }
        const uint32_t sc = S + SM_XS + ((bid & 1) ? 0 : 2) * KR_STRIDE;
        auto pk = [](uint32_t v) { return ((v >> 16) << 11) | (v & 2047u); };
        auto gt = [](uint32_t a, uint32_t b) { return (b - a) >> 31; };
        uint32_t mx = 0;
#pragma unroll
        for (int q = 0; q < 4; q++) {
            k[q] = make_uint4(pk(k[q].x), pk(k[q].y), pk(k[q].z), pk(k[q].w));
            mx = max(max(mx, max(k[q].x, k[q].y)), max(k[q].z, k[q].w));
        }
        bar_sync(1, 128);
        sts32(sc + 4 * i, mx);
        if (i == 0) sts32(sc + 1024, 0u);
        bar_sync(1, 128);
        int rank;
        {
            int c[8] = {0, 0, 0, 0, 0, 0, 0, 0};
#pragma unroll 1
            for (int q = 0; q < 32; q += 4) {
                uint4 v[4];
#pragma unroll
                for (int e = 0; e < 4; e++) v[e] = lds128(sc + 16 * (q + e));
#pragma unroll
                for (int e = 0; e < 4; e++) {
                    c[(2 * e) & 7] += gt(v[e].x, mx); c[(2 * e + 1) & 7] += gt(v[e].y, mx);
                    c[(2 * e + 4) & 7] += gt(v[e].z, mx); c[(2 * e + 5) & 7] += gt(v[e].w, mx);
                }
            }
            rank = ((c[0] + c[1]) + (c[2] + c[3])) + ((c[4] + c[5]) + (c[6] + c[7]));
        }
        if (rank == 7) sts32(sc + 1028, mx);
        bar_sync(1, 128);
        if (rank < 8) {
            const uint32_t lb = lds32(sc + 1028);
            int cq[4];
#pragma unroll
            for (int q = 0; q < 4; q++) cq[q] = (gt(lb, k[q].x) + gt(lb, k[q].y)) + (gt(lb, k[q].z) + gt(lb, k[q].w));
            const int c = 16 - ((cq[0] + cq[1]) + (cq[2] + cq[3]));
            uint32_t pos;
            asm volatile("atom.shared.add.u32 %0, [%1], %2;" : "=r"(pos) : "r"(sc + 1024), "r"(c) : "memory");
            pos = sc + 512 + 4 * pos;
#pragma unroll
            for (int q = 0; q < 4; q++) {
                if (k[q].x >= lb) { sts32(pos, k[q].x); pos += 4; }
                if (k[q].y >= lb) { sts32(pos, k[q].y); pos += 4; }
                if (k[q].z >= lb) { sts32(pos, k[q].z); pos += 4; }
                if (k[q].w >= lb) { sts32(pos, k[q].w); pos += 4; }
            }
        }
        bar_sync(1, 128);
        const int n = lds32(sc + 1024);
        if (i < n) {
            const uint32_t mine = lds32(sc + 512 + 4 * i);
            rank = 0;
#pragma unroll 1
            for (int q = 0; q < n; q += 4) {
                const uint4 v = lds128(sc + 512 + 4 * q);
                rank += ((v.x > mine) + (q + 1 < n && v.y > mine)) + ((q + 2 < n && v.z > mine) + (q + 3 < n && v.w > mine));
            }
            const uint32_t k32 = (mine >> 11) << 16, rb = (k32 ^ ((~(int)k32 >> 31) | 0x80000000u)) & 0xFFFF0000u;
            if (rank < 8 && pass) st_rlx(&p.s->sel[bid - NMAIN][rank], (2047 - (mine & 2047)) | (tag << 15) | (pack_bf(rcpf(1.f + ex2f(-1.4426950408889634f * __uint_as_float(rb))), 0.f) << 16));
        }
        }
    }

    if (warp == 13 || warp == 14) {
        const int i = tid - 416;
        if (i == 0) sts32(S + SM_EPOCH, tag);
        if (rowcta) {
            if (p.tn.t_marg <= 600) {
                const uint32_t back = ld_rlx(p.s->x + 2 * ((4 * hw + 2 + (g >> 2)) * 2048 + bid * 16 + (g & 3) * 4 + t));
                if (back == 0xFFFFFFFFu) __nanosleep(20);
            }
            spin_until(clk32(), p.tn.t_marg);
        } else {
            spin_until(t0, p.tn.t_svc);
        }
        const uint4* xa = (const uint4*)p.s->x + xd * 1024 + i;
        const int e = bid - NDOWN;
        const uint4* xe = (const uint4*)p.s->x + (128 + (e >> 2)) * 1024 + (i >> 1) * 8 + (e & 3) * 2 + (i & 1);
        const uint32_t da = S + SM_X0 + ((i >> 1) & 3) * X0_STRIDE + ((i & 1) ? X0_ODD : 0) + 128 + 16 * (i >> 3);
        const uint32_t de = S + SM_EX + ((i & 1) ? X0_ODD : 0) + 128 + 16 * (i >> 1);
        uint4 v[2][10];
        auto fetch = [&](int half) {
#pragma unroll
            for (int k = 0; k < 10; k++) {
                v[half][k].x = v[half][k].z = tag;
                if (k < 8 || big) v[half][k] = ld_rlx4(k < 8 ? xa + 512 * half + 64 * k : xe + 512 * half + 256 * (k - 8));
            }
        };
        fetch(0); fetch(1);
#pragma unroll
        for (int half = 0; half < 2; half++) {
#pragma unroll 1
            for (int it = 0; it < SPIN_LIMIT; it++) {
                uint32_t bad = 0;
#pragma unroll
                for (int k = 0; k < 10; k++) bad |= (v[half][k].x ^ tag) | (v[half][k].z ^ tag);
                if (!(bad & 1)) break;
                __nanosleep(60);
                fetch(half);
            }
#pragma unroll
            for (int k = 0; k < 10; k++)
                if (k < 8 || big) sts128(k < 8 ? da + 1024 * half + 128 * k : de + 1024 * half + 512 * (k - 8), v[half][k].x & ~1u, v[half][k].y, v[half][k].z & ~1u, v[half][k].w);
            __syncwarp();
            if (lane == 0) mbar_arrive(S + (B_X0 + half) * 8);
        }
    }

    if (warp < 12) {
        const bool cw = warp >= 8;
        if (has) {
            const uint32_t xb = S + (cw ? SM_EX : SM_X0 + slot * X0_STRIDE), kt = S + (cw ? EX_KT : SM_KT + slot * KT_STRIDE);
            const int g0 = cw ? warp - 8 : 0, g1 = cw ? warp - 7 : 4;
            const uint32_t park = (cw ? S + EX_HAND + g0 * 2048 : kt) + lane * 16;
            if (cw) mbar_wait(S + B_TAB1 * 8, 0);
            const uint4 ki = lds128(S + SM_KINF + slot * 16);
            const float inv = __uint_as_float(ki.x);
            if (warp >= 4) {
                const uint32_t fa = S + (cw ? EX_FAR : SM_FAR + slot * FAR_STRIDE);
                mbar_wait(S + (cw ? B_X1 : B_X0) * 8, 0);
                mbar_wait(S + B_KG * 8, 0);
#pragma unroll 1
                for (int rho = cw ? g0 : 0; rho < (cw ? 7 : 4); rho += cw ? 4 : 1) box_round(xb, fa, (!cw && rho == 3) ? 6 : rho, lane);
                if (cw) bar_sync(2, 128); else __syncwarp();
                const int dd = g - 2 * t, gf = g0 ? g0 : 1;
                const uint32_t tb0 = dd == -5 ? ki.z : (dd == -4 ? ki.z << 16 : 0u), tb1 = dd == 3 ? ki.z : (dd == 4 ? ki.z << 16 : 0u);
                uint32_t tad = xb + (mi == 1 ? 144 : mi == 2 ? 128 : X0_ODD + 128) + 16 * j + 512 * gf - 1024;
                uint32_t ad8 = fa + (mi == 0 ? FB9E : mi == 1 ? FB7O : mi == 2 ? FB9O + 16 : FB7E) + 112 - 16 * j + 512 * gf - 768;
                uint32_t ad4 = fa + ((mi & 1) ? FB3 : FB5) + 240 + 16 * (8 * (mi >> 1) - j) + 1024 * gf - 640;
                const uint32_t p4 = kt + KT_P4 + 16 * (g + t), p8 = kt + KT_P8 + 8 * (g + 2 * t);
#pragma unroll 1
                for (int grp = gf; grp < g1; grp++) {
                    float a[4][4], e[2][4], o[2][4];
#pragma unroll
                    for (int k = 0; k < 4; k++) a[0][k] = a[1][k] = a[2][k] = a[3][k] = e[0][k] = e[1][k] = o[0][k] = o[1][k] = 0.f;
                    {
                        if (!cw && grp == 2) {
                            mbar_wait(S + B_X1 * 8, 0);
#pragma unroll 1
                            for (int rho = 3; rho < 6; rho++) box_round(xb, fa, rho, lane);
                            __syncwarp();
                        }
                        {
                            uint4 A4[10];
#pragma unroll
                            for (int s = 0; s < 10; s++) A4[s] = lds128(p4 + 64 * s);
                            auto s4 = [&](int m) {
                                uint32_t b[4];
                                ldm4t(ad4 - 256 * m, b[0], b[1], b[2], b[3]);
#pragma unroll
                                for (int h = 1; h >= 0; h--)
#pragma unroll
                                    for (int i = 0; i < 4; i++) {
                                        const int s = 2 * m - 2 + 2 * i + (1 - h), k = m + (i & 2);
                                        if (k <= 5 && k >= ((i & 1) ? 0 : 1) && !((i & 1) && k == 5)) mma_h(a[i], A4[s >= 0 && s < 10 ? s : 0].x, A4[s >= 0 && s < 10 ? s : 0].y, A4[s >= 0 && s < 10 ? s : 0].z, A4[s >= 0 && s < 10 ? s : 0].w, b[2 * h], b[2 * h + 1]);
                                    }
                            };
                            auto tap = [&](int i) {
                                uint32_t b[4];
                                ldm4(tad + 128 * i, b[0], b[1], b[2], b[3]);
                                mma_h(a[i], b[0], b[1], b[2], b[3], tb1, tb0);
                            };
                            s4(1); s4(0); s4(2); s4(-1); tap(3); s4(-2);
                            if (grp >= 2) { s4(3); tap(0); s4(4); tap(1); s4(5); tap(2); }
                        }
                        {
                            uint32_t A8[9][4];
#pragma unroll
                            for (int k = 0; k < 9; k++) { A8[k][0] = lds32(p8 + 64 * k); A8[k][1] = lds32(p8 + 64 * k + 64); A8[k][2] = lds32(p8 + 64 * k + 4); A8[k][3] = lds32(p8 + 64 * k + 68); }
                            auto s8 = [&](int m) {
                                uint32_t b[4];
                                ldm4t(ad8 - 128 * m, b[0], b[1], b[2], b[3]);
                                mma_h(e[1], A8[m + 2][0], A8[m + 2][1], A8[m + 2][2], A8[m + 2][3], b[0], b[1]);
                                mma_h(o[1], A8[m + 2][0], A8[m + 2][1], A8[m + 2][2], A8[m + 2][3], b[2], b[3]);
                                if (m >= 0) {
                                    mma_h(e[0], A8[m >= 0 ? m : 0][0], A8[m >= 0 ? m : 0][1], A8[m >= 0 ? m : 0][2], A8[m >= 0 ? m : 0][3], b[0], b[1]);
                                    mma_h(o[0], A8[m >= 0 ? m : 0][0], A8[m >= 0 ? m : 0][1], A8[m >= 0 ? m : 0][2], A8[m >= 0 ? m : 0][3], b[2], b[3]);
                                }
                            };
                            s8(-2);
                            if (grp >= 2) {
                                s8(-1); s8(0); s8(1); s8(2);
                                if (grp >= 3) { s8(3); s8(4); s8(5); s8(6); }
                            }
                        }
                    }
                    tad += 512; ad8 += 512; ad4 += 1024;
#pragma unroll
                    for (int pp = 0; pp < 2; pp++) {
                        if (!cw) {
#pragma unroll 1
                            for (int it = 0; it < SPIN_LIMIT && !__all_sync(~0u, lds32v(park + (2 * pp + 1) * 512) == SLOT_FREE); it++) __nanosleep(32);
                        }
#pragma unroll
                        for (int i = 0; i < 2; i++)
                            sts128(park + (2 * pp + i) * 512, __float_as_uint((a[2 * pp + i][0] + e[pp][2 * i]) * inv), __float_as_uint((a[2 * pp + i][1] + e[pp][2 * i + 1]) * inv),
                                   __float_as_uint((a[2 * pp + i][2] + o[pp][2 * i]) * inv), __float_as_uint((a[2 * pp + i][3] + o[pp][2 * i + 1]) * inv));
                    }
                }
            }
            if ((warp & 12) != 4) {
                uint32_t R[66], x[5];
#pragma unroll
                for (int i = 0; i < 66; i++) R[i] = lds32(kt + 4 * (8 + g - 2 * t) + 32 * i);
                float w[5][4];
#pragma unroll
                for (int i = 0; i < 5; i++) w[i][0] = w[i][1] = w[i][2] = w[i][3] = 0.f;
                uint32_t xa = xb + ((lane & 8) ? X0_ODD + 16 : 16) + 16 * j + 512 * g0;
                uint2* yo = (uint2*)p.s->y + (32 * g0 + g) * 2304 + ch * 4 + t;
                mbar_wait(S + B_X0 * 8, 0);
                const uint32_t ytag = lds32(S + SM_EPOCH);
                if (g0 == 0) {
                    const uint32_t x01 = lds32(xb + 128);
                    const float c0 = lane == 31 ? __uint_as_float(ki.y) * inv * h_lo(x01) : 0.f, c1 = lane == 31 ? c0 + __uint_as_float(ki.y) * inv * h_hi(x01) : 0.f;
                    __syncwarp();
#pragma unroll
                    for (int i = 0; i < 4; i++) sts128(park + i * 512, 0u, 0u, i == 3 ? __float_as_uint(c0) : 0u, i == 3 ? __float_as_uint(c1) : 0u);
                }
                ldm2(xa - 16, x[1], x[0]);
                ldm2(xa, x[1], x[2]);
                ldm2(xa + 16, x[3], x[4]);
                uint32_t zz = z, pk = park;
                float sc = inv;
                const bool direct = g0 == 0;
                uint32_t dir = direct;
                asm volatile("" : "+r"(pk));
#pragma unroll 1
                for (int gq = g0; gq < g1; gq++) {
                    uint32_t pa = pk;
#pragma unroll 1
                    for (int n = 4; n > 0; n--) {
                        asm volatile("" : "+r"(zz), "+f"(sc), "+r"(pa), "+r"(dir));
                        sweep_steps<1, 5>(w, R, xa, x, zz);
                        uint4 v = lds128v(pa | (x[4] & zz));
                        sweep_steps<6, 8>(w, R, xa, x, zz);
                        xa += 128;
                        if (__any_sync(~0u, v.x == SLOT_FREE)) {
#pragma unroll 1
                            for (int it = 0; it < SPIN_LIMIT; it++) {
                                v = lds128v(pa);
                                if (!__any_sync(~0u, v.x == SLOT_FREE)) break;
                            }
                        }
                        const float y0 = fmaf(w[0][0], sc, __uint_as_float(v.x)), y1 = fmaf(w[0][1], sc, __uint_as_float(v.y));
                        const float y2 = fmaf(w[0][2], sc, __uint_as_float(v.z)), y3 = fmaf(w[0][3], sc, __uint_as_float(v.w));
                        if (dir) {
                            *yo = make_uint2((pack_bf(y0, y1) & ~1u) | ytag, pack_bf(y2, y3));
                            sts32(pa, SLOT_FREE);
                        } else {
                            sts128(pa, __float_as_uint(y0), __float_as_uint(y1), __float_as_uint(y2), __float_as_uint(y3));
                        }
                        yo += 18432;
                        pa += 512;
                    }
                    if (direct && lane == 0) red_add(&p.s->cnt[(8 + gq) * 32]);
                }
                __syncwarp();
                if (lane == 0) mbar_arrive(S + (direct ? B_EM : B_SP + g0) * 8);
                if (cw && g0 < 3) {
                    mbar_wait(S + (B_SP + g0 + 1) * 8, 0);
#pragma unroll
                    for (int i = 0; i < 4; i++) {
                        const uint4 v = lds128(park + 2048 + i * 512);
                        yo[i * 18432] = make_uint2((pack_bf(fmaf(w[i + 1][0], inv, __uint_as_float(v.x)), fmaf(w[i + 1][1], inv, __uint_as_float(v.y))) & ~1u) | ytag,
                                                   pack_bf(fmaf(w[i + 1][2], inv, __uint_as_float(v.z)), fmaf(w[i + 1][3], inv, __uint_as_float(v.w))));
                    }
                    if (lane == 0) red_add(&p.s->cnt[(8 + g0 + 1) * 32]);
                }
            }
        }
        if (rowcta && (warp & 12) == 4) {
            bar_sync(10, 128);
            const int i = tid - 128, rb0 = 16 * (bid >> 2), c0 = 144 * (bid & 3);
            if (i == 0) mbar_arrive(S + B_FD * 8);
#pragma unroll 3
            for (int v = i; v < 1152; v += 128) {
                const int row = (v * 3641) >> 16, vv = v - 18 * row;
                cp16(S + SM_ROWS + row * 304 + 16 * vv, (const uint4*)(p.u + (size_t)(512 * (row >> 4) + rb0 + (row & 15)) * D_ + c0) + vv);
            }
            if (i < 64) {
                const uint32_t sw = ld_stat(&p.s->stat[512 * (i >> 4) + rb0 + (i & 15)], lds32(S + SM_EPOCH));
                const float ri = rcpf(bf_hi(sw));
                const uint32_t hi = pack_bf(ri, ri);
                const float rl = ri - bf_lo(hi);
                sts128(S + SM_KT + KT_P4 + 16 * i, prmt(sw, sw, 0x1010), hi, pack_bf(rl, rl), 0u);
            }
            asm volatile("cp.async.wait_all;" ::: "memory");
            __syncwarp();
            if (lane == 0) mbar_arrive(S + B_OUT * 8);
        }
        if (!rowcta) return;

        const int rb0 = 16 * (bid >> 2), c0 = 144 * (bid & 3);
        mbar_wait(S + B_OUT * 8, 0);
        mbar_wait(S + B_XS * 8, 0);
        const uint32_t otag = lds32(S + SM_EPOCH) * 0x00010001u;
        const uint2 skip = lds64(S + SM_SKIP);
        const int pi_g = (g & 1) + 8 * ((g >> 1) & 1) + 2 * (g >> 2), pi_j = (j & 1) + 8 * ((j >> 1) & 1) + 2 * (j >> 2);
#pragma unroll 1
        for (int un = warp; un < 36; un += 12) {
            const int q = (un * 57) >> 9, cu = un - 9 * q;
            const uint32_t rw = S + SM_ROWS + 16 * q * 304 + 32 * cu;
            const uint32_t ad = rw + (pi_j + 4 * (mi & 1)) * 304 + 16 * (mi >> 1);
            const uint32_t dk0 = __ldg((const uint32_t*)p.dskip + (c0 >> 1) + 8 * cu + t), dk1 = __ldg((const uint32_t*)p.dskip + (c0 >> 1) + 8 * cu + 4 + t);
            const uint4 sa = lds128(S + SM_KT + KT_P4 + 16 * (16 * q + pi_g)), sb = lds128(S + SM_KT + KT_P4 + 16 * (16 * q + 4 + pi_g));
            uint32_t x[4], tt[4], gt[4], y[4];
            ldm4(ad, x[0], x[1], x[2], x[3]);
#pragma unroll
            for (int e = 0; e < 4; e++) {
                const uint4 s = (e & 1) ? sb : sa;
                const uint32_t xn = norm2(x[e], s.x, s.y, s.z);
                tt[e] = bmul(xn, e < 2 ? dk0 : dk1);
                gt[e] = pack_bf(silu_f(bf_lo(xn)), silu_f(bf_hi(xn)));
            }
            mbar_wait(S + (B_YIN + q) * 8, 0);
            const uint32_t yb = S + SM_STG + q * 4608 + 512 * cu;
#pragma unroll 1
            for (int it = 0; it < SPIN_LIMIT; it++) {
                ldm4t(yb + (8 * (mi >> 1) + j) * 32 + 16 * (mi & 1), y[0], y[1], y[2], y[3]);
                const uint32_t bad = ((y[0] ^ otag) | (y[1] ^ otag) | (y[2] ^ otag) | (y[3] ^ otag)) & 0x00010001u;
                if (!__any_sync(~0u, (g & 3) == 0 && bad)) break;
                const uint4 v = ld_rlx4((const uint4*)(p.s->y + (32 * q + (bid >> 2)) * 4608 + (bid & 3) * 1152 + 128 * cu) + lane);
                __syncwarp();
                sts128(yb + 16 * lane, v.x, v.y, v.z, v.w);
                __syncwarp();
            }
#pragma unroll
            for (int e = 0; e < 4; e++) y[e] = badd(x[e], bmul(badd(y[e], tt[e]), gt[e]));
            stm4(ad, y[0], y[1], y[2], y[3]);
            __syncwarp();
            const int row = lane >> 1;
            const uint4 o = lds128(rw + row * 304 + 16 * (lane & 1));
            if (!((((q & 2) ? skip.y : skip.x) >> (16 * (q & 1) + row)) & 1))
                *((uint4*)(p.out + (size_t)(512 * q + rb0 + row) * D_ + c0 + 16 * cu) + (lane & 1)) = o;
        }
        return;
    }

    {
        const int fw = warp - 13;
        if (fw < nsl) {
            st_rlx(&p.s->h[tag ^ 1][(32 * (sl0 + fw) + 16 * r) * 4 + lane], 0u);
            st_rlx(&p.s->h[tag ^ 1][(32 * (sl0 + fw) + 16 * r) * 4 + 32 + lane], 0u);
        }
        if (fw == 2) {
            spin_until(t0, p.tn.t_xs);
            uint32_t sv = 0;
#pragma unroll 1
            for (int it = 0; it < SPIN_LIMIT; it++) {
                sv = ld_rlx(&p.s->sel[bid & 3][j]);
                if (__all_sync(~0u, ((sv >> 15) & 1) == tag)) break;
                __nanosleep(40);
            }
            mbar_wait(S + B_KG * 8, 0);
            if (lane == 0) { fence_async(); mbar_expect(S + B_BOX * 8, 8 * 1152); }
            __syncwarp();
            if (lane < 8) bulk_g2s(S + SM_XS + lane * ROW_STRIDE, p.u + (size_t)(sv & 2047) * D_, 1152, S + B_BOX * 8);
            const uint32_t st = ld_stat(&p.s->stat[sv & 2047], tag);
            const float ri = rcpf(bf_hi(st));
            const uint32_t hi = pack_bf(ri, ri);
            const float rl = ri - bf_lo(hi);
            if (lane == 0) sts64(S + SM_SKIP, 0u, 0u);
            __syncwarp();
            if (lane < 8) {
                const int row = sv & 2047;
                if (((row >> 4) & 31) == (bid >> 2)) asm volatile("red.shared.or.b32 [%0], %1;" ::"r"(S + SM_SKIP + 4 * (row >> 10)), "r"(1u << (16 * ((row >> 9) & 1) + (row & 15))) : "memory");
                sts32(S + SM_XS + 8 * ROW_STRIDE + 4 * lane, sv);
                sts128(S + SM_RP + 16 * lane, prmt(st, st, 0x1010), hi, pack_bf(rl, rl), 0u);
            }
        }
        asm volatile("barrier.cluster.wait.aligned;" ::: "memory");
        bar_sync(9, 96);
        mbar_wait(S + B_BOX * 8, 0);
#pragma unroll
        for (int k = 0; k < 6; k++) {
            const int v = tid - 416 + 96 * k, tk = (v * 911) >> 16;
            const uint4 x = lds128(S + SM_XS + 16 * (v + tk)), st = lds128(S + SM_RP + 16 * tk);
            sts128(S + SM_XS + 16 * (v + tk), norm2(x.x, st.x, st.y, st.z), norm2(x.y, st.x, st.y, st.z), norm2(x.z, st.x, st.y, st.z), norm2(x.w, st.x, st.y, st.z));
        }
        bar_sync(9, 96);
        if (tid == 416) mbar_arrive(S + B_XS * 8);
        const uint32_t ob = mapa(S, r ^ 1);
        if (fw == 2) {
            if (elect()) {
#pragma unroll 1
                for (int st = 0; st < (down ? 24 : 6 * nsl); st++) {
                    if (st == 12 && down) break;
                    mbar_wait(S + (B_W + st) * 8, 0);
                    if (st % 3 == 2) mbar_arrive(S + (B_GU + st / 3) * 8);
                }
            }
            __syncwarp();
        }
        if (fw < 2) {
            const uint32_t bad = S + SM_XS + j * ROW_STRIDE + mi * 16;
            uint32_t aad = (SW + (8 * (mi >> 1) + j) * 64 + 16 * ((mi & 1) ^ (j >> 1))) ^ ((r ^ fw) * 32);
            uint32_t b[18][4];
#pragma unroll
            for (int k = 0; k < 18; k++) ldm4(bad + 64 * k, b[k][0], b[k][1], b[k][2], b[k][3]);
#pragma unroll 1
            for (int u = 0; u < nsl; u++) {
                float d[4][4];
#pragma unroll
                for (int i = 0; i < 4; i++) d[i][0] = d[i][1] = d[i][2] = d[i][3] = 0.f;
#pragma unroll
                for (int hf = 0; hf < 2; hf++) {
                    mbar_wait(S + (B_GU + 2 * u + hf) * 8, 0);
#pragma unroll
                    for (int sub = 0; sub < 3; sub++) {
                        uint32_t a[6][4];
#pragma unroll
                        for (int k = 0; k < 6; k++) ldm4t(aad + 1024 * k, a[k][0], a[k][1], a[k][2], a[k][3]);
#pragma unroll
                        for (int k = 0; k < 6; k++) {
                            const int kb = 9 * hf + 3 * sub + (k >> 1);
                            mma_bf(d[k & 3], a[k][0], a[k][1], a[k][2], a[k][3], b[kb][2 * (k & 1)], b[kb][2 * (k & 1) + 1]);
                        }
                        aad += STAGE;
                    }
                }
                const uint32_t k0 = pack_bf((d[0][0] + d[1][0]) + (d[2][0] + d[3][0]), (d[0][1] + d[1][1]) + (d[2][1] + d[3][1]));
                const uint32_t k1 = pack_bf((d[0][2] + d[1][2]) + (d[2][2] + d[3][2]), (d[0][3] + d[1][3]) + (d[2][3] + d[3][3]));
                if (fw == 1) {
                    asm volatile("st.async.shared::cluster.mbarrier::complete_tx::bytes.v2.b32 [%0], {%1, %2}, [%3];" ::"r"(ob + SM_PART + u * 256 + lane * 8), "r"(k0), "r"(k1), "r"(ob + (B_GX + u) * 8) : "memory");
                } else {
                    mbar_wait(S + (B_GX + u) * 8, 0);
                    const uint2 o = lds64(S + SM_PART + u * 256 + lane * 8);
#pragma unroll
                    for (int i = 0; i < 2; i++) {
                        const uint32_t mine = i ? k1 : k0, other = i ? o.y : o.x, gb = r ? other : mine, ub = r ? mine : other;
                        uint32_t hv = bmul(pack_bf(silu_f(bf_lo(gb)), silu_f(bf_hi(gb))), ub);
                        if ((hv & 0xFFFFu) == 0) hv |= 0x8000u;
                        if ((hv >> 16) == 0) hv |= 0x80000000u;
                        st_rlx(&p.s->h[tag][(32 * (sl0 + u) + 16 * r) * 4 + 32 * i + lane], hv);
                    }
                    __syncwarp();
                    if (lane < 8) red_add(&p.s->cnt[lane * 32]);
                }
            }
        }
        if (!down) return;

        const int fi = 32 * fw + lane, tok = 4 * r + ((fi >> 4) & 3), cc = 16 * pr + (fi & 15);
        const uint32_t sel = lds32(S + SM_XS + 8 * ROW_STRIDE + 4 * tok);
        const int row = sel & 2047;
        const uint32_t* ya = p.s->y + (row >> 4) * 4608 + cc * 8 + (row & 6);
        const float xraw = __bfloat162float(p.u[(size_t)row * D_ + cc]), dsk = __bfloat162float(p.dskip[cc]);
        const float xn = bf_lo(lds16(S + SM_XS + tok * ROW_STRIDE + 2 * cc));
        if (fw == 0) {
#pragma unroll 1
            for (int st = 12; st < 24; st++) mbar_wait(S + (B_W + st) * 8, 0);
        }
        if (fw == 2 && elect()) wait_count(&p.s->cnt[(bid & 7) * 32], epoch * 288u);
        bar_sync(9, 96);
        float dn[4][4];
        uint2 yv2 = make_uint2(tag ^ 1, 0u);
#pragma unroll 1
        for (int ph = 0; ph < 64; ph++) {
            if (fw == 2 && elect()) {
                fence_async();
                fence_async_g();
                mbar_expect(S + B_H * 8, 36864);
                bulk_g2s(SW, (const char*)p.s->h[tag] + r * 36864, 36864, S + B_H * 8);
            }
            asm volatile("ld.relaxed.gpu.global.v2.u32 {%0,%1}, [%2];" : "=r"(yv2.x), "=r"(yv2.y) : "l"(ya) : "memory");
            mbar_wait(S + B_H * 8, ph & 1);
#pragma unroll
            for (int i = 0; i < 4; i++) dn[i][0] = dn[i][1] = dn[i][2] = dn[i][3] = 0.f;
            uint32_t bq[4] = {~0u, ~0u, ~0u, ~0u};
            const int fr = j + 8 * (mi >> 1);
            uint32_t wa = SW + 12 * STAGE + fw * 2048 + fr * 32 + (((mi & 1) ^ ((fr >> 2) & 1)) << 4), ha = SW + fw * 1024 + lane * 16;
#pragma unroll 1
            for (int s0 = 0; s0 < 12; s0 += 3) {
                uint32_t a[6][8], b[6][4];
#pragma unroll
                for (int s = 0; s < 3; s++) {
                    if (s == 2 && s0 == 9) wa += S + SM_W_LAST - (SW + 23 * STAGE);
#pragma unroll
                    for (int e = 0; e < 2; e++) {
                        ldm4t(ha + e * 512, b[2 * s + e][0], b[2 * s + e][1], b[2 * s + e][2], b[2 * s + e][3]);
                        ldm4t(wa + e * 1024, a[2 * s + e][0], a[2 * s + e][1], a[2 * s + e][2], a[2 * s + e][3]);
                        ldm4t(wa + e * 1024 + 512, a[2 * s + e][4], a[2 * s + e][5], a[2 * s + e][6], a[2 * s + e][7]);
                    }
                    wa += STAGE; ha += 3072;
                }
#pragma unroll
                for (int k = 0; k < 6; k++) {
                    mma_bf(dn[2 * (k & 1)], a[k][0], a[k][1], a[k][2], a[k][3], b[k][0], b[k][1]);
                    mma_bf(dn[2 * (k & 1) + 1], a[k][4], a[k][5], a[k][6], a[k][7], b[k][2], b[k][3]);
#pragma unroll
                    for (int q = 0; q < 4; q++) bq[q] = __vminu2(bq[q], b[k][q]);
                }
            }
            const uint32_t bm = __vminu2(__vminu2(bq[0], bq[1]), __vminu2(bq[2], bq[3])), bd = (bm - 0x00010001u) & ~bm;
            uint32_t anybad;
            asm volatile("{.reg .pred p, q; setp.ne.u32 p, %1, 0; bar.red.or.pred q, 9, 96, p; selp.u32 %0, 1, 0, q;}" : "=r"(anybad) : "r"(bd & 0x80008000u) : "memory");
            if (!anybad) break;
        }
        float* red = (float*)(smem + SM_RED + fw * 512);
        red[(2 * t) * 16 + g] = (dn[0][0] + dn[1][0]) + (dn[2][0] + dn[3][0]);
        red[(2 * t + 1) * 16 + g] = (dn[0][1] + dn[1][1]) + (dn[2][1] + dn[3][1]);
        red[(2 * t) * 16 + g + 8] = (dn[0][2] + dn[1][2]) + (dn[2][2] + dn[3][2]);
        red[(2 * t + 1) * 16 + g + 8] = (dn[0][3] + dn[1][3]) + (dn[2][3] + dn[3][3]);
        bar_sync(9, 96);
        if (fw < 2) {
            const float* rs = (const float*)(smem + SM_RED);
            const int mine = 64 * r + fi, other = mine ^ 64;
            st_async32(ob + SM_RP + 4 * fi, __float_as_uint(rs[other] + rs[128 + other] + rs[256 + other]), ob + B_RED * 8);
            const float s = rs[mine] + rs[128 + mine] + rs[256 + mine];
#pragma unroll 1
            for (int it = 0; it < SPIN_LIMIT && (yv2.x & 1) != tag; it++)
                asm volatile("ld.relaxed.gpu.global.v2.u32 {%0,%1}, [%2];" : "=r"(yv2.x), "=r"(yv2.y) : "l"(ya) : "memory");
            const uint32_t yw = (row & 8) ? yv2.y : yv2.x;
            const float sg = bf_round(((row & 1) ? bf_hi(yw) : bf_lo(yw)) + bf_round(xn * dsk));
            mbar_wait(S + B_RED * 8, 0);
            const float o = *(const float*)(smem + SM_RP + 4 * fi);
            const float yv = bf_round(bf_round(r == 0 ? s + o : o + s) * bf_hi(sel));
            p.out[(size_t)row * D_ + cc] = __float2bfloat16(xraw + bf_round(sg * bf_round(silu_f(bf_round(xn + yv)))));
            if (bid == 0 && fi == 0) st_rlx(&p.s->cnt[16 * 32], epoch);
        }
    }
}

typedef CUresult (*EncodeFn)(CUtensorMap*, CUtensorMapDataType, cuuint32_t, void*, const cuuint64_t*, const cuuint64_t*, const cuuint32_t*,
                             const cuuint32_t*, CUtensorMapInterleave, CUtensorMapSwizzle, CUtensorMapL2promotion, CUtensorMapFloatOOBfill);

static void make2d(EncodeFn enc, CUtensorMap* m, const void* base, uint64_t cols, uint64_t rows, uint32_t bc, uint32_t br, CUtensorMapSwizzle sw) {
    cuuint64_t gd[2] = {cols, rows};
    cuuint64_t gs[1] = {cols * 2};
    cuuint32_t bd[2] = {bc, br}, es[2] = {1, 1};
    enc(m, CU_TENSOR_MAP_DATA_TYPE_BFLOAT16, 2, const_cast<void*>(base), gd, gs, bd, es, CU_TENSOR_MAP_INTERLEAVE_NONE, sw,
        CU_TENSOR_MAP_L2_PROMOTION_L2_128B, CU_TENSOR_MAP_FLOAT_OOB_FILL_NONE);
}

static Tune g_tune = {2000, 9000, 3, 5, 8, 5000, 7500, 0, 9000, 1, 0, 0};


static void launch(void* const* d_in, void* d_out) {
    static EncodeFn enc = nullptr;
    static Scratch* gs = nullptr;
    if (!enc) {
        void* fn = nullptr;
        cudaDriverEntryPointQueryResult qr;
        cudaGetDriverEntryPoint("cuTensorMapEncodeTiled", &fn, cudaEnableDefault, &qr);
        enc = (EncodeFn)fn;
        cudaFuncSetAttribute(fused_kernel, cudaFuncAttributeMaxDynamicSharedMemorySize, SM_TOTAL);
        cudaGetSymbolAddress((void**)&gs, g_s);
    }
    Hot p;
    Maps m;
    auto in = [&](int i) { return (const __nv_bfloat16*)d_in[i]; };
    p.u = in(0); p.are = in(1); p.aim = in(2); p.bre = in(3); p.bim = in(4); p.cre = in(5); p.cim = in(6);
    p.logdt = in(7); p.dskip = in(8); p.wr = in(10); p.pwg = in(11); p.pwu = in(12); p.pwd = in(13);
    p.out = (__nv_bfloat16*)d_out;
    p.tn = g_tune;
    p.s = gs;
    make2d(enc, &m.wg, p.pwg, F_, D_, 32, 96, CU_TENSOR_MAP_SWIZZLE_64B);
    make2d(enc, &m.wu, p.pwu, F_, D_, 32, 96, CU_TENSOR_MAP_SWIZZLE_64B);
    make2d(enc, &m.wd, p.pwd, D_, F_, 16, 192, CU_TENSOR_MAP_SWIZZLE_32B);
    fused_kernel<<<NCTA, NTHREADS, SM_TOTAL>>>(p, m);
}

}

extern "C" void kernel_launch(void* const* d_in, const int* in_sizes, int n_in, void* d_out, int out_size) {
    static int clusters = -1;
    if (clusters < 0) clusters = v3::max_clusters();
    if (clusters < 15 || !v3::launch(d_in, d_out)) v2::launch(d_in, d_out);
}
```

```cpp
#include <cuda_runtime.h>
#include <cuda_bf16.h>
#include <cuda_fp16.h>
#include <cuda.h>
#include <stdint.h>
#include <stddef.h>
#include <type_traits>


namespace v3 {

constexpr bool LD4 = false, ZZ = true;

constexpr int D_ = 576, F_ = 4608;
constexpr int NCTA = 120, NTHREADS = 512;
constexpr int SPIN_LIMIT = 1 << 16;

enum { B_Y = 0, B_X = 8, B_TOP = 10, B_XS = 12, B_UP = 13, B_RAW = 15, B_FULL = 16, B_FIN = 43, B_SEL = 44, B_ST = 45, B_EMPTY = 38  , B_ROWS = 66, B_WR = 67 };
constexpr int SM_SKIP = 544, SM_SEL = 576;
constexpr int SM_ST = 640;
constexpr int SM_RAW = 2688, PITCH = 80;
constexpr int SM_CH = SM_RAW + 256 * PITCH, CH = 18304;
constexpr int TAB = 0, FT = 3072, XX = 3712, BOX = 8064, YIN = 14208;
constexpr int SM_B = SM_CH + 5 * CH, BP = 1168;
constexpr int SM_CAND = SM_B + 8 * BP, SM_PROG = SM_CAND + 256, SM_DUMP = SM_PROG + 128;
constexpr int NRING = 12, SM_W = SM_B + 10240, SM_FIN = SM_W + NRING * 8192, SM_TOTAL = 232448;
static_assert(SM_W % 1024 == 0 && SM_FIN + 8192 <= SM_TOTAL && SM_TOTAL - 18432 >= SM_W + 10 * 8192, "smem");

struct Tune { int t_tile, stag, tail, win0, s0, t_rows, da, ns0, zero; };

struct Scratch {
    uint32_t h[8 * 2304];
    uint2 stat[2048];
    uint32_t ep[NCTA * 8];
};
__device__ __align__(1024) Scratch g_s;

struct Hot {
    const __nv_bfloat16* u;
    int bre, bim, cre, cim, are, aim, logdt, dskip, wr, ep;
    Scratch* s;
    __nv_bfloat16* out;
    Tune tn;
};
struct Maps { CUtensorMap w[3], u; };

__device__ __forceinline__ uint32_t smem_u32(const void* p) { return (uint32_t)__cvta_generic_to_shared(p); }
__device__ __forceinline__ void mbar_init(uint32_t b, int c) { asm volatile("mbarrier.init.shared::cta.b64 [%0], %1;" ::"r"(b), "r"(c) : "memory"); }
__device__ __forceinline__ void mbar_expect(uint32_t b, int bytes) { asm volatile("mbarrier.arrive.expect_tx.shared::cta.b64 _, [%0], %1;" ::"r"(b), "r"(bytes) : "memory"); }
__device__ __forceinline__ void mbar_arrive(uint32_t b) { asm volatile("mbarrier.arrive.shared::cta.b64 _, [%0];" ::"r"(b) : "memory"); }
__device__ __forceinline__ bool elect() { uint32_t d; asm volatile("{.reg .pred p; elect.sync _|p, 0xffffffff; selp.u32 %0,1,0,p;}" : "=r"(d)); return d; }
__device__ __forceinline__ void mbar_wait(uint32_t b, int par) {
    asm volatile("{\n.reg .pred p;\nLW:\nmbarrier.try_wait.parity.shared::cta.b64 p, [%0], %1, 2000;\n@!p bra LW;\n}" ::"r"(b), "r"(par) : "memory");
}
__device__ __forceinline__ void mbar_wait_short(uint32_t b) {
    asm volatile("{\n.reg .pred p;\nLW:\nmbarrier.try_wait.parity.shared::cta.b64 p, [%0], 0;\n@!p bra LW;\n}" ::"r"(b) : "memory");
}
__device__ __forceinline__ uint32_t mapa(uint32_t a, uint32_t rank) { uint32_t d; asm("mapa.shared::cluster.u32 %0, %1, %2;" : "=r"(d) : "r"(a), "r"(rank)); return d; }
__device__ __forceinline__ void tma2d(uint32_t dst, const CUtensorMap* m, int c0, int c1, uint32_t bar) {
    asm volatile("cp.async.bulk.tensor.2d.shared::cluster.global.mbarrier::complete_tx::bytes [%0], [%1, {%3, %4}], [%2];" ::"r"(dst), "l"(m), "r"(bar), "r"(c0), "r"(c1) : "memory");
}
__device__ __forceinline__ void bulk_g2s(uint32_t dst, const void* src, int bytes, uint32_t bar) {
    asm volatile("cp.async.bulk.shared::cluster.global.mbarrier::complete_tx::bytes [%0], [%1], %2, [%3];" ::"r"(dst), "l"(src), "r"(bytes), "r"(bar) : "memory");
}
__device__ __forceinline__ void bulk_mc(uint32_t dst, const void* src, int bytes, uint32_t bar) {
    asm volatile("cp.async.bulk.shared::cluster.global.mbarrier::complete_tx::bytes.multicast::cluster [%0], [%1], %2, [%3], %4;"
                 ::"r"(dst), "l"(src), "r"(bytes), "r"(bar), "h"((uint16_t)255) : "memory");
}
__device__ __forceinline__ void bar_sync(int id, int n) { asm volatile("bar.sync %0, %1;" ::"r"(id), "r"(n) : "memory"); }
__device__ __forceinline__ void bar_arrive(int id, int n) { asm volatile("bar.arrive %0, %1;" ::"r"(id), "r"(n) : "memory"); }
__device__ __forceinline__ uint4 ld_rlx4(const void* p) { uint4 v; asm volatile("ld.relaxed.gpu.global.v4.u32 {%0,%1,%2,%3}, [%4];" : "=r"(v.x), "=r"(v.y), "=r"(v.z), "=r"(v.w) : "l"(p) : "memory"); return v; }
__device__ __forceinline__ uint2 ld_rlx2(const void* p) { uint2 v; asm volatile("ld.relaxed.gpu.global.v2.u32 {%0,%1}, [%2];" : "=r"(v.x), "=r"(v.y) : "l"(p) : "memory"); return v; }
__device__ __forceinline__ uint32_t ld_rlx(const void* p) { uint32_t v; asm volatile("ld.relaxed.gpu.global.u32 %0, [%1];" : "=r"(v) : "l"(p) : "memory"); return v; }
__device__ __forceinline__ void st_rlx(void* p, uint32_t v) { asm volatile("st.relaxed.gpu.global.u32 [%0], %1;" ::"l"(p), "r"(v) : "memory"); }
__device__ __forceinline__ void st_rlx2(void* p, uint32_t x, uint32_t y) { asm volatile("st.relaxed.gpu.global.v2.u32 [%0], {%1,%2};" ::"l"(p), "r"(x), "r"(y) : "memory"); }
__device__ __forceinline__ uint4 ldg4(const void* p) { uint4 v; asm volatile("ld.global.nc.v4.u32 {%0,%1,%2,%3}, [%4];" : "=r"(v.x), "=r"(v.y), "=r"(v.z), "=r"(v.w) : "l"(p)); return v; }
__device__ __forceinline__ uint32_t ldg1(const void* p) { uint32_t v; asm volatile("ld.global.nc.u32 %0, [%1];" : "=r"(v) : "l"(p)); return v; }
__device__ __forceinline__ uint32_t ldg16(const void* p) { uint16_t v; asm volatile("ld.global.nc.u16 %0, [%1];" : "=h"(v) : "l"(p)); return v; }
__device__ __forceinline__ const void* at256(const void* b, int o) { const void* r; asm("mad.wide.s32 %0, %1, 256, %2;" : "=l"(r) : "r"(o), "l"(b)); return r; }
__device__ __forceinline__ int laneid() { int v; asm volatile("mov.u32 %0, %%laneid;" : "=r"(v)); return v; }
__device__ __forceinline__ int ctaid() { int v; asm volatile("mov.u32 %0, %%ctaid.x;" : "=r"(v)); return v; }
__device__ __forceinline__ uint32_t lds32(uint32_t a) { uint32_t v; asm volatile("ld.shared.u32 %0, [%1];" : "=r"(v) : "r"(a) : "memory"); return v; }
__device__ __forceinline__ uint32_t lds32v(uint32_t a) { uint32_t v; asm volatile("ld.volatile.shared.u32 %0, [%1];" : "=r"(v) : "r"(a) : "memory"); return v; }
__device__ __forceinline__ uint32_t lds16(uint32_t a) { uint16_t v; asm volatile("ld.shared.u16 %0, [%1];" : "=h"(v) : "r"(a) : "memory"); return v; }
__device__ __forceinline__ uint2 lds64(uint32_t a) { uint2 v; asm volatile("ld.shared.v2.u32 {%0,%1}, [%2];" : "=r"(v.x), "=r"(v.y) : "r"(a) : "memory"); return v; }
__device__ __forceinline__ uint4 lds128(uint32_t a) { uint4 v; asm volatile("ld.shared.v4.u32 {%0,%1,%2,%3}, [%4];" : "=r"(v.x), "=r"(v.y), "=r"(v.z), "=r"(v.w) : "r"(a) : "memory"); return v; }
__device__ __forceinline__ void sts16(uint32_t a, uint32_t v) { asm volatile("st.shared.u16 [%0], %1;" ::"r"(a), "h"((uint16_t)v) : "memory"); }
__device__ __forceinline__ void sts32(uint32_t a, uint32_t v) { asm volatile("st.shared.u32 [%0], %1;" ::"r"(a), "r"(v) : "memory"); }
__device__ __forceinline__ void sts32v(uint32_t a, uint32_t v) { asm volatile("st.volatile.shared.u32 [%0], %1;" ::"r"(a), "r"(v) : "memory"); }
__device__ __forceinline__ void sts64(uint32_t a, uint32_t x, uint32_t y) { asm volatile("st.shared.v2.u32 [%0], {%1,%2};" ::"r"(a), "r"(x), "r"(y) : "memory"); }
__device__ __forceinline__ void sts128(uint32_t a, uint32_t x, uint32_t y, uint32_t z, uint32_t w) { asm volatile("st.shared.v4.u32 [%0], {%1,%2,%3,%4};" ::"r"(a), "r"(x), "r"(y), "r"(z), "r"(w) : "memory"); }
__device__ __forceinline__ void sts128v(uint32_t a, uint32_t x, uint32_t y, uint32_t z, uint32_t w) { asm volatile("st.volatile.shared.v4.u32 [%0], {%1,%2,%3,%4};" ::"r"(a), "r"(x), "r"(y), "r"(z), "r"(w) : "memory"); }
__device__ __forceinline__ void sts128f(uint32_t a, float x, float y, float z, float w) { asm volatile("st.shared.v4.f32 [%0], {%1,%2,%3,%4};" ::"r"(a), "f"(x), "f"(y), "f"(z), "f"(w) : "memory"); }
__device__ __forceinline__ void st_async4(uint32_t a, uint32_t x, uint32_t y, uint32_t z, uint32_t w, uint32_t bar) {
    asm volatile("st.async.shared::cluster.mbarrier::complete_tx::bytes.v4.b32 [%0], {%1,%2,%3,%4}, [%5];" ::"r"(a), "r"(x), "r"(y), "r"(z), "r"(w), "r"(bar) : "memory");
}
__device__ __forceinline__ void st_async2(uint32_t a, uint32_t x, uint32_t y, uint32_t bar) {
    asm volatile("st.async.shared::cluster.mbarrier::complete_tx::bytes.v2.b32 [%0], {%1,%2}, [%3];" ::"r"(a), "r"(x), "r"(y), "r"(bar) : "memory");
}
__device__ __forceinline__ void st_async2f(uint32_t a, float x, float y, uint32_t bar) {
    asm volatile("st.async.shared::cluster.mbarrier::complete_tx::bytes.v2.f32 [%0], {%1,%2}, [%3];" ::"r"(a), "f"(x), "f"(y), "r"(bar) : "memory");
}
__device__ __forceinline__ void ldm4(uint32_t a, uint32_t& r0, uint32_t& r1, uint32_t& r2, uint32_t& r3) {
    asm volatile("ldmatrix.sync.aligned.m8n8.x4.shared.b16 {%0,%1,%2,%3}, [%4];" : "=r"(r0), "=r"(r1), "=r"(r2), "=r"(r3) : "r"(a) : "memory");
}
__device__ __forceinline__ void ldm4t(uint32_t a, uint32_t (&r)[4]) {
    asm volatile("ldmatrix.sync.aligned.m8n8.x4.trans.shared.b16 {%0,%1,%2,%3}, [%4];" : "=r"(r[0]), "=r"(r[1]), "=r"(r[2]), "=r"(r[3]) : "r"(a) : "memory");
}
__device__ __forceinline__ void ldm2(uint32_t a, uint32_t& r0, uint32_t& r1) {
    asm volatile("ldmatrix.sync.aligned.m8n8.x2.shared.b16 {%0,%1}, [%2];" : "=r"(r0), "=r"(r1) : "r"(a) : "memory");
}
__device__ __forceinline__ void ldm2t(uint32_t a, uint32_t& r0, uint32_t& r1) {
    asm volatile("ldmatrix.sync.aligned.m8n8.x2.trans.shared.b16 {%0,%1}, [%2];" : "=r"(r0), "=r"(r1) : "r"(a) : "memory");
}
__device__ __forceinline__ void stm4(uint32_t a, uint32_t r0, uint32_t r1, uint32_t r2, uint32_t r3) {
    asm volatile("stmatrix.sync.aligned.m8n8.x4.shared.b16 [%0], {%1,%2,%3,%4};" ::"r"(a), "r"(r0), "r"(r1), "r"(r2), "r"(r3) : "memory");
}
__device__ __forceinline__ void stm4t(uint32_t a, uint32_t r0, uint32_t r1, uint32_t r2, uint32_t r3) {
    asm volatile("stmatrix.sync.aligned.m8n8.x4.trans.shared.b16 [%0], {%1,%2,%3,%4};" ::"r"(a), "r"(r0), "r"(r1), "r"(r2), "r"(r3) : "memory");
}
__device__ __forceinline__ void stm2t(uint32_t a, uint32_t r0, uint32_t r1) {
    asm volatile("stmatrix.sync.aligned.m8n8.x2.trans.shared.b16 [%0], {%1,%2};" ::"r"(a), "r"(r0), "r"(r1) : "memory");
}
__device__ __forceinline__ uint32_t movm(uint32_t a) { uint32_t d; asm volatile("movmatrix.sync.aligned.m8n8.trans.b16 %0, %1;" : "=r"(d) : "r"(a)); return d; }
__device__ __forceinline__ void mma_bf(float (&c)[4], uint32_t a0, uint32_t a1, uint32_t a2, uint32_t a3, uint32_t b0, uint32_t b1) {
    asm volatile("mma.sync.aligned.m16n8k16.row.col.f32.bf16.bf16.f32 {%0,%1,%2,%3},{%4,%5,%6,%7},{%8,%9},{%0,%1,%2,%3};"
                 : "+f"(c[0]), "+f"(c[1]), "+f"(c[2]), "+f"(c[3]) : "r"(a0), "r"(a1), "r"(a2), "r"(a3), "r"(b0), "r"(b1));
}
__device__ __forceinline__ void mma_bf8(float (&c)[4], uint32_t a0, uint32_t a1, uint32_t b0) {
    asm volatile("mma.sync.aligned.m16n8k8.row.col.f32.bf16.bf16.f32 {%0,%1,%2,%3},{%4,%5},{%6},{%0,%1,%2,%3};"
                 : "+f"(c[0]), "+f"(c[1]), "+f"(c[2]), "+f"(c[3]) : "r"(a0), "r"(a1), "r"(b0));
}
__device__ __forceinline__ void mma_h(float (&c)[4], uint32_t a0, uint32_t a1, uint32_t a2, uint32_t a3, uint32_t b0, uint32_t b1) {
    asm volatile("mma.sync.aligned.m16n8k16.row.col.f32.f16.f16.f32 {%0,%1,%2,%3},{%4,%5,%6,%7},{%8,%9},{%0,%1,%2,%3};"
                 : "+f"(c[0]), "+f"(c[1]), "+f"(c[2]), "+f"(c[3]) : "r"(a0), "r"(a1), "r"(a2), "r"(a3), "r"(b0), "r"(b1));
}
__device__ __forceinline__ void mma_h8(float (&c)[4], uint32_t a0, uint32_t a1, uint32_t b0) {
    asm volatile("mma.sync.aligned.m16n8k8.row.col.f32.f16.f16.f32 {%0,%1,%2,%3},{%4,%5},{%6},{%0,%1,%2,%3};"
                 : "+f"(c[0]), "+f"(c[1]), "+f"(c[2]), "+f"(c[3]) : "r"(a0), "r"(a1), "r"(b0));
}
template <int LIM>
__device__ __forceinline__ void mma_hp(int n, float (&d)[4], const float (&c)[4], uint32_t a0, uint32_t a1, uint32_t a2, uint32_t a3, uint32_t b0, uint32_t b1) {
    asm volatile("{.reg .pred p; setp.gt.s32 p, %14, %15;\n"
                 "@p mma.sync.aligned.m16n8k16.row.col.f32.f16.f16.f32 {%0,%1,%2,%3},{%4,%5,%6,%7},{%8,%9},{%10,%11,%12,%13};}"
                 : "+f"(d[0]), "+f"(d[1]), "+f"(d[2]), "+f"(d[3])
                 : "r"(a0), "r"(a1), "r"(a2), "r"(a3), "r"(b0), "r"(b1), "f"(c[0]), "f"(c[1]), "f"(c[2]), "f"(c[3]), "r"(n), "n"(LIM));
}
template <int LIM>
__device__ __forceinline__ void mma_hq(int n, float (&d)[4], uint32_t a0, uint32_t a1, uint32_t a2, uint32_t a3, uint32_t b0, uint32_t b1) {
    asm volatile("{.reg .pred p; setp.gt.s32 p, %10, %11;\n"
                 "@p mma.sync.aligned.m16n8k16.row.col.f32.f16.f16.f32 {%0,%1,%2,%3},{%4,%5,%6,%7},{%8,%9},{%0,%1,%2,%3};}"
                 : "+f"(d[0]), "+f"(d[1]), "+f"(d[2]), "+f"(d[3]) : "r"(a0), "r"(a1), "r"(a2), "r"(a3), "r"(b0), "r"(b1), "r"(n), "n"(LIM));
}
__device__ __forceinline__ void mma_hc(float (&d)[4], const float (&c)[4], uint32_t a0, uint32_t a1, uint32_t a2, uint32_t a3, uint32_t b0, uint32_t b1) {
    asm volatile("mma.sync.aligned.m16n8k16.row.col.f32.f16.f16.f32 {%0,%1,%2,%3},{%4,%5,%6,%7},{%8,%9},{%10,%11,%12,%13};"
                 : "=f"(d[0]), "=f"(d[1]), "=f"(d[2]), "=f"(d[3]) : "r"(a0), "r"(a1), "r"(a2), "r"(a3), "r"(b0), "r"(b1), "f"(c[0]), "f"(c[1]), "f"(c[2]), "f"(c[3]));
}
__device__ __forceinline__ uint32_t pack_bf(float lo, float hi) { uint32_t r; asm("cvt.rn.bf16x2.f32 %0, %1, %2;" : "=r"(r) : "f"(hi), "f"(lo)); return r; }
__device__ __forceinline__ uint32_t pack_h(float lo, float hi) { uint32_t r; asm("cvt.rn.f16x2.f32 %0, %1, %2;" : "=r"(r) : "f"(hi), "f"(lo)); return r; }
__device__ __forceinline__ float bf_lo(uint32_t w) { return __uint_as_float(w << 16); }
__device__ __forceinline__ float bf_hi(uint32_t w) { return __uint_as_float(w & 0xFFFF0000u); }
__device__ __forceinline__ float bf_round(float x) { return __uint_as_float(pack_bf(0.f, x)); }
__device__ __forceinline__ uint32_t badd(uint32_t a, uint32_t b) { uint32_t r; asm("add.rn.bf16x2 %0, %1, %2;" : "=r"(r) : "r"(a), "r"(b)); return r; }
__device__ __forceinline__ uint32_t bsub(uint32_t a, uint32_t b) { uint32_t r; asm("sub.rn.bf16x2 %0, %1, %2;" : "=r"(r) : "r"(a), "r"(b)); return r; }
__device__ __forceinline__ uint32_t bmul(uint32_t a, uint32_t b) { uint32_t r; asm("mul.rn.bf16x2 %0, %1, %2;" : "=r"(r) : "r"(a), "r"(b)); return r; }
__device__ __forceinline__ uint32_t bfma(uint32_t a, uint32_t b, uint32_t c) { uint32_t r; asm("fma.rn.bf16x2 %0, %1, %2, %3;" : "=r"(r) : "r"(a), "r"(b), "r"(c)); return r; }
__device__ __forceinline__ uint32_t hadd(uint32_t a, uint32_t b) { uint32_t r; asm("add.rn.f16x2 %0, %1, %2;" : "=r"(r) : "r"(a), "r"(b)); return r; }
__device__ __forceinline__ uint32_t prmt(uint32_t a, uint32_t b, uint32_t s) { uint32_t r; asm("prmt.b32 %0, %1, %2, %3;" : "=r"(r) : "r"(a), "r"(b), "r"(s)); return r; }
__device__ __forceinline__ uint32_t lop_ne(uint32_t a, uint32_t b, uint32_t c) { uint32_t r; asm("lop3.b32 %0, %1, %2, %3, 0x7E;" : "=r"(r) : "r"(a), "r"(b), "r"(c)); return r; }
__device__ __forceinline__ float ex2f(float x) { float r; asm("ex2.approx.ftz.f32 %0, %1;" : "=f"(r) : "f"(x)); return r; }
__device__ __forceinline__ float rcpf(float x) { float r; asm("rcp.approx.ftz.f32 %0, %1;" : "=f"(r) : "f"(x)); return r; }
__device__ __forceinline__ float sqrt_ap(float x) { float r; asm("sqrt.approx.ftz.f32 %0, %1;" : "=f"(r) : "f"(x)); return r; }
__device__ __forceinline__ float tanh_ap(float x) { float r; asm("tanh.approx.f32 %0, %1;" : "=f"(r) : "f"(x)); return r; }
__device__ __forceinline__ float sigm(float x) { return rcpf(1.f + ex2f(-1.4426950408889634f * x)); }
__device__ __forceinline__ float silu_half(float h) { return fmaf(h, tanh_ap(h), h); }
__device__ __forceinline__ uint32_t clk32() { uint32_t c; asm volatile("mov.u32 %0, %%clock;" : "=r"(c)); return c; }
__device__ __forceinline__ void spin_until(uint32_t t0, int dt) {
#pragma unroll 1
    while ((int)(clk32() - t0) < dt) __nanosleep(32);
}
__device__ __forceinline__ void cp16(uint32_t dst, const void* src) { asm volatile("cp.async.cg.shared.global [%0], [%1], 16;" ::"r"(dst), "l"(src) : "memory"); }

__device__ __forceinline__ uint32_t xslot(int s, int h) { return XX + 32 * (s & ~1) + 16 * ((2 * h + (s & 1)) ^ ((s >> 1) & 2)); }

struct cf { float x, y; };
__device__ __forceinline__ cf cmul(cf a, cf b) { return {a.x * b.x - a.y * b.y, a.x * b.y + a.y * b.x}; }
__device__ __forceinline__ cf csq(cf a) { return {a.x * a.x - a.y * a.y, (a.x + a.x) * a.y}; }
__device__ __forceinline__ cf cpow_direct(float zr2, float zi, float l) {
    const float mag = ex2f(zr2 * l), th = zi * l;
    return {mag * __cosf(th), mag * __sinf(th)};
}
struct hp { uint32_t re, im; };
struct hm { __half2 v; };
__device__ __forceinline__ __half2 as_h2(uint32_t v) { return *reinterpret_cast<__half2*>(&v); }
__device__ __forceinline__ uint32_t as_u32(__half2 v) { return *reinterpret_cast<uint32_t*>(&v); }
__device__ __forceinline__ hp mk2(cf a, cf b) { return {pack_h(a.x, b.x), pack_h(a.y, b.y)}; }
__device__ __forceinline__ hm mk1(cf a) { return {as_h2(pack_h(a.x, a.y))}; }
__device__ __forceinline__ hp his(hp a, hp b) { return {prmt(a.re, b.re, 0x7632), prmt(a.im, b.im, 0x7632)}; }
__device__ __forceinline__ hp operator*(hp a, hm b) {
    const __half2 c = __low2half2(b.v), s = __high2half2(b.v), x = as_h2(a.re), y = as_h2(a.im);
    return {as_u32(__hfma2(x, c, __hneg2(__hmul2_rn(y, s)))), as_u32(__hfma2(x, s, __hmul2_rn(y, c)))};
}
struct KParams { uint32_t are, aim, bre, bim, cre, cim, ldt, dsk, sa, la, lb; };

__device__ __forceinline__ uint32_t kgen(KParams kp, uint32_t scr, uint32_t oth, int bar, int lane, float (&d)[5][4], float& k0, int nc, uint32_t pause) {
    const float dt = bf_round(ex2f(bf_lo(kp.ldt) * 1.4426950408889634f));
    cf w = cmul({bf_lo(kp.cre), bf_lo(kp.cim)}, {dt * bf_lo(kp.bre), dt * bf_lo(kp.bim)});
    cf w1 = cmul({bf_hi(kp.cre), bf_hi(kp.cim)}, {dt * bf_hi(kp.bre), dt * bf_hi(kp.bim)});
    const float dk = bf_lo(kp.dsk), dt2 = dt * 1.4426950408889634f;
    uint32_t z = prmt(kp.are, kp.aim, 0x5410), z1 = prmt(kp.are, kp.aim, 0x7632);
    uint32_t eb = __reduce_max_sync(~0u, __float_as_uint(fmaxf(fmaxf(fmaxf(fabsf(w.x), fabsf(w.y)), fmaxf(fabsf(w1.x), fabsf(w1.y))), fabsf(dk) * 0x1p-20f)));
    k0 = fmaf(dk, 1.f / 64.f, w.x + w1.x);
    const uint32_t sa = kp.sa, la = kp.la, lb = kp.lb;
    sts128(oth + 2048 + 16 * lane, __float_as_uint(w1.x), __float_as_uint(w1.y), z1, __float_as_uint(k0));
    sts32(oth + 2560, eb);
    bar_sync(bar, 64);
    const uint4 ov = lds128(sa + 2048);
    eb = min(max(max(eb, lds32(scr + 2560)) & 0x7F800000u, 0x00800000u), 0x7A000000u);
    const float sc = __uint_as_float(0x7B000000u - eb);
    k0 = (k0 + __uint_as_float(ov.w)) * sc;
#pragma unroll
    for (int i = 0; i < 5; i++) d[i][0] = d[i][1] = d[i][2] = d[i][3] = 0.f;
    auto st = [&](int grp, hp a, hp b, hp c, hp e) { sts128v(sa + 1024 * grp, a.re, b.re, c.re, e.re); sts128v(sa + 1024 * grp + 512, a.im, b.im, c.im, e.im); };
#pragma unroll 1
    do {
        const float zr2 = dt2 * bf_lo(z), zi = dt * bf_hi(z);
        const cf ws = {w.x * sc, w.y * sc};
        z = z1; w = w1;
        z1 = ov.z; w1 = {__uint_as_float(ov.x), __uint_as_float(ov.y)};
        const cf a1 = cpow_direct(zr2, zi, 1.f), a256 = cpow_direct(zr2, zi, 256.f);
        uint32_t a[4][4];
        {
            const cf b1 = cpow_direct(-zr2, zi, -16.f), b2 = csq(b1), b4 = csq(b2), b8 = csq(b4);
            const hm m2 = mk1(b2), m4 = mk1(b4), m8 = mk1(b8);
            const hp u0 = mk2({1.f, 0.f}, b1), u1 = u0 * m2, u2 = u0 * m4, u3 = u1 * m4;
            __syncwarp();
            st(1, u0 * m8, u1 * m8, u2 * m8, u3 * m8);
            st(0, u0, u1, u2, u3);
            __syncwarp();
#pragma unroll
            for (int k = 0; k < 4; k++) ldm4t(la + 128 * k, a[k]);
        }
        auto tile = [&](int T, int grp) {
#pragma unroll
            for (int e = 0; e < 2; e++) {
                uint32_t b[4];
                ldm4t(lb + 1024 * grp + 256 * e, b);
                mma_h(d[T], a[2 * e][0], a[2 * e][1], a[2 * e][2], a[2 * e][3], b[0], b[1]);
                mma_h(d[T], a[2 * e + 1][0], a[2 * e + 1][1], a[2 * e + 1][2], a[2 * e + 1][3], b[2], b[3]);
            }
        };
        const cf a2 = csq(a1), a4 = csq(a2), a8 = csq(a4), a512 = csq(a256), a1024 = csq(a512);
        const hm m2 = mk1(a2), m4 = mk1(a4), m8 = mk1(a8), m256 = mk1(a256), m512 = mk1(a512);
        const hp v1 = mk2(cmul(ws, a1), cmul(ws, a2)), v3 = v1 * m2, v5 = v1 * m4, v7 = v3 * m4, v15 = v7 * m8;
        const hp e1 = his(v1, v3) * m256, e2 = e1 * m4;
        hp f0 = his(v3, v7), g0 = his(v7, v15);
        asm volatile("" : "+r"(f0.re), "+r"(f0.im), "+r"(g0.re), "+r"(g0.im));
        __syncwarp();
        st(2, e1, e2, e1 * m8, e2 * m8);
        st(0, v1, v5, v1 * m8, v5 * m8);
        st(1, v3, v7, v3 * m8, v15);
        __syncwarp();
        tile(0, 0); tile(1, 1); tile(2, 2);
        const hp f1 = f0 * m512, f2 = f1 * m8, g1 = g0 * mk1(a1024), g2 = g1 * m256;
        __syncwarp();
        st(0, f1, f2, f1 * m256, f2 * m256);
        st(1, g1, g2, g1 * m512, g2 * m512);
        __syncwarp();
        tile(3, 0); tile(4, 1);
        if (pause) mbar_wait_short(pause);
    } while (--nc);
    return eb;
}

__device__ __forceinline__ void near_lags(uint32_t S, int k, uint32_t yo, uint32_t eb) {
    const int lane = threadIdx.x & 31, g = lane >> 2, t = lane & 3, mi = lane >> 3, j = lane & 7, warp = k;
    const uint32_t cb = S + SM_CH + k * CH;
    uint32_t R[66], x[5];
#pragma unroll
    for (int i = 0; i < 66; i++) R[i] = lds32(cb + TAB + 4 * (7 + g - 2 * t) + 32 * i);
    bar_arrive(1 + k, 64);
    float w[5][4];
#pragma unroll
    for (int i = 0; i < 5; i++) w[i][0] = w[i][1] = w[i][2] = w[i][3] = 0.f;
    uint32_t xa[8], xo = cb;
    {
        const uint32_t v = xslot(lane & 15, lane >> 4);
#pragma unroll
        for (int i = 0; i < 8; i++) xa[i] = __shfl_sync(~0u, v, LD4 ? j + i + (mi == 1 ? 17 : (mi == 2 ? 16 : 1)) : j + 2 * (lane & 8) + i);
    }
    uint32_t fa = xa[0], idm = 0;
    uint32_t ya = S + SM_DUMP + 8 * lane, ybar = S + 61 * 8, dy = 0, db = 0;
    const uint32_t sc = prmt(eb + 0x04800000u, 0, 0x3232);
    uint32_t z = lds32(cb + XX + 4 * lane);
    int n = 16;
    mbar_wait(S + B_X * 8, 0);
    uint32_t A[3][4];
    if (LD4) {
        ldm4(xo + xa[0], A[0][0], A[0][1], A[0][2], A[0][3]);
        ldm4(xo + xa[1], A[1][0], A[1][1], A[1][2], A[1][3]);
    } else {
        ldm2(xo + xa[0], x[1], x[0]);
        ldm2(xo + xa[1], x[1], x[2]);
        ldm2(xo + xa[2], x[3], x[4]);
    }
    auto send = [&]() { st_async2(ya, bmul(pack_bf(w[0][0], w[0][1]), sc), bmul(pack_bf(w[0][2], w[0][3]), sc), ybar); };
    auto tile = [&](auto nj) {
        constexpr int NJ = decltype(nj)::value;
        asm volatile("" : "+r"(z), "+r"(xo));
        uint32_t f0, f1;
        ldm2(xo + fa, f0, f1);
        send();
#pragma unroll
        for (int q = 1; q <= 8; q++) {
            uint32_t n0, n1, a2, a3;
            if (LD4) {
                ldm4(xo + xa[(q + 1) & 7] + 32 * ((q + 1) & 8), A[2][0], A[2][1], A[2][2], A[2][3]);
                x[1] = A[0][0]; x[2] = A[0][1]; a2 = A[0][2]; a3 = A[0][3];
#pragma unroll
                for (int e = 0; e < 4; e++) { A[0][e] = A[1][e]; A[1][e] = A[2][e]; }
            } else {
                ldm2(xo + xa[(q + 2) & 7] + 32 * ((q + 2) & 8), n0, n1);
                a2 = x[0] | z; a3 = x[1] | z;
            }
#pragma unroll
            for (int i = 0; i < NJ; i++) {
                const int s = 16 * i + 16 - 2 * q;
                if (q == 1) mma_hc(w[i], w[i + 1], x[1], x[2], a2, a3, R[s], R[s + 1]);
                else mma_h(w[i], x[1], x[2], a2, a3, R[s], R[s + 1]);
            }
            if (q == 4) mma_h8(w[1], f0, f1, idm);
            if (q == 7 && ZZ) {
                const uint32_t zz = x[1] & z;
                ya += dy + zz; ybar += db + zz; dy = 512 - dy; db = 8 - db;
            }
            if (q == 8 && NJ == 4) {
                const float zero[4] = {0.f, 0.f, 0.f, 0.f};
                mma_hc(w[4], zero, x[1], x[2], a2, a3, R[64], R[65]);
            }
            if (!LD4) { x[0] = x[2]; x[1] = x[3]; x[2] = x[4]; x[3] = n0; x[4] = n1; }
        }
        xo += 256; if (!ZZ) { ya += dy; ybar += db; dy = 512 - dy; db = 8 - db; }
    };
    int lim = 15;
#pragma unroll 1
    for (;;) {
        n -= lim;
#pragma unroll 1
        do tile(std::integral_constant<int, 4>()); while (--n);
        n = lim;
        if (n < 5) break;
        const int lane = laneid(), g = lane >> 2, t = lane & 3;
        if (n == 15) {
            ybar = mapa(S + B_Y * 8, g >> 1);
            db = dy = mapa(S + B_Y * 8, 4 + (g >> 1)) - ybar;
            ya = ybar - B_Y * 8 + SM_CH + k * CH + YIN + (yo ^ (8 * (lane & 7)));
        }
        if (n == 13) { fa = TAB - 768 + 16 * (lane & 15); idm = g == 2 * t ? 0x3C00u : (g == 2 * t + 1 ? 0x3C000000u : 0u); }
#pragma unroll 1
        while ((lim = lds32v(S + SM_PROG + 4 * k)) >= n) __nanosleep(40);
        if (n == 15) lim = 13;
    }
#pragma unroll 1
    for (; n > 0; n--) tile(std::integral_constant<int, 2>());
    send();
}

__global__ void __cluster_dims__(8, 1, 1) __launch_bounds__(NTHREADS, 1) fused_kernel(const Hot p, const __grid_constant__ Maps m) {
    extern __shared__ __align__(1024) char smem[];
    const uint32_t t0 = clk32();
    const int tid = threadIdx.x, lane = tid & 31, bx = blockIdx.x;
    const int g = lane >> 2, t = lane & 3, mi = lane >> 3, j = lane & 7;
    const uint32_t role = __shfl_sync(~0u, (tid >> 5) | ((uint32_t)((bx < 24 ? 0x5776666632103210ull : 0x5436666621043210ull) >> ((tid >> 3) & 60)) & 15) << 8 |
                                               max(4 * (bx >> 3), 5 * (bx >> 3) - 3) << 16 | bx << 24, 0);
    const int warp = role & 255, k = (role >> 8) & 255, cbase = (role >> 13) & 0x7F8, bid = role >> 24, r = bid & 7, cl = role >> 27;
    const int pair = cl > 2, nch = 4 + pair;
    uint32_t S = smem_u32(smem);
    asm volatile("" : "+r"(S));

    const int half = warp >= nch;
    const bool two = cl == 1 || cl == 2, extra = two && k == 7, svcwarp = (warp >> 2) == 2;
    KParams kp;
    uint32_t epoch;
    if (k < nch) {
        const uint32_t ch = cbase + 8 * k + r;
        const char* pb = (const char*)p.u + (ch * 256 + half * 128 + lane * 4);
        kp.bre = ldg1(at256(pb, p.bre)); kp.bim = ldg1(at256(pb, p.bim));
        kp.cre = ldg1(at256(pb, p.cre)); kp.cim = ldg1(at256(pb, p.cim));
        kp.ldt = ldg16(at256(p.u + ch, lane & 1 ? p.dskip : p.logdt));
        kp.are = ldg1(at256(pb, p.are)); kp.aim = ldg1(at256(pb, p.aim));
        sts128(S + SM_CH + k * CH + 16 * lane + (half ? FT : (lane < 2 ? TAB : (lane < 8 ? TAB + 2048 : FT + 384))), 0u, 0u, 0u, 0u);
        sts32(S + SM_PROG + 4 * k, 13);
        const uint32_t scr = S + SM_CH + k * CH + BOX + 3072 * half + 16 * j;
        kp.sa = __shfl_sync(~0u, scr + 128 * mi, lane);
        kp.la = __shfl_sync(~0u, scr + 1024 * (mi & 1) + 512 * (mi >> 1), lane);
        kp.lb = __shfl_sync(~0u, scr + 512 * (mi & 1) + 128 * (mi >> 1), lane);
    } else if (warp == 12) {
        if (elect()) {
            mbar_init(S + B_WR * 8, 1);
            mbar_init(S + B_ROWS * 8, 1);
            mbar_expect(S + B_WR * 8, 1152);
            bulk_g2s(S + SM_B + 2048, (const char*)p.u + p.wr * 256ll, 1152, S + B_WR * 8);
            while ((int)(clk32() - t0) < p.tn.t_rows) {}
            mbar_expect(S + B_ROWS * 8, two ? 36864 : 18432);
            const __nv_bfloat16* src = p.u + (8 * (cl & 14) + 2 * r + (cl & 1)) * 9216;
            bulk_g2s(S + SM_TOTAL - 18432, src, 18432, S + B_ROWS * 8);
            if (two) bulk_g2s(S + SM_CH + 4 * CH - 128, p.u + (113 + 2 * r) * 9216, 18432, S + B_ROWS * 8);
        }
    } else if (svcwarp) {
        if (elect()) {
#pragma unroll
            for (int i = 0; i < 16; i++) mbar_init(S + (warp & 3) * 128 + i * 8, warp > (i < 14 ? 10 : 9) ? 4 : 1);
            asm volatile("fence.mbarrier_init.release.cluster;" ::: "memory");
        }
        __syncwarp();
        sts128(S + SM_B + 16 * tid, 0x3F803F80u, 0x3F803F80u, 0x3F803F80u, 0x3F803F80u);
        if (tid < 256 + B_RAW) mbar_expect(S + lane * 8, (uint32_t)(0x0808480101180804ull >> (8 * max(lane - 7, 0)) & 255) * (lane < B_TOP ? 128 * nch : 128));
    }
    if (svcwarp || extra) epoch = ld_rlx(at256(p.u + bid * 16, p.ep));
    __syncthreads();
    asm volatile("barrier.cluster.arrive.relaxed.aligned;" ::: "memory");
    const uint2* sp = &p.s->stat[256 * r + 2 * (tid & 127)];
    uint4 sw;
    if (svcwarp) sw = ld_rlx4(sp);
    if (svcwarp || extra) {
        const uint32_t tag = ~epoch & 1;
        const int tile = extra ? 15 : cl, wj = extra ? warp + 2 * cl - 15 : warp & 3;
        float d2[4] = {0, 0, 0, 0}, d3[4] = {0, 0, 0, 0}, d4[4] = {0, 0, 0, 0}, d5[4] = {0, 0, 0, 0}, d6[4] = {0, 0, 0, 0}, d7[4] = {0, 0, 0, 0};
        const uint32_t xa = S + (extra ? SM_CH + 4 * CH - 128 : SM_TOTAL - 18432) + (8 * (mi >> 1) + 2 * wj + (mi & 1)) * 1152 + 16 * j;
        const uint32_t wa = S + SM_B + 4104 - 2056 * (g & 1) + 64 * (g >> 2) + 16 * t + 2 * (g & 2), ones = 0x3F803F80u;
        uint32_t wv[18];
        mbar_wait_short(S + B_WR * 8);
#pragma unroll
        for (int i = 0; i < 18; i++) wv[i] = lds32(wa + 128 * (i >> 1) + 8 * (i & 1));
#pragma unroll
        for (int i = 0; i < 9; i++) mma_bf(d5, ones, ones, ones, ones, wv[2 * i], wv[2 * i + 1]);
        float wsum = d5[1] + __shfl_xor_sync(~0u, d5[1], 1);
        wsum += __shfl_xor_sync(~0u, wsum, 2);
        mbar_wait_short((S + B_ROWS * 8) | (__float_as_uint(wsum) & p.tn.zero));
        __syncwarp();
#pragma unroll
        for (int i = 0; i < 9; i++) {
            const uint4 x = lds128(xa + 128 * i);
            mma_bf8(d3, x.x, x.y, x.x);
            mma_bf8(d4, x.x, x.y, x.y);
            mma_bf8(d6, x.z, x.w, x.z);
            mma_bf8(d7, x.z, x.w, x.w);
            mma_bf(d2, x.x, x.y, x.z, x.w, wv[2 * i], wv[2 * i + 1]);
        }
        float sx = d2[0] + d2[2], sq = (g & 1) ? (d3[1] + d4[3]) + (d6[1] + d7[3]) : (d3[0] + d4[2]) + (d6[0] + d7[2]);
        float dot = (t & 1) ? d2[3] : d2[1];
        sx += __shfl_xor_sync(~0u, sx, 4);
        sq = __shfl_sync(~0u, sq, 9 * mi) + __shfl_sync(~0u, sq, 9 * mi + 4);
        dot += __shfl_xor_sync(~0u, dot, 1);
        dot += __shfl_xor_sync(~0u, dot, 6);
        const float mean = sx * (1.f / 576.f), var = fmaxf(sq * (1.f / 576.f) - mean * mean, 0.f);
        const float mu = bf_round(mean), sd = bf_round(sqrt_ap(bf_round(bf_round(var) + 1e-5f)));
        const uint32_t idx = 2047 - (128 * (tile & 14) + 32 * r + 16 * (tile & 1) + 8 * (mi >> 1) + 2 * wj + (mi & 1));
        const uint32_t rb = pack_bf(0.f, (dot - mu * wsum) * rcpf(sd));
        uint2 v = make_uint2((__float_as_uint(mu) >> 16) | __float_as_uint(sd), (((rb ^ (((int)rb >> 31) | 0x80000000u)) >> 1) & 0x7FFF8000u) | (tag << 31) | idx);
        uint2* const dst = &p.s->stat[256 * r + 16 * tile];
        if (extra) {
            if (j == 0) st_rlx2(dst + 4 * wj + mi, v.x, v.y);
            bar_arrive(13, 224);
        } else {
        const uint32_t ga = S + SM_B + 3200 + 32 * wj;
        if (j == 0) sts64(ga + 8 * mi, v.x, v.y);
        bar_sync(15, 128);
        if (tid < 272) {
            v = lds64(ga + 8 * lane);
            st_rlx2(dst + lane, v.x, v.y);
        }
        if (lane == 0) mbar_arrive(S + (B_EMPTY + 10) * 8);
        }
    }

    if (k < nch) {
        const uint32_t cb = S + SM_CH + k * CH, scr = cb + BOX + 3072 * half, oth = cb + BOX + 3072 - 3072 * half;
        float d[5][4], k0;
        kp.dsk = __shfl_sync(~0u, kp.ldt, 1);
        kp.ldt = __shfl_sync(~0u, kp.ldt, 0);
        const uint32_t eb = kgen(kp, scr, oth, 1 + k, lane, d, k0, k > 7 - nch ? 3 - 2 * half : 2, ((p.tn.stag >> warp) & 1) ? S + (B_EMPTY + 10) * 8 : 0);
        __syncwarp();
#pragma unroll
        for (int i = 0; i < 5; i++)
            if (half == (i < 3)) sts128f(kp.sa + i * 512, d[i][0], d[i][1], d[i][2], d[i][3]);
        if (!half) {
#pragma unroll
            for (int o = 16; o > 0; o >>= 1) k0 += __shfl_xor_sync(~0u, k0, o);
        }
        bar_sync(1 + k, 64);
        auto both = [&](int i, uint32_t& w0, uint32_t& w1) {
            const uint4 v = lds128(oth + i * 512 + lane * 16);
            w0 = pack_h(d[i][0] + __uint_as_float(v.x), d[i][1] + __uint_as_float(v.y));
            w1 = pack_h(d[i][2] + __uint_as_float(v.z), d[i][3] + __uint_as_float(v.w));
        };
        if (half) {
            uint32_t a0, a1, b0, b1;
            both(3, a0, a1); both(4, b0, b1);
            const uint32_t o = cb + FT + 56 + 128 * (t >> 1) + 8 * g + 4 * (t & 1), q = cb + FT + 376 + 64 * t + 4 * g;
            sts32(o, a0); sts32(o + 64, a1); sts32(q, b0); sts32(q + 32, b1);
        } else {
            {
                uint32_t a[2], b[2], c[2], last = pack_h(k0, k0);
                both(0, a[0], a[1]); both(1, b[0], b[1]); both(2, c[0], c[1]);
                const uint32_t o = cb + TAB + 32 + 16 * lane;
                sts16(cb + TAB + 28, last);
#pragma unroll
                for (int h = 0; h < 4; h++) {
                    const uint32_t e = h < 2 ? b[h] : c[h - 2], pv = __shfl_sync(~0u, lane == 31 ? last : e, lane - 1);
                    if (h < 2) sts128(o + 512 * h, prmt(a[h], pv, 0x7610), prmt(a[h], 0, 0x1032), prmt(e, a[h], 0x7610), prmt(e, 0, 0x1032));
                    else sts128(o + 512 * h, prmt(pv, 0, 0x3232), prmt(e, pv, 0x7610), prmt(e, 0, 0x1032), prmt(e, 0, 0x3232));
                    last = e;
                }
                if (lane == 31) sts128(o + 1552, prmt(last, 0, 0x3232), prmt(last, 0, 0x3232), last & 0xFFFF0000u, 0u);
                __syncwarp();
            }
            near_lags(S, k, 64 * r + 16 * ((2 * k + (cbase >> 2) + (r >> 2)) & 3), eb);
            return;
        }
    }

    const int ph0 = pair & ~r, f0 = pair ? 32 * (bid & ~1) + 768 : 64 * bid;
    if (warp == 12) {
        if (elect()) {
            asm volatile("prefetch.tensormap [%0];" ::"l"(&m.u) : "memory");
            spin_until(t0, p.tn.t_tile);
            mbar_expect(S + B_RAW * 8, 256 * PITCH);
            asm volatile("cp.async.bulk.tensor.5d.shared::cluster.global.mbarrier::complete_tx::bytes [%0], [%1, {%3, 0, %4, 0, 0}], [%2];"
                         ::"r"(S + SM_RAW), "l"(&m.u), "r"(S + B_RAW * 8), "r"(cbase), "r"(4 * r) : "memory");
            uint32_t bar = S + B_FULL * 8, dst = S + SM_W, em = 0x1249400u, wm = ~(1u << p.tn.s0) << (p.tn.win0 + 2 - 2 * pair), wb = bar;
#pragma unroll 1
            for (int ph = ph0; ph < 3; ph += 1 + (pair & r)) {
                const int c0 = ph < 2 ? f0 : cbase, c1 = ph < 2 ? 0 : 576 * r;
#pragma unroll 1
                for (int n = 0; n < 576; n += 64) {
                    if (wm & 1) { mbar_wait(wb, 0); wb += 8; }
                    if (em & 1) mbar_wait(bar + 8 * (B_EMPTY - B_FULL), 0);
                    mbar_expect(bar, ph < 2 ? 8192 : 128 * 40);
                    tma2d(dst, m.w + ph, c0, c1 + n, bar);
                    bar += 8; em >>= 1; wm >>= 1;
                    dst = dst == S + SM_W + (NRING - 1) * 8192 ? S + SM_W : dst + 8192;
                }
            }
        }
        return;
    }

    if (warp == 15) {
        asm volatile("barrier.cluster.wait.aligned;" ::: "memory");
        sts32(S + SM_SKIP + 4 * j, 0u);
        const uint32_t ob = mapa(S, g);
        bar_sync(13, two ? 224 : 160);
        const uint4 ka = lds128(S + SM_B + 256 + 16 * lane), kb = lds128(S + SM_B + 768 + 16 * lane);
        uint32_t k0 = ka.x, k1 = ka.y, mine = 0, c = 0;
        int rank = lane;
#pragma unroll 1
        for (int pass = 0;; pass++) {
#pragma unroll 1
            for (int n = 0; n < (pass < 2 ? 4 : 8); n++) {
                const uint32_t a = __viaddmin_u32(k0, c, __viaddmin_u32(k1, c, ka.z + c)), b = __viaddmin_u32(ka.w, c, __viaddmin_u32(kb.x, c, kb.y + c));
                c += ~__reduce_min_sync(~0u, __vimin3_u32(a, b, __viaddmin_u32(kb.z, c, kb.w + c)));
                if ((pass < 2 ? t : j) == n) mine = c;
            }
            if (pass == 2) break;
            asm volatile("st.async.shared::cluster.mbarrier::complete_tx::bytes.b32 [%0], %1, [%2];" ::"r"(ob + SM_CAND + 128 * pass + 16 * r + 4 * t), "r"(~mine), "r"(ob + (B_TOP + pass) * 8) : "memory");
            mbar_wait_short(S + (B_TOP + pass) * 8);
            const uint32_t v = lds32(S + SM_CAND + 4 * lane);
            if (pass) {
                k0 = v; k1 = lds32(S + SM_CAND + 128 + 4 * lane); c = 0;
            } else {
                uint32_t cn[4] = {0, 0, 0, 0};
#pragma unroll 4
                for (int e = 0; e < 128; e += 16) {
                    const uint4 o = lds128(S + SM_CAND + e);
                    cn[0] += (o.x - v) >> 31; cn[1] += (o.y - v) >> 31; cn[2] += (o.z - v) >> 31; cn[3] += (o.w - v) >> 31;
                }
                const int rk = (cn[0] + cn[1]) + (cn[2] + cn[3]);
                if (!__any_sync(~0u, t == 3 && rk < 8)) { rank = rk; mine = ~v; break; }
            }
        }
        const uint32_t row = ~mine & 2047, ix = (row & 0xE0) * 8 + ((row >> 3) & 0xE0) + (row & 0x11) + ((row >> 2) & 2) + (row & 6) * 2;
        const uint32_t mr = __reduce_or_sync(~0u, rank == r ? row : 0u);
        if (elect()) {
            bulk_mc(S + SM_B + BP * r, p.u + mr * D_, 1152, S + B_XS * 8);
        }
        const bool own = rank < 8 && (ix >> 8) == r;
        const uint32_t m2 = 2 * mine, rb = (m2 ^ ((~(int)m2 >> 31) | 0x80000000u)) & 0xFFFF0000u;
        if (rank < 8) sts64(S + SM_SEL + 8 * rank, ix | rb, row);
        if (own) asm volatile("red.shared.or.b32 [%0], %1;" ::"r"(S + SM_SKIP + 4 * (ix & 7)), "r"(1u << ((ix >> 3) & 31)) : "memory");
        const int no = __popc(__ballot_sync(~0u, own));
        if (lane < 2) mbar_expect(S + (B_FIN + lane) * 8, lane ? 0 : no * (nch - 2) * 256);
    }

    if (svcwarp) {
        const uint32_t tag = ~epoch & 1;
        const int fw = warp & 3, i = tid & 127;
        asm volatile("barrier.cluster.wait.aligned;" ::: "memory");
        mbar_wait_short(S + B_RAW * 8);
#pragma unroll 1
        for (int it = 0; it < SPIN_LIMIT && (int)((sw.y ^ -tag) | (sw.w ^ -tag)) < 0; it++) sw = ld_rlx4(sp);
        sts64(S + SM_B + 256 + 8 * i, ~sw.y, ~sw.w);
        {
            const float r0 = 0.5f * rcpf(bf_hi(sw.x)), r1 = 0.5f * rcpf(bf_hi(sw.z));
            sts128f(S + SM_ST + 16 * (i & 0x71) + 32 * (i & 6) + 4 * (i & 8), r0, -bf_lo(sw.x) * r0, r1, -bf_lo(sw.z) * r1);
        }
        bar_sync(13, two ? 224 : 160);
        if (i == 0) {
            mbar_arrive(S + B_ST * 8);
            st_rlx(&p.s->ep[bid * 8], epoch + 1);
        }
    }
    if (svcwarp || (k >= pair && k < nch)) {
        {
            const int fw = svcwarp ? warp & 3 : k & 3, u0 = svcwarp ? 0 : p.tn.ns0, q0 = 2 * u0 + (fw >> 1);
            const uint32_t xb = mapa(S, g);
            uint32_t xd = xb + SM_CH + xslot(8 + 2 * r + (t >> 1), t & 1) + 512 * q0, xbar = xb + B_X * 8 + (svcwarp ? 0 : 8);
            uint32_t ra = S + SM_RAW + (64 * mi + j + 8 * q0) * PITCH, sa = S + SM_ST + 16 * t + 256 * q0;
            if (!svcwarp) mbar_wait(S + B_ST * 8, 0);
#pragma unroll 1
            for (int u = fw + u0; u < fw + (svcwarp ? p.tn.ns0 : 4); u++) {
                uint4 s[4];
#pragma unroll
                for (int e = 0; e < 4; e++) s[e] = lds128(sa + 64 * e);
#pragma unroll 1
                for (int n = u & 1; n < nch; n += 2) {
                    uint32_t a[4];
                    ldm4t(ra + 16 * n, a);
#pragma unroll
                    for (int e = 0; e < 4; e++)
                        a[e] = pack_h(fmaf(bf_lo(a[e]), __uint_as_float(s[e].x), __uint_as_float(s[e].y)), fmaf(bf_hi(a[e]), __uint_as_float(s[e].z), __uint_as_float(s[e].w)));
                    st_async4(xd + n * CH, a[0], a[1], a[2], a[3], xbar);
                }
                xd += 1024; ra += 16 * PITCH; sa += 512; xbar |= 8;
            }
        }
    }
    if (svcwarp) {
        const uint32_t tag = ~epoch & 1;
        const int fw = warp & 3, i = tid & 127;
        mbar_wait_short(S + B_SEL * 8);
        const uint2 sv = lds64(S + SM_SEL + 8 * j);
        const uint32_t bw = S + SM_B + BP * j + 16 * (i >> 3);
        {
            const uint32_t s1 = ld_rlx(&p.s->stat[sv.x & 2047]);
            const float ri = rcpf(bf_hi(s1));
            const uint32_t mu = prmt(s1, 0, 0x1010), hi = pack_bf(ri, ri), lo = pack_bf(ri - bf_lo(hi), ri - bf_lo(hi));
            auto nrm = [&](uint32_t x) { const uint32_t e = bsub(x, mu); return bfma(e, hi, bmul(e, lo)); };
            mbar_wait_short(S + B_XS * 8);
            uint4 v[5];
#pragma unroll
            for (int n = 0; n < 5; n++) v[n] = lds128(bw + 256 * n);
#pragma unroll
            for (int n = 0; n < 5; n++)
                if (n < 4 || fw < 2) sts128(bw + 256 * n, nrm(v[n].x), nrm(v[n].y), nrm(v[n].z), nrm(v[n].w));
        }
        const uint32_t tx = clk32();
        const int mt = (fw + 3) & 3;
        const uint32_t* const hp = p.s->h + 2304 * r + 4 * i;
        uint32_t bar = S + B_FULL * 8, of = 0;
        const uint32_t aa = S + SM_W + (8 * (mi >> 1) + j) * 128 + (((2 * mt + (mi & 1)) ^ j) << 4);
        float d[4][4];
#pragma unroll 1
        for (int ph = ph0;; ph++) {
            if (ph == 2) {
                bar_sync(15, 128);
                spin_until(tx, p.tn.da);
                uint4 v[5];
                const uint32_t tm = -tag;
#pragma unroll 1
                for (int it = 0; it < SPIN_LIMIT; it++) {
                    uint32_t bad = 0;
#pragma unroll
                    for (int n = 0; n < 5; n++) v[n] = ld_rlx4(hp + (n < 4 ? 512 * n : 1792));
#pragma unroll
                    for (int n = 0; n < 5; n++) bad |= lop_ne(v[n].x, v[n].z, tm);
                    if (!(bad & 1)) break;
                }
#pragma unroll
                for (int n = 0; n < 5; n++) sts128(bw + (n < 4 ? 256 * n : 896), v[n].x, v[n].y, v[n].z, v[n].w);
            }
            if (ph == ph0 || ph == 2) bar_sync(15, 128);
            if (ph == 2 && mt >= nch - 2) break;
#pragma unroll
            for (int e = 0; e < 4; e++) d[0][e] = d[1][e] = d[2][e] = d[3][e] = 0.f;
#pragma unroll 1
            for (int n = 0; n < 1152; n += 384) {
                uint32_t a[12][4], b[24];
                mbar_wait(bar + 8 * min(lane, 2), 0);
                __syncwarp();
#pragma unroll
                for (int e = 0; e < 12; e++) {
                    if (!(e & 1)) ldm4(S + SM_B + BP * j + 16 * mi + n + 32 * e, b[2 * e], b[2 * e + 1], b[2 * e + 2], b[2 * e + 3]);
                    ldm4t(aa + of + 2048 * e, a[e]);
                }

#pragma unroll
                for (int e = 0; e < 12; e++) mma_bf(d[e & 3], a[e][0], a[e][1], a[e][2], a[e][3], b[2 * e], b[2 * e + 1]);
                if (lane == 0) mbar_arrive(min(bar + (B_EMPTY + NRING - B_FULL) * 8, S + 63 * 8));
                bar += 24;
                of = of == 8192 * (NRING - 3) ? 0 : of + 24576;
            }
#pragma unroll
            for (int e = 0; e < 4; e++) d[0][e] = (d[0][e] + d[1][e]) + (d[2][e] + d[3][e]);
            uint32_t k0 = pack_bf(d[0][0], d[0][1]), k1 = pack_bf(d[0][2], d[0][3]);
            const uint32_t ea = SM_FIN + 6144 + 8 * i, eb = B_UP * 8;
            if (ph == 0) {
                const uint32_t ob = mapa(S, r & ~pair);
                st_async2(ob + ea, k0, k1, ob + eb);
                ph += pair;
                continue;
            }
            if (ph == 1) {
                k0 = pack_bf(silu_half(0.5f * bf_lo(k0)), silu_half(0.5f * bf_hi(k0))); k1 = pack_bf(silu_half(0.5f * bf_lo(k1)), silu_half(0.5f * bf_hi(k1)));
                mbar_wait_short((S + eb) | (k0 & k1 & p.tn.zero));
                const uint2 v = lds64(S + ea);
                k0 = bmul(k0, v.x); k1 = bmul(k1, v.y);
                __syncwarp();
            }
            k0 = movm(k0); k1 = movm(k1);
            if (ph == 2) {
                const uint32_t ob = mapa(S, (__shfl_sync(~0u, sv.x, g) >> 8) & 7);
                st_async2(ob + SM_FIN + 768 * g + 96 * r + 32 * mt + 8 * t, k0, k1, ob + B_FIN * 8);
                break;
            }
            const uint32_t o = __shfl_xor_sync(~0u, (lane & 1) ? k0 : k1, 1);
            st_rlx2(p.s->h + 4 * f0 + 64 * mt + 31 * (lane & 1) + lane, (((lane & 1) ? o : k0) & ~1u) | tag, (lane & 1) ? k1 : o);
        }
        const int l = min(lane, 4 * nch - 1);
        int n = fw;
#pragma unroll 1
        for (uint32_t own = __ballot_sync(~0u, ((sv.x >> 8) & 7) == r) & 255; own; own &= own - 1) {
            if (n-- & 3) continue;
            const int tk = __ffs(own) - 1;
            const uint2 e = lds64(S + SM_SEL + 8 * tk), st = lds64(S + SM_ST + 8 * (e.x & 0xE3) + 16 * (e.x & 12) + 2 * (e.x & 16));
            const uint32_t ix = e.x, x = lds32(S + SM_RAW + (16 * (ix & 12) + ((ix >> 2) & 60) + (ix & 3)) * PITCH + 4 * l);
            const uint32_t yb = S + SM_CH + YIN + (l >> 2) * CH + 16 * (ix & 0xE0) + 128 * (l & 3) + 16 * (((ix >> 3) ^ ((l >> 1) + (cbase >> 2))) & 3) + 2 * (ix & 7);
            const float sg = 0.5f * sigm(bf_hi(ix));
            const uint32_t hx = pack_bf(fmaf(bf_lo(x), __uint_as_float(st.x), __uint_as_float(st.y)), fmaf(bf_hi(x), __uint_as_float(st.x), __uint_as_float(st.y))), sg2 = pack_bf(sg, sg);
            mbar_wait((S + B_FIN * 8) | (hx & sg2 & p.tn.zero), 0);
            float a[2] = {0.f, 0.f}, b[2] = {0.f, 0.f};
#pragma unroll
            for (int q = 0; q < 8; q++) {
                const uint32_t v = lds32(S + SM_FIN + 768 * tk + 96 * q + 4 * (l & 24) + 8 * (l & 3) + (l & 4));
                a[q & 1] += bf_lo(v); b[q & 1] += bf_hi(v);
            }
            const uint32_t hv = badd(hx, bmul(pack_bf(a[0] + a[1], b[0] + b[1]), sg2)), gt = pack_bf(silu_half(bf_lo(hv)), silu_half(bf_hi(hv)));
            mbar_wait((S + B_Y * 8 + ((ix >> 2) & 56)) | (gt & p.tn.zero), 0);
            *(uint32_t*)(p.out + e.y * D_ + cbase + 2 * l) = bfma(lds16(yb) | (lds16(yb + 64) << 16), gt, x);
        }
        return;
    }

    mbar_wait(S + B_X * 8, 0);
    if (k < nch) {
        const uint32_t cb = S + SM_CH + k * CH, bx = cb + BOX + 16;
        bar_sync(1 + k, 64);
        float u[4][4], v[4][4], w[4][4];
#pragma unroll
        for (int i = 0; i < 4; i++) v[i][0] = v[i][1] = v[i][2] = v[i][3] = w[i][0] = w[i][1] = w[i][2] = w[i][3] = 0.f;
        uint2 T4[10];
        const uint32_t ta = cb + FT + 4 * (g - t);
#pragma unroll
        for (int e = 0; e < 10; e++) T4[e] = lds64(ta + 24 + 32 * e + 4 * (g - t));
        const uint32_t tb = prmt(lds32(cb + FT + 308), 0, g == 2 * t ? 0x4432 : (g == 2 * t + 1 ? 0x3244 : 0x4444));
        const uint32_t a0 = bx + 576 * (j & 1) + 16 * (j >> 1), a4 = a0 + (mi == 1 ? 1152 : (mi == 2 ? 1136 : 0));
        const uint32_t a8 = a0 + 2304 + 1152 * (mi & 1) + 64 * (mi >> 1), at = bx + 4608 + 576 * (mi & 1) + 128 * (mi >> 1) + 16 * j;
        const uint32_t hb = bx + (lane < 2 ? 1152 + 576 * lane : 2896), o = bx + 16 * lane;
        uint32_t xi = cb + xslot(8 + lane, 0), xp = cb + xslot(7 + lane, 0), hs = cb + XX;
#pragma unroll 1
        for (int n = 9; n > 0; n -= 4) {
            {
                const uint4 hv = lds128(hs);
                hs = hb + 496;
                const uint2 v0 = lds64(xp + 8);
                const uint4 v1 = lds128(xp ^ 32), v2 = lds128(xi), v3 = lds128(xi ^ 32);
                xi += 1024; xp += 1024;
                __syncwarp();
                if (lane < 3) sts128(hb - 16, hv.x, hv.y, hv.z, hv.w);
                const uint32_t P[13] = {v0.x, v0.y, v1.x, v1.y, v1.z, v1.w, v2.x, v2.y, v2.z, v2.w, v3.x, v3.y, v3.z};
                uint32_t Q[12], s2[12], s4[10], b3[11], b5[9];
#pragma unroll
                for (int e = 0; e < 12; e++) { Q[e] = prmt(P[e], P[e + 1], 0x5432); s2[e] = hadd(P[e], Q[e]); }
#pragma unroll
                for (int e = 0; e < 11; e++) b3[e] = hadd(Q[e], s2[e + 1]);
#pragma unroll
                for (int e = 0; e < 10; e++) s4[e] = hadd(s2[e], s2[e + 1]);
#pragma unroll
                for (int e = 0; e < 9; e++) b5[e] = hadd(s4[e + 1], P[e + 3]);
                sts128(o, b3[3], b3[4], b3[5], b3[6]);
                sts128(o + 1152, b3[7], b3[8], b3[9], b3[10]);
                sts128(o + 576, b5[0], b5[1], b5[2], b5[3]);
                sts128(o + 1728, b5[4], b5[5], b5[6], b5[7]);
                if (n > 4) {
                    sts128(o + 4608, s2[4], s2[5], s2[6], s2[7]);
                    sts128(o + 5184, s2[8], s2[9], s2[10], s2[11]);
                    sts128(o + 2304, hadd(b3[0], s4[2]), hadd(b3[1], s4[3]), hadd(b3[2], s4[4]), hadd(b3[3], s4[5]));
                    sts128(o + 3456, hadd(b3[4], s4[6]), hadd(b3[5], s4[7]), hadd(b3[6], s4[8]), hadd(b3[7], s4[9]));
                    sts128(o + 4032, hadd(s4[0], b5[1]), hadd(s4[1], b5[2]), hadd(s4[2], b5[3]), hadd(s4[3], b5[4]));
                    sts128(o + 2896, hadd(s4[4], b5[5]), hadd(s4[5], b5[6]), hadd(s4[6], b5[7]), hadd(s4[7], b5[8]));
                }
                __syncwarp();
            }
            uint32_t A[8][4];
#pragma unroll
            for (int e = 0; e < 8; e++) ldm4t(a4 + 64 * e, A[e]);
#pragma unroll
            for (int e = 0; e < 8; e++)
#pragma unroll
                for (int b = 3; b >= e / 2; b--) {
                    const uint2 T = T4[2 * (b - e / 2) + 1 - (e & 1)];
                    if (e == 0) mma_hc(u[b], v[b], A[e][0], A[e][1], A[e][2], A[e][3], T.x, T.y);
                    else mma_h(u[b], A[e][0], A[e][1], A[e][2], A[e][3], T.x, T.y);
                }
            if (n == 9) mbar_wait_short(S + (B_X + 1) * 8);
#pragma unroll
            for (int e = 0; e < 2; e++)
                stm4t(cb + TAB + 2304 - 256 * n + 512 * e + 16 * lane, pack_h(u[2 * e][0], u[2 * e][1]), pack_h(u[2 * e][2], u[2 * e][3]),
                      pack_h(u[2 * e + 1][0], u[2 * e + 1][1]), pack_h(u[2 * e + 1][2], u[2 * e + 1][3]));
            __syncwarp();
            sts32v(S + SM_PROG + 4 * k, n > 1 ? n : p.tn.tail);
            if (n == 1) break;
            uint32_t C[4][4], E[2][4], T8[16];
#pragma unroll
            for (int e = 0; e < 4; e++) ldm4t(a8 + 128 * e, C[e]);
#pragma unroll
            for (int e = 0; e < 2; e++) ldm4t(at + 256 * e, E[e]);
#pragma unroll
            for (int e = 0; e < 8; e++) T8[e] = lds32(ta + 376 + 32 * (e >> 1) - 16 * (e & 1));
#pragma unroll
            for (int e = 7; e >= 0; e--)
#pragma unroll
                for (int b = 0; b <= e / 2; b++) {
                    const uint2 T = T4[2 * (4 + b - e / 2) + 1 - (e & 1)];
                    if (e == 7) mma_hc(v[b], w[b], A[e][0], A[e][1], A[e][2], A[e][3], T.x, T.y);
                    else mma_h(v[b], A[e][0], A[e][1], A[e][2], A[e][3], T.x, T.y);
                }
#pragma unroll
            for (int e = 3; e >= 0; e--) {
                mma_h8(v[e], E[e >> 1][2 * (e & 1)], E[e >> 1][2 * (e & 1) + 1], tb);
#pragma unroll
                for (int b = 3; b >= e; b--) mma_h(v[b], C[e][0], C[e][1], C[e][2], C[e][3], T8[2 * (b - e)], T8[2 * (b - e) + 1]);
            }
            if (n == 9) {
#pragma unroll
                for (int e = 8; e < 16; e++) T8[e] = lds32(ta + 376 + 32 * (e >> 1) - 16 * (e & 1));
#pragma unroll
                for (int e = 3; e >= 0; e--)
#pragma unroll
                    for (int b = 0; b < 4; b++) mma_h(w[b], C[e][0], C[e][1], C[e][2], C[e][3], T8[2 * (4 + b - e)], T8[2 * (4 + b - e) + 1]);
            }
        }
    }

  {
    int lane;
    asm volatile("mov.u32 %0, %%laneid;" : "=r"(lane));
    const int g = lane >> 2, t = lane & 3, mi = lane >> 3, j = lane & 7, sh = (cbase >> 3) & 1;
    mbar_wait_short(S + B_SEL * 8);
    if (k < 2 * nch - 4) {
        const int q0 = k & 1, kk = (k & 6) - sh;
        uint32_t xa = S + SM_RAW + (16 * (g & 4) + (g & 3) + 8 * q0) * PITCH + 8 * t + 16 * kk, sa = S + SM_ST + 16 * (g & 4) + 8 * (g & 3) + 256 * q0, bar = S + (B_Y + q0) * 8;
        uint32_t ya = S + SM_CH + YIN + ((j >> 2) + kk) * CH + 128 * (j & 2) + 128 * (mi & 1) + 64 * (j & 1) + 16 * ((mi >> 1) ^ (j >> 1)) + 512 * q0;
        uint32_t sk = (unsigned)(kk + (t >> 1)) < (unsigned)nch ? lds32(S + SM_SKIP + 4 * g) >> (4 * q0) : ~0u;
        char* o = (char*)p.out + ((256 * q0 + 32 * r + 4 * (g & 2) + 2 * (g >> 2) + (g & 1)) * D_ + cbase + 8 * kk + 4 * t) * 2;
#pragma unroll 1
        for (int n = 0; n < 4; n++) {
            uint2 x[4];
            uint32_t gt[8], y[2][4];
#pragma unroll
            for (int e = 0; e < 4; e++) {
                x[e] = lds64(xa + (128 * (e & 1) + 2 * (e & 2)) * PITCH);
                const uint2 s = lds64(sa + 128 * (e & 1) + 16 * (e & 2));
                const float a = __uint_as_float(s.x), b = __uint_as_float(s.y);
                gt[2 * e] = pack_bf(silu_half(fmaf(bf_lo(x[e].x), a, b)), silu_half(fmaf(bf_hi(x[e].x), a, b)));
                gt[2 * e + 1] = pack_bf(silu_half(fmaf(bf_lo(x[e].y), a, b)), silu_half(fmaf(bf_hi(x[e].y), a, b)));
            }
            mbar_wait(bar | (((gt[0] | gt[1] | gt[2]) | (gt[3] | gt[4] | gt[5]) | (gt[6] | gt[7])) & p.tn.zero), 0);
            ldm4t(ya, y[0]);
            ldm4t(ya ^ 32, y[1]);
#pragma unroll
            for (int e = 0; e < 4; e++)
                asm volatile("{.reg .pred p; setp.eq.u32 p, %3, 0;\n@p st.global.v2.u32 [%0], {%1, %2};}" ::"l"(o + (8 * (e & 1) + 16 * (e & 2)) * D_),
                             "r"(bfma(y[e >> 1][2 * (e & 1)], gt[2 * e], x[e].x)), "r"(bfma(y[e >> 1][2 * (e & 1) + 1], gt[2 * e + 1], x[e].y)), "r"(sk & (1 << e)) : "memory");
            xa += 16 * PITCH; sa += 512; ya += 1024; bar += 16; sk >>= 8; o += 1024 * D_;
        }
    }
  }
}

typedef CUresult (*EncodeFn)(CUtensorMap*, CUtensorMapDataType, cuuint32_t, void*, const cuuint64_t*, const cuuint64_t*, const cuuint32_t*,
                             const cuuint32_t*, CUtensorMapInterleave, CUtensorMapSwizzle, CUtensorMapL2promotion, CUtensorMapFloatOOBfill);

static void make2d(EncodeFn enc, CUtensorMap* m, const void* base, uint64_t cols, uint64_t rows, uint32_t bc = 64) {
    cuuint64_t gd[2] = {cols, rows};
    cuuint64_t gs[1] = {cols * 2};
    cuuint32_t bd[2] = {bc, 64}, es[2] = {1, 1};
    enc(m, CU_TENSOR_MAP_DATA_TYPE_BFLOAT16, 2, const_cast<void*>(base), gd, gs, bd, es, CU_TENSOR_MAP_INTERLEAVE_NONE, CU_TENSOR_MAP_SWIZZLE_128B,
        CU_TENSOR_MAP_L2_PROMOTION_L2_128B, CU_TENSOR_MAP_FLOAT_OOB_FILL_NONE);
}

static void make5d(EncodeFn enc, CUtensorMap* m, const void* base, uint32_t cols, CUtensorMapSwizzle sw) {
    cuuint64_t gd[5] = {D_, 2, 32, 8, 4};
    cuuint64_t gs[4] = {D_ * 2, D_ * 16, D_ * 512, D_ * 4};
    cuuint32_t bd[5] = {cols, 2, 4, 8, 4}, es[5] = {1, 1, 1, 1, 1};
    enc(m, CU_TENSOR_MAP_DATA_TYPE_BFLOAT16, 5, const_cast<void*>(base), gd, gs, bd, es, CU_TENSOR_MAP_INTERLEAVE_NONE, sw,
        CU_TENSOR_MAP_L2_PROMOTION_NONE, CU_TENSOR_MAP_FLOAT_OOB_FILL_NONE);
}

static Tune g_tune = {2200, 231, 2, 2, 4, 800, 4200, 2, 0};

static int max_clusters() {
    cudaFuncSetAttribute(fused_kernel, cudaFuncAttributeMaxDynamicSharedMemorySize, SM_TOTAL);
    cudaLaunchConfig_t cfg = {};
    cudaLaunchAttribute at[1];
    at[0].id = cudaLaunchAttributeClusterDimension;
    at[0].val.clusterDim.x = 8; at[0].val.clusterDim.y = 1; at[0].val.clusterDim.z = 1;
    cfg.gridDim = dim3(NCTA); cfg.blockDim = dim3(NTHREADS); cfg.dynamicSmemBytes = SM_TOTAL; cfg.attrs = at; cfg.numAttrs = 1;
    int n = 0;
    if (cudaOccupancyMaxActiveClusters(&n, fused_kernel, &cfg) != cudaSuccess) { cudaGetLastError(); n = 0; }
    return n;
}

static bool launch(void* const* d_in, void* d_out) {
    static EncodeFn enc = nullptr;
    static Scratch* gs = nullptr;
    if (!enc) {
        void* fn = nullptr;
        cudaDriverEntryPointQueryResult qr;
        cudaGetDriverEntryPoint("cuTensorMapEncodeTiled", &fn, cudaEnableDefault, &qr);
        enc = (EncodeFn)fn;
        cudaFuncSetAttribute(fused_kernel, cudaFuncAttributeMaxDynamicSharedMemorySize, SM_TOTAL);
        cudaGetSymbolAddress((void**)&gs, g_s);
    }
    Hot p;
    Maps m;
    auto in = [&](int i) { return (const __nv_bfloat16*)d_in[i]; };
    bool ok = true;
    auto off = [&](const void* q) {
        const long long d = (const char*)q - (const char*)d_in[0];
        ok = ok && d / 256 * 256 == d && (int)(d / 256) == d / 256;
        return (int)(d / 256);
    };
    p.u = in(0); p.are = off(in(1)); p.aim = off(in(2)); p.bre = off(in(3)); p.bim = off(in(4)); p.cre = off(in(5)); p.cim = off(in(6));
    p.logdt = off(in(7)); p.dskip = off(in(8)); p.wr = off(in(10)); p.ep = off(gs->ep);
    if (!ok) return false;
    p.out = (__nv_bfloat16*)d_out;
    p.tn = g_tune;
    p.s = gs;
    make2d(enc, &m.w[0], in(12), F_, D_);
    make2d(enc, &m.w[1], in(11), F_, D_);
    make2d(enc, &m.w[2], in(13), D_, F_, 40);
    make5d(enc, &m.u, in(0), 40, CU_TENSOR_MAP_SWIZZLE_NONE);
    fused_kernel<<<NCTA, NTHREADS, SM_TOTAL>>>(p, m);
    return true;
}

}

namespace v2 {

constexpr int L_ = 2048, D_ = 576, F_ = 4608;
constexpr int NDOWN = 72, NMAIN = 128, NCTA = 132, NTHREADS = 512;
constexpr int SPIN_LIMIT = 1 << 16;
constexpr uint32_t SLOT_FREE = 0x7FFFABCDu;

constexpr int SM_PART = 544;
constexpr int SM_RED = SM_PART;
constexpr int SM_STA = 2080;
constexpr int SM_ONES = 2176;
constexpr int SM_KINF = 2192;
constexpr int SM_RP = 2272;
constexpr int SM_XS = 2704;
constexpr int KR_STRIDE = 1296;
constexpr int SM_X0 = 12080, X0_STRIDE = 4512, X0_ODD = 2240;
constexpr int SM_KT = 30128, KT_STRIDE = 3584, KT_P4 = 2144, KT_P8 = 2896;
constexpr int SM_FAR = 44544, FAR_STRIDE = 11328;
constexpr int FB5 = 0, FB3 = 3328, FB9E = 6656, FB9O = 7824, FB7E = 8992, FB7O = 10160;
constexpr int SM_ROWS = SM_FAR, ROW_STRIDE = 1168;
constexpr int SM_STG = SM_FAR + 19968;
constexpr int KG_SCR = 3072;
constexpr int SM_EX = 89856;
constexpr int EX_KT = SM_EX + X0_STRIDE, EX_FAR = EX_KT + KT_STRIDE, EX_HAND = 109312;
constexpr int SM_W_DOWN = 90112, SM_W_BIG = 121856, STAGE = 6144;
constexpr int SM_W_LAST = 12288;
constexpr int SM_TOTAL = 232448;
constexpr int SM_EPOCH = 2528, SM_SKIP = 2536;
static_assert(SM_STG + 8 * KG_SCR <= SM_EX && SM_STG % 128 == 0 && EX_HAND % 128 == 0 && EX_FAR + FAR_STRIDE <= EX_HAND && EX_HAND + 12288 <= SM_W_BIG, "scratch");

enum { B_ROWS = 0, B_KG, B_X0, B_X1, B_BOX  , B_TAB, B_EM = 6, B_SP = 10, B_OUT = 14, B_H = 15, B_RED = 16, B_TAB1 = 17, B_XS = 18, B_GX = 19, B_YIN = 22, B_P1 = 26, B_FD, B_GU = 28, B_W = 34, B_COUNT = 58 };

struct Tune { short f_start, f_t3, w2, w2b, w3, t_xs, t_svc, t_marg, f_t2, w1, zero, pad; };

struct Scratch {
    uint32_t x[144 * 4096];
    uint32_t y[128 * 4608];
    uint32_t h[2][F_ * 4];
    uint32_t key[L_];
    uint32_t stat[L_];
    uint32_t sel[4][32];
    uint32_t cnt[17 * 32];
};
__device__ __align__(1024) Scratch g_s;

struct Hot {
    const __nv_bfloat16* u;
    Scratch* s;
    const __nv_bfloat16 *wr, *are, *aim, *bre, *bim, *cre, *cim, *logdt;
    Tune tn;
    const __nv_bfloat16 *dskip, *pwg, *pwu, *pwd;
    __nv_bfloat16* out;
};
struct Maps { CUtensorMap wg, wu, wd; };

__device__ __forceinline__ uint32_t smem_u32(const void* p) { return (uint32_t)__cvta_generic_to_shared(p); }
__device__ __forceinline__ void mbar_init(uint32_t b, int c) { asm volatile("mbarrier.init.shared::cta.b64 [%0], %1;" ::"r"(b), "r"(c) : "memory"); }
__device__ __forceinline__ void mbar_expect(uint32_t b, int bytes) { asm volatile("mbarrier.arrive.expect_tx.shared::cta.b64 _, [%0], %1;" ::"r"(b), "r"(bytes) : "memory"); }
__device__ __forceinline__ void mbar_arrive(uint32_t b) { asm volatile("mbarrier.arrive.shared::cta.b64 _, [%0];" ::"r"(b) : "memory"); }
__device__ __forceinline__ bool elect() { uint32_t d; asm volatile("{.reg .pred p; elect.sync _|p, 0xffffffff; selp.u32 %0,1,0,p;}" : "=r"(d)); return d; }
__device__ __forceinline__ bool mbar_test(uint32_t b, int par) {
    uint32_t d;
    asm volatile("{.reg .pred p; mbarrier.test_wait.parity.shared::cta.b64 p, [%1], %2; selp.u32 %0,1,0,p;}" : "=r"(d) : "r"(b), "r"(par) : "memory");
    return d;
}
#define WAIT_LOOP(ins) "{\n.reg .pred p;\n.reg .u32 n;\nmov.u32 n, 0;\nLW:\n" ins " p, [%0], %1;\n@p bra LD;\nadd.u32 n, n, 1;\nsetp.lt.u32 p, n, 16384;\n@p bra LW;\nLD:\n}"
__device__ __forceinline__ void mbar_wait(uint32_t b, int par) { asm volatile(WAIT_LOOP("mbarrier.try_wait.parity.shared::cta.b64")::"r"(b), "r"(par) : "memory"); }
__device__ __forceinline__ uint32_t mapa(uint32_t a, uint32_t rank) { uint32_t d; asm("mapa.shared::cluster.u32 %0, %1, %2;" : "=r"(d) : "r"(a), "r"(rank)); return d; }
__device__ __forceinline__ void bulk_g2s(uint32_t dst, const void* src, int bytes, uint32_t bar) {
    asm volatile("cp.async.bulk.shared::cluster.global.mbarrier::complete_tx::bytes [%0], [%1], %2, [%3];" ::"r"(dst), "l"(src), "r"(bytes), "r"(bar) : "memory");
}
__device__ __forceinline__ void tma2d(uint32_t dst, const CUtensorMap* m, int c0, int c1, uint32_t bar) {
    asm volatile("cp.async.bulk.tensor.2d.shared::cluster.global.mbarrier::complete_tx::bytes [%0], [%1, {%3, %4}], [%2];" ::"r"(dst), "l"(m), "r"(bar), "r"(c0), "r"(c1) : "memory");
}
__device__ __forceinline__ void pf_tmap(const CUtensorMap* m) { asm volatile("prefetch.tensormap [%0];" ::"l"(m) : "memory"); }
__device__ __forceinline__ void bar_sync(int id, int n) { asm volatile("bar.sync %0, %1;" ::"r"(id), "r"(n) : "memory"); }
__device__ __forceinline__ uint4 ld_rlx4(const void* p) { uint4 v; asm volatile("ld.relaxed.gpu.global.v4.u32 {%0,%1,%2,%3}, [%4];" : "=r"(v.x), "=r"(v.y), "=r"(v.z), "=r"(v.w) : "l"(p) : "memory"); return v; }
__device__ __forceinline__ uint32_t ld_rlx(const void* p) { uint32_t v; asm volatile("ld.relaxed.gpu.global.u32 %0, [%1];" : "=r"(v) : "l"(p) : "memory"); return v; }
__device__ __forceinline__ void st_rlx(void* p, uint32_t v) { asm volatile("st.relaxed.gpu.global.u32 [%0], %1;" ::"l"(p), "r"(v) : "memory"); }
__device__ __forceinline__ uint32_t lds32(uint32_t a) { uint32_t v; asm volatile("ld.shared.u32 %0, [%1];" : "=r"(v) : "r"(a) : "memory"); return v; }
__device__ __forceinline__ uint32_t lds32v(uint32_t a) { uint32_t v; asm volatile("ld.volatile.shared.u32 %0, [%1];" : "=r"(v) : "r"(a) : "memory"); return v; }
__device__ __forceinline__ uint4 lds128v(uint32_t a) { uint4 v; asm volatile("ld.volatile.shared.v4.u32 {%0,%1,%2,%3}, [%4];" : "=r"(v.x), "=r"(v.y), "=r"(v.z), "=r"(v.w) : "r"(a) : "memory"); return v; }
__device__ __forceinline__ uint32_t lds16(uint32_t a) { uint16_t v; asm volatile("ld.shared.u16 %0, [%1];" : "=h"(v) : "r"(a) : "memory"); return v; }
__device__ __forceinline__ uint2 lds64(uint32_t a) { uint2 v; asm volatile("ld.shared.v2.u32 {%0,%1}, [%2];" : "=r"(v.x), "=r"(v.y) : "r"(a) : "memory"); return v; }
__device__ __forceinline__ uint4 lds128(uint32_t a) { uint4 v; asm volatile("ld.shared.v4.u32 {%0,%1,%2,%3}, [%4];" : "=r"(v.x), "=r"(v.y), "=r"(v.z), "=r"(v.w) : "r"(a) : "memory"); return v; }
__device__ __forceinline__ void sts16(uint32_t a, uint32_t v) { asm volatile("st.shared.u16 [%0], %1;" ::"r"(a), "h"((uint16_t)v) : "memory"); }
__device__ __forceinline__ void sts32(uint32_t a, uint32_t v) { asm volatile("st.shared.u32 [%0], %1;" ::"r"(a), "r"(v) : "memory"); }
__device__ __forceinline__ void sts64(uint32_t a, uint32_t x, uint32_t y) { asm volatile("st.shared.v2.u32 [%0], {%1,%2};" ::"r"(a), "r"(x), "r"(y) : "memory"); }
__device__ __forceinline__ void sts128(uint32_t a, uint32_t x, uint32_t y, uint32_t z, uint32_t w) { asm volatile("st.shared.v4.u32 [%0], {%1,%2,%3,%4};" ::"r"(a), "r"(x), "r"(y), "r"(z), "r"(w) : "memory"); }
__device__ __forceinline__ void st_async32(uint32_t a, uint32_t v, uint32_t bar) {
    asm volatile("st.async.shared::cluster.mbarrier::complete_tx::bytes.b32 [%0], %1, [%2];" ::"r"(a), "r"(v), "r"(bar) : "memory");
}
__device__ __forceinline__ void ldm4(uint32_t a, uint32_t& r0, uint32_t& r1, uint32_t& r2, uint32_t& r3) {
    asm volatile("ldmatrix.sync.aligned.m8n8.x4.shared.b16 {%0,%1,%2,%3}, [%4];" : "=r"(r0), "=r"(r1), "=r"(r2), "=r"(r3) : "r"(a) : "memory");
}
__device__ __forceinline__ void ldm4t(uint32_t a, uint32_t& r0, uint32_t& r1, uint32_t& r2, uint32_t& r3) {
    asm volatile("ldmatrix.sync.aligned.m8n8.x4.trans.shared.b16 {%0,%1,%2,%3}, [%4];" : "=r"(r0), "=r"(r1), "=r"(r2), "=r"(r3) : "r"(a) : "memory");
}
__device__ __forceinline__ void ldm2(uint32_t a, uint32_t& r0, uint32_t& r1) {
    asm volatile("ldmatrix.sync.aligned.m8n8.x2.shared.b16 {%0,%1}, [%2];" : "=r"(r0), "=r"(r1) : "r"(a) : "memory");
}
__device__ __forceinline__ void stm4(uint32_t a, uint32_t r0, uint32_t r1, uint32_t r2, uint32_t r3) {
    asm volatile("stmatrix.sync.aligned.m8n8.x4.shared.b16 [%0], {%1,%2,%3,%4};" ::"r"(a), "r"(r0), "r"(r1), "r"(r2), "r"(r3) : "memory");
}
__device__ __forceinline__ void mma_bf(float& c0, float& c1, float& c2, float& c3, uint32_t a0, uint32_t a1, uint32_t a2, uint32_t a3, uint32_t b0, uint32_t b1) {
    asm volatile("mma.sync.aligned.m16n8k16.row.col.f32.bf16.bf16.f32 {%0,%1,%2,%3},{%4,%5,%6,%7},{%8,%9},{%0,%1,%2,%3};"
                 : "+f"(c0), "+f"(c1), "+f"(c2), "+f"(c3) : "r"(a0), "r"(a1), "r"(a2), "r"(a3), "r"(b0), "r"(b1));
}
__device__ __forceinline__ void mma_bf(float (&c)[4], uint32_t a0, uint32_t a1, uint32_t a2, uint32_t a3, uint32_t b0, uint32_t b1) { mma_bf(c[0], c[1], c[2], c[3], a0, a1, a2, a3, b0, b1); }
__device__ __forceinline__ void mma_h(float (&c)[4], uint32_t a0, uint32_t a1, uint32_t a2, uint32_t a3, uint32_t b0, uint32_t b1) {
    asm volatile("mma.sync.aligned.m16n8k16.row.col.f32.f16.f16.f32 {%0,%1,%2,%3},{%4,%5,%6,%7},{%8,%9},{%0,%1,%2,%3};"
                 : "+f"(c[0]), "+f"(c[1]), "+f"(c[2]), "+f"(c[3]) : "r"(a0), "r"(a1), "r"(a2), "r"(a3), "r"(b0), "r"(b1));
}
__device__ __forceinline__ void mma_bf8(float (&c)[4], uint32_t a0, uint32_t a1, uint32_t b0) {
    asm volatile("mma.sync.aligned.m16n8k8.row.col.f32.bf16.bf16.f32 {%0,%1,%2,%3},{%4,%5},{%6},{%0,%1,%2,%3};"
                 : "+f"(c[0]), "+f"(c[1]), "+f"(c[2]), "+f"(c[3]) : "r"(a0), "r"(a1), "r"(b0));
}
__device__ __forceinline__ uint32_t pack_bf(float lo, float hi) { uint32_t r; asm("cvt.rn.bf16x2.f32 %0, %1, %2;" : "=r"(r) : "f"(hi), "f"(lo)); return r; }
__device__ __forceinline__ uint32_t pack_h(float lo, float hi) { uint32_t r; asm("cvt.rn.f16x2.f32 %0, %1, %2;" : "=r"(r) : "f"(hi), "f"(lo)); return r; }
__device__ __forceinline__ float bf_lo(uint32_t w) { return __uint_as_float(w << 16); }
__device__ __forceinline__ float bf_hi(uint32_t w) { return __uint_as_float(w & 0xFFFF0000u); }
__device__ __forceinline__ float bf_round(float x) { return bf_lo(pack_bf(x, 0.f)); }
__device__ __forceinline__ uint32_t badd(uint32_t a, uint32_t b) { uint32_t r; asm("add.rn.bf16x2 %0, %1, %2;" : "=r"(r) : "r"(a), "r"(b)); return r; }
__device__ __forceinline__ uint32_t bsub(uint32_t a, uint32_t b) { uint32_t r; asm("sub.rn.bf16x2 %0, %1, %2;" : "=r"(r) : "r"(a), "r"(b)); return r; }
__device__ __forceinline__ uint32_t bmul(uint32_t a, uint32_t b) { uint32_t r; asm("mul.rn.bf16x2 %0, %1, %2;" : "=r"(r) : "r"(a), "r"(b)); return r; }
__device__ __forceinline__ uint32_t bfma(uint32_t a, uint32_t b, uint32_t c) { uint32_t r; asm("fma.rn.bf16x2 %0, %1, %2, %3;" : "=r"(r) : "r"(a), "r"(b), "r"(c)); return r; }
__device__ __forceinline__ uint32_t prmt(uint32_t a, uint32_t b, uint32_t s) { uint32_t r; asm("prmt.b32 %0, %1, %2, %3;" : "=r"(r) : "r"(a), "r"(b), "r"(s)); return r; }
__device__ __forceinline__ float ex2f(float x) { float r; asm("ex2.approx.ftz.f32 %0, %1;" : "=f"(r) : "f"(x)); return r; }
__device__ __forceinline__ float rcpf(float x) { float r; asm("rcp.approx.ftz.f32 %0, %1;" : "=f"(r) : "f"(x)); return r; }
__device__ __forceinline__ float silu_f(float x) { return x * rcpf(1.f + ex2f(-1.4426950408889634f * x)); }
__device__ __forceinline__ uint32_t norm2(uint32_t x, uint32_t m, uint32_t hi, uint32_t lo) { uint32_t d = bsub(x, m); return bfma(d, hi, bmul(d, lo)); }
__device__ __forceinline__ uint32_t clk32() { uint32_t c; asm volatile("mov.u32 %0, %%clock;" : "=r"(c)); return c; }
__device__ __forceinline__ void spin_until(uint32_t t0, int dt) {
#pragma unroll 1
    while ((int)(clk32() - t0) < dt) __nanosleep(32);
}
__device__ __forceinline__ float sqrt_ap(float x) { float r; asm("sqrt.approx.ftz.f32 %0, %1;" : "=f"(r) : "f"(x)); return r; }

__device__ __forceinline__ void cp16(uint32_t dst, const void* src) { asm volatile("cp.async.cg.shared.global [%0], [%1], 16;" ::"r"(dst), "l"(src) : "memory"); }
__device__ __forceinline__ void pf_l2(const void* p) { asm volatile("cp.async.bulk.prefetch.L2.global [%0], 16;" ::"l"(p) : "memory"); }
__device__ __forceinline__ void bulk_s2g(void* dst, uint32_t src, int bytes) {
    asm volatile("cp.async.bulk.global.shared::cta.bulk_group [%0], [%1], %2;" ::"l"(dst), "r"(src), "r"(bytes) : "memory");
}
__device__ __forceinline__ uint32_t ld_acq(const void* p) { uint32_t v; asm volatile("ld.acquire.gpu.global.u32 %0, [%1];" : "=r"(v) : "l"(p) : "memory"); return v; }
__device__ __forceinline__ void red_add(void* p) { asm volatile("red.relaxed.gpu.global.add.u32 [%0], 1;" ::"l"(p) : "memory"); }
__device__ __forceinline__ void fence_async() { asm volatile("fence.proxy.async.shared::cta;" ::: "memory"); }
__device__ __forceinline__ void fence_async_g() { asm volatile("fence.proxy.async.global;" ::: "memory"); }
__device__ __forceinline__ void red_rel(void* p) { asm volatile("red.release.gpu.global.add.u32 [%0], 1;" ::"l"(p) : "memory"); }
__device__ __forceinline__ void wait_count(const uint32_t* p, uint32_t want) {
#pragma unroll 1
    for (int it = 0; it < SPIN_LIMIT && ld_rlx(p) != want; it++) __nanosleep(20);
}
__device__ __forceinline__ uint32_t ld_stat(const uint32_t* p, uint32_t tag) {
    uint32_t v = 0;
#pragma unroll 1
    for (int it = 0; it < SPIN_LIMIT; it++) {
        v = ld_rlx(p);
        if ((v >> 31) == tag) break;
    }
    return v & 0x7FFFFFFFu;
}
__device__ __forceinline__ uint32_t hadd(uint32_t a, uint32_t b) { uint32_t r; asm("add.rn.f16x2 %0, %1, %2;" : "=r"(r) : "r"(a), "r"(b)); return r; }
__device__ __forceinline__ float h_lo(uint32_t w) { return __half2float(__ushort_as_half((unsigned short)w)); }
__device__ __forceinline__ float h_hi(uint32_t w) { return __half2float(__ushort_as_half((unsigned short)(w >> 16))); }
__device__ __forceinline__ uint32_t x0_chunk(uint32_t xb, int c) { return xb + ((c & 1) ? X0_ODD + 120 : 128) + 8 * c; }

struct cf { float x, y; };
__device__ __forceinline__ cf cmul(cf a, cf b) { return {a.x * b.x - a.y * b.y, a.x * b.y + a.y * b.x}; }
__device__ __forceinline__ cf csq(cf a) { return {a.x * a.x - a.y * a.y, (a.x + a.x) * a.y}; }
__device__ __forceinline__ cf cpow_direct(float zr2, float zi, float l) {
    const float mag = ex2f(zr2 * l), th = zi * l;
    return {mag * __cosf(th), mag * __sinf(th)};
}
__device__ __forceinline__ __half2 as_h2(uint32_t v) { return *reinterpret_cast<__half2*>(&v); }
__device__ __forceinline__ uint32_t as_u32(__half2 v) { return *reinterpret_cast<uint32_t*>(&v); }
struct hm { uint32_t v, s; };
__device__ __forceinline__ hm mk_hm(cf a) {
    const uint32_t v = pack_h(a.x, a.y);
    return {v, prmt(v, v, 0x1032) ^ 0x8000u};
}
__device__ __forceinline__ uint32_t hcmul(uint32_t x, hm y) {
    const __half2 xx = as_h2(x);
    return as_u32(__hfma2(__high2half2(xx), as_h2(y.s), __hmul2(__low2half2(xx), as_h2(y.v))));
}

struct KParams { uint32_t are, aim, bre, bim, cre, cim, ldt; };
__device__ __forceinline__ KParams kgen_load(const Hot& p, int ch, int half, int lane) {
    const uint32_t po = ch * 64 + half * 32 + lane;
    KParams k;
    k.are = __ldg((const uint32_t*)p.are + po); k.aim = __ldg((const uint32_t*)p.aim + po);
    k.bre = __ldg((const uint32_t*)p.bre + po); k.bim = __ldg((const uint32_t*)p.bim + po);
    k.cre = __ldg((const uint32_t*)p.cre + po); k.cim = __ldg((const uint32_t*)p.cim + po);
    k.ldt = __ldg((const uint16_t*)p.logdt + ch + (lane & p.tn.zero));
    return k;
}

__device__ __forceinline__ void kgen(KParams kp, uint32_t scr, uint32_t os, int c0, int c1, uint32_t pause) {
    const int lane = threadIdx.x & 31;
    const float dt = bf_round(ex2f(bf_lo(kp.ldt) * 1.4426950408889634f));
    const cf w0 = cmul({bf_lo(kp.cre), bf_lo(kp.cim)}, {dt * bf_lo(kp.bre), dt * bf_lo(kp.bim)});
    const cf w1 = cmul({bf_hi(kp.cre), bf_hi(kp.cim)}, {dt * bf_hi(kp.bre), dt * bf_hi(kp.bim)});
    uint32_t eb = __reduce_max_sync(~0u, __float_as_uint(fmaxf(fmaxf(fabsf(w0.x), fabsf(w0.y)), fmaxf(fabsf(w1.x), fabsf(w1.y))))) & 0x7F800000u;
    eb = min(max(eb, 0x00800000u), 0x7E800000u);
    const float sc = __uint_as_float(0x7F000000u - eb);
    float k0 = c0 ? 0.f : w0.x + w1.x;
#pragma unroll
    for (int o = 16; o > 0; o >>= 1) k0 += __shfl_xor_sync(~0u, k0, o);
    float d[5][4];
#pragma unroll
    for (int i = 0; i < 5; i++) d[i][0] = d[i][1] = d[i][2] = d[i][3] = 0.f;
    const int mi = lane >> 3, j = lane & 7;
    const uint32_t st0 = scr + mi * 128 + ((j ^ mi) << 4), st1 = st0 ^ 64;
    const uint32_t la = scr + (lane & 15) * 128 + (((lane >> 4) ^ j) << 4), lb = scr + j * 128 + ((mi ^ j) << 4);
    auto st = [&](int row, uint32_t a, uint32_t b, uint32_t c, uint32_t e) { stm4(((row & 4) ? st1 : st0) + row * 128, a, b, c, e); };
#pragma unroll 1
    for (int c = c0; c < c1; c++) {
        if (c > c0 && pause) mbar_wait(pause, 0);
        const float zr2 = dt * (c ? bf_hi(kp.are) : bf_lo(kp.are)) * 1.4426950408889634f;
        const float zi = dt * (c ? bf_hi(kp.aim) : bf_lo(kp.aim));
        const cf w = {(c ? w1.x : w0.x) * sc, (c ? w1.y : w0.y) * sc};
        const cf a1 = cpow_direct(zr2, zi, 1.f), a256 = cpow_direct(zr2, zi, 256.f);
        uint32_t a[4][4];
        {
            const cf a16 = cpow_direct(-zr2, zi, -16.f);
            const cf a32 = csq(a16), a48 = cmul(a32, a16), a64 = csq(a32), a128 = csq(a64), a192 = cmul(a128, a64);
            const uint32_t p1 = pack_h(a16.x, a16.y), p2 = pack_h(a32.x, a32.y), p3 = pack_h(a48.x, a48.y);
            const hm q1 = mk_hm(a64), q2 = mk_hm(a128), q3 = mk_hm(a192);
            __syncwarp();
            st(0, 0x00003C00u, p1, p2, p3);
            st(4, q1.v, hcmul(p1, q1), hcmul(p2, q1), hcmul(p3, q1));
            st(8, q2.v, hcmul(p1, q2), hcmul(p2, q2), hcmul(p3, q2));
            st(12, q3.v, hcmul(p1, q3), hcmul(p2, q3), hcmul(p3, q3));
            __syncwarp();
#pragma unroll
            for (int k = 0; k < 4; k++) ldm4(la ^ (k * 32), a[k][0], a[k][1], a[k][2], a[k][3]);
        }
        auto tile = [&](int T, int row) {
#pragma unroll
            for (int kp2 = 0; kp2 < 2; kp2++) {
                uint32_t b0, b1, b2, b3;
                ldm4((lb ^ (kp2 * 64)) + row * 128, b0, b1, b2, b3);
                mma_h(d[T], a[2 * kp2][0], a[2 * kp2][1], a[2 * kp2][2], a[2 * kp2][3], b0, b1);
                mma_h(d[T], a[2 * kp2 + 1][0], a[2 * kp2 + 1][1], a[2 * kp2 + 1][2], a[2 * kp2 + 1][3], b2, b3);
            }
        };
        const cf a2 = csq(a1), a4 = csq(a2), a8 = csq(a4), a12 = cmul(a8, a4);
        const cf u1 = cmul(w, a1), u2 = cmul(w, a2), u3 = cmul(u2, a1), u4 = cmul(w, a4);
        uint32_t v[16];
        v[0] = pack_h(u1.x, u1.y); v[1] = pack_h(u2.x, u2.y); v[2] = pack_h(u3.x, u3.y); v[3] = pack_h(u4.x, u4.y);
        const hm m4 = mk_hm(a4), m8 = mk_hm(a8), m12 = mk_hm(a12);
#pragma unroll
        for (int i = 0; i < 4; i++) { v[4 + i] = hcmul(v[i], m4); v[8 + i] = hcmul(v[i], m8); v[12 + i] = hcmul(v[i], m12); }
        const hm m256 = mk_hm(a256);
        __syncwarp();
#pragma unroll
        for (int i = 0; i < 4; i++) st(4 * i, v[4 * i], v[4 * i + 1], v[4 * i + 2], v[4 * i + 3]);
        st(16, hcmul(v[1], m256), hcmul(v[3], m256), hcmul(v[5], m256), hcmul(v[7], m256));
        st(20, hcmul(v[9], m256), hcmul(v[11], m256), hcmul(v[13], m256), hcmul(v[15], m256));
        __syncwarp();
        tile(0, 0); tile(1, 8); tile(2, 16);
        const cf a512 = csq(a256), a768 = cmul(a512, a256), a1024 = csq(a512);
        const cf a1280 = cmul(a1024, a256), a1536 = csq(a768), a1792 = cmul(a1024, a768);
        const hm m512 = mk_hm(a512), m768 = mk_hm(a768);
        const hm n0 = mk_hm(a1024), n1 = mk_hm(a1280), n2 = mk_hm(a1536), n3 = mk_hm(a1792);
        __syncwarp();
        st(0, hcmul(v[3], m512), hcmul(v[7], m512), hcmul(v[11], m512), hcmul(v[15], m512));
        st(4, hcmul(v[3], m768), hcmul(v[7], m768), hcmul(v[11], m768), hcmul(v[15], m768));
        st(8, hcmul(v[7], n0), hcmul(v[15], n0), hcmul(v[7], n1), hcmul(v[15], n1));
        st(12, hcmul(v[7], n2), hcmul(v[15], n2), hcmul(v[7], n3), hcmul(v[15], n3));
        __syncwarp();
        tile(3, 0); tile(4, 8);
    }
    __syncwarp();
#pragma unroll
    for (int i = 0; i < 5; i++) sts128(os + i * 512 + lane * 16, __float_as_uint(d[i][0]), __float_as_uint(d[i][1]), __float_as_uint(d[i][2]), __float_as_uint(d[i][3]));
    sts64(os + 2560, eb, __float_as_uint(k0));
}

__device__ __forceinline__ void ktables(uint32_t os, int ostep, int np, uint32_t kr, uint32_t kt, uint32_t kinf, int part) {
    const int lane = threadIdx.x & 31, g = lane >> 2, t = lane & 3;
    uint32_t eb = 0;
    float k0 = 0.f, f[4];
#pragma unroll
    for (int q = 0; q < 4; q++) {
        uint2 v = make_uint2(0u, 0u);
        if (q < np) v = lds64(os + q * ostep + 2560);
        eb = max(eb, v.x);
        k0 += __uint_as_float(v.y);
        f[q] = __uint_as_float(v.x);
    }
    const float rs = __uint_as_float(0x7F000000u - eb);
#pragma unroll
    for (int q = 0; q < 4; q++) f[q] *= rs;
#pragma unroll 1
    for (int i = (part & 1) ? 0 : 2; i < ((part & 2) ? 5 : 3); i++) {
        float a0 = 0.f, a1 = 0.f, a2 = 0.f, a3 = 0.f;
        uint4 v[4];
#pragma unroll
        for (int q = 0; q < 4; q++) {
            v[q] = make_uint4(0u, 0u, 0u, 0u);
            if (q < np) v[q] = lds128(os + q * ostep + i * 512 + lane * 16);
        }
#pragma unroll
        for (int q = 0; q < 4; q++) { a0 += __uint_as_float(v[q].x) * f[q]; a1 += __uint_as_float(v[q].y) * f[q]; a2 += __uint_as_float(v[q].z) * f[q]; a3 += __uint_as_float(v[q].w) * f[q]; }
        const int sg = 32 >> max(i - 1, 0);
        const uint32_t o = kr + 4 + (i < 2 ? 16 * i : 256 * i) + sg * g + (i < 3 ? 8 : 128) * (t >> 1) + (i < 4 ? 4 : 64) * (t & 1);
        sts32(o, pack_h(a0, a1));
        sts32(o + 8 * sg, pack_h(a2, a3));
    }
    sts32(kr, pack_h(0.f, k0 * rs));
    __syncwarp();
    if (part & 1) {
        uint32_t w0[4], w1[4], a[2], b[2];
#pragma unroll
        for (int r = 0; r < 4; r++) { w0[r] = lds32(kr + 4 * lane + 128 * r); w1[r] = lds32(kr + 4 * lane + 128 * r + 4); }
#pragma unroll
        for (int r = 0; r < 2; r++) { a[r] = lds32(kr + 512 + 4 * lane + 128 * r); b[r] = lds32(kr + 516 + 4 * lane + 128 * r); }
#pragma unroll
        for (int r = 0; r < 4; r++) sts64(kt + 8 * lane + 256 * r + 32, prmt(w0[r], w0[r], 0x1032), prmt(w0[r], w1[r], 0x3254));
        if (lane == 31) b[1] = pack_h(h_lo(b[1]) - h_hi(b[1]), 0.f);
#pragma unroll
        for (int r = 0; r < 2; r++)
            sts128(kt + 4 * 264 + 16 * lane + 512 * r, prmt(a[r], a[r], (r == 0 && lane == 0) ? 0x1032 : 0x3232), prmt(a[r], a[r], 0x3232), prmt(a[r], b[r], 0x3254), prmt(b[r], b[r], 0x1032));
        if (lane < 24) sts32(kt + 4 * (lane < 8 ? lane : 512 + lane), 0u);
    }
    if (part & 2) {
        const uint32_t k512 = lds16(kr + 2 * 385), k1024 = lds16(kr + 2 * 513);
        if (lane == 0) {
            sts128(kinf, eb, __float_as_uint(h_lo(k512)), k1024, 0u);
            sts16(kr + 2 * 512, pack_h(h_lo(lds16(kr + 2 * 512)) - h_lo(k1024), 0.f));
        }
#pragma unroll
        for (int r = 0; r < 3; r++)
            if (r < 2 || lane < 26) sts128(kt + KT_P4 + 16 * lane + 512 * r, 0u, 0u, 0u, 0u);
        __syncwarp();
        uint32_t x0[5], x1[5], y0[5], y1[5];
#pragma unroll
        for (int r = 0; r < 5; r++) {
            const int m = min(126 + lane + 32 * r, 256);
            x0[r] = lds16(kr + 2 * (257 + m)); x1[r] = lds16(kr + 2 * (259 + m)); y0[r] = lds16(kr + 2 * (385 + m)); y1[r] = lds16(kr + 2 * (387 + m));
        }
#pragma unroll
        for (int r = 0; r < 5; r++) {
            const int m = 126 + lane + 32 * r;
            if (m < 128) x0[r] = y0[r] = 0;
            if (m > 253) x1[r] = 0;
            if (m > 254) y1[r] = 0;
            if (m < 256) sts32(kt + KT_P4 + 4 * (((m - 96) & ~3) | ((m & 1) << 1) | ((m >> 1) & 1)), x0[r] | (x1[r] << 16));
            if (m < 257) sts32(kt + KT_P8 + 4 * (m - 96), y0[r] | (y1[r] << 16));
        }
    }
    __syncwarp();
}

__device__ __forceinline__ void mma_hc(float (&d)[4], const float (&c)[4], uint32_t a0, uint32_t a1, uint32_t a2, uint32_t a3, uint32_t b0, uint32_t b1) {
    asm volatile("mma.sync.aligned.m16n8k16.row.col.f32.f16.f16.f32 {%0,%1,%2,%3},{%4,%5,%6,%7},{%8,%9},{%10,%11,%12,%13};"
                 : "=f"(d[0]), "=f"(d[1]), "=f"(d[2]), "=f"(d[3]) : "r"(a0), "r"(a1), "r"(a2), "r"(a3), "r"(b0), "r"(b1), "f"(c[0]), "f"(c[1]), "f"(c[2]), "f"(c[3]));
}
template <int Q0, int Q1>
__device__ __forceinline__ void sweep_steps(float (&w)[5][4], const uint32_t (&R)[66], uint32_t xa, uint32_t (&x)[5], uint32_t z) {
#pragma unroll
    for (int q = Q0; q <= Q1; q++) {
        uint32_t n0, n1;
        ldm2(xa + 16 * (q + 1), n0, n1);
        const uint32_t a2 = x[0] | z, a3 = x[1] | z;
#pragma unroll
        for (int j = 0; j < 4; j++) {
            const int s = 8 * j + 8 - q;
            if (q == 1) mma_hc(w[j], w[j + 1], x[1], x[2], a2, a3, R[2 * s], R[2 * s + 1]);
            else mma_h(w[j], x[1], x[2], a2, a3, R[2 * s], R[2 * s + 1]);
        }
        if (q == 8) {
            const float zero[4] = {0.f, 0.f, 0.f, 0.f};
            mma_hc(w[4], zero, x[1], x[2], a2, a3, R[64], R[65]);
        }
        x[0] = x[2]; x[1] = x[3]; x[2] = x[4]; x[3] = n0; x[4] = n1;
    }
}

__device__ __forceinline__ void box_round(uint32_t xb, uint32_t fa, int rho, int lane) {
    if (rho == 6) {
        const int a = lane >> 3, j = lane & 7;
        sts128(fa + 3328 * (lane >> 4) + 16 * ((lane & 15) < 15 ? (lane & 15) : 207), 0u, 0u, 0u, 0u);
        sts128(fa + FB9E + 1168 * a + 16 * (j < 7 ? j : 71 + (a & 1)), 0u, 0u, 0u, 0u);
        __syncwarp();
    }
    const int c = rho < 6 ? 32 * rho + lane : -1;
    const uint4 pv = lds128(x0_chunk(xb, c - 1)), ow = lds128(x0_chunk(xb, c));
    const uint2 nx = lds64(x0_chunk(xb, c + 1));
    const uint32_t P[9] = {pv.y, pv.z, pv.w, ow.x, ow.y, ow.z, ow.w, nx.x, nx.y};
    uint32_t Q[8], b3[6], b5[4];
#pragma unroll
    for (int k = 0; k < 8; k++) Q[k] = prmt(P[k], P[k + 1], 0x5432);
#pragma unroll
    for (int k = 0; k < 6; k++) b3[k] = hadd(hadd(Q[k], Q[k + 1]), P[k + 1]);
#pragma unroll
    for (int k = 0; k < 4; k++) b5[k] = hadd(b3[k + 2], hadd(P[k + 2], P[k + 4]));
    sts128(fa + FB5 + 240 + 16 * c, b5[0], b5[1], b5[2], b5[3]);
    sts128(fa + FB3 + 240 + 16 * c, b3[0], b3[1], b3[2], b3[3]);
    if (rho < 4 || rho == 6) {
        uint32_t b7[4], b9[4];
#pragma unroll
        for (int k = 0; k < 4; k++) {
            b7[k] = hadd(b5[k], hadd(Q[k + 1], Q[k + 4]));
            b9[k] = hadd(b7[k], hadd(P[k + 1], P[k + 5]));
        }
        const uint32_t ad = fa + ((c & 1) ? FB9O + 120 : FB9E + 112) + 8 * c;
        sts128(ad, b9[0], b9[1], b9[2], b9[3]);
        sts128(ad + (FB7E - FB9E), b7[0], b7[1], b7[2], b7[3]);
    }
}

__global__ void __cluster_dims__(2, 1, 1) __launch_bounds__(NTHREADS, 1) fused_kernel(const Hot p, const __grid_constant__ Maps m) {
    extern __shared__ __align__(1024) char smem[];
    const uint32_t t0 = clk32();
    const int tid = (threadIdx.x + 32 * 0) & (NTHREADS - 1), lane = tid & 31, warp = __shfl_sync(~0u, tid >> 5, 0), bid = blockIdx.x;
    const uint32_t S = smem_u32(smem), z = (uint32_t)p.tn.zero;
    const bool down = bid < NDOWN, rowcta = bid < NMAIN, big = rowcta && !down;
    const int xd = rowcta ? bid : 142 + ((bid - NMAIN) >> 1);
    const int slot = warp < 8 ? (warp & 3) : 4;
    const bool has = warp < 8 ? (rowcta || (slot >> 1) == (bid & 1)) : (big && warp < 12);
    const int ch = slot < 4 ? 4 * xd + slot : 512 + bid - NDOWN;
    KParams kp;
    if (has) kp = kgen_load(p, ch, warp < 8 ? warp >> 2 : (warp >> 1) & 1, lane);
    if (elect()) {
#pragma unroll 1
        for (int i = warp; i < B_COUNT; i += 16) {
            const uint32_t c = i < 16 ? (uint32_t)((big ? 0x1411115555412290ull : 0x1411114444412290ull) >> (4 * i)) & 15 : 1;
            mbar_init(S + i * 8, c ? c : NTHREADS);
        }
        asm volatile("fence.mbarrier_init.release.cluster;" ::: "memory");
    }
    if (rowcta) {
#pragma unroll 1
        for (int i = tid; i < 1224; i += NTHREADS)
            cp16(S + SM_ROWS + 16 * (i + min((i * 911) >> 16, 16)), i < 1152 ? (const uint4*)p.u + bid * 1152 + i : (const uint4*)p.wr + (i - 1152));
    }
    if (tid >= 256 && tid < 336) {
        const int i = tid - 256;
        if (i < 64 || big) sts128(S + (i < 64 ? SM_X0 + (i >> 4) * X0_STRIDE : SM_EX) + ((i & 8) ? X0_ODD : 0) + 16 * (i & 7), 0u, 0u, 0u, 0u);
    }
    if (tid == 447) sts128(S + SM_ONES, 0x3F803F80u, 0x3F803F80u, 0x3F803F80u, 0x3F803F80u);
    __syncthreads();
    if (rowcta) asm volatile("cp.async.mbarrier.arrive.noinc.shared::cta.b64 [%0];" ::"r"(S + B_ROWS * 8) : "memory");
    if (warp == 15 && lane < 4) mbar_expect(S + (lane < 3 ? B_GX + lane : B_RED) * 8, 256);
    asm volatile("barrier.cluster.arrive.relaxed.aligned;" ::: "memory");
    const int g = lane >> 2, t = lane & 3, mi = lane >> 3, j = lane & 7;
    const uint32_t SW = S + (down ? SM_W_DOWN : SM_W_BIG);
    const int pr = bid >> 1, r = bid & 1, nsl = pr >= 54 ? 3 : 2, sl0 = pr < 54 ? 2 * pr : 3 * pr - 54;

    if (warp == 12) {
        if (elect()) {
            const int ng = 6 * nsl, ns = down ? 24 : ng;
            const CUtensorMap* mg = r ? &m.wu : &m.wg;
            pf_tmap(mg);
            if (down) pf_tmap(&m.wd);
            const uint32_t epoch = ld_rlx(&p.s->cnt[16 * 32]) + 1;
            spin_until(t0, p.tn.f_start);
            int done = 0;
#pragma unroll 1
            for (int s = 0; s < ns; s++) {
                if (s == ng) spin_until(t0, p.tn.f_t3);
                #pragma unroll 1
                for (int it = 0; it < SPIN_LIMIT; it++) {
                    const int w = s >= ng ? p.tn.w3 : ((int)(clk32() - t0) < p.tn.f_t2 ? p.tn.w1 : (nsl == 3 ? p.tn.w2b : p.tn.w2));
                    if (s - done < w) break;
                    if (mbar_test(S + (B_W + done) * 8, 0)) done++;
                    else __nanosleep(32);
                }
                const uint32_t bar = S + (B_W + s) * 8;
                uint32_t dst = SW + s * STAGE;
                if (s == 23) { mbar_wait(S + B_EM * 8, 0); fence_async(); dst = S + SM_W_LAST; }
                mbar_expect(bar, STAGE);
                const int u = (s * 43) >> 8;
                if (s < ng) tma2d(dst, mg, 32 * (sl0 + u), 96 * (s - 6 * u), bar);
                else tma2d(dst, &m.wd, 16 * pr, r * 2304 + 192 * (s - 12), bar);
            }
            if (rowcta) {
                mbar_wait(S + B_FD * 8, 0);
                fence_async();
#pragma unroll 1
                for (int q = 0; q < 4; q++) {
                    wait_count(&p.s->cnt[(8 + q) * 32], epoch * (uint32_t)D_);
                    fence_async_g();
                    mbar_expect(S + (B_YIN + q) * 8, 4608);
                    bulk_g2s(S + SM_STG + q * 4608, p.s->y + (32 * q + (bid >> 2)) * 4608 + (bid & 3) * 1152, 4608, S + (B_YIN + q) * 8);
                }
            }
        }
        return;
    }

    uint32_t epoch = 0;
    if (warp >= 8 || !rowcta) epoch = ld_rlx(&p.s->cnt[16 * 32] + (lane & z)) + 1;
    const uint32_t tag = epoch & 1;
    const int hw = warp < 12 ? warp - 8 : warp - 9;

    if (rowcta && warp >= 8 && warp < 15) {
        const uint32_t ad = S + SM_ROWS + (lane & 15) * ROW_STRIDE + 192 * hw + 16 * (lane >> 4);
        uint32_t wd = j ? S + SM_ROWS + 16 * ROW_STRIDE + 192 * hw + 16 * mi : S + SM_ONES;
        const uint32_t wstep = j ? 64 : 0, ones = 0x3F803F80u | z;
        float d1[4] = {0, 0, 0, 0}, d2[4] = {0, 0, 0, 0}, d3[4] = {0, 0, 0, 0}, d4[4] = {0, 0, 0, 0};
        mbar_wait(S + B_ROWS * 8, 0);
#pragma unroll
        for (int kk = 0; kk < 3; kk++) {
            uint32_t w[4];
            ldm4(wd, w[0], w[1], w[2], w[3]);
            wd += wstep;
#pragma unroll
            for (int e = 0; e < 2; e++) {
                uint32_t a0, a1, a2, a3;
                ldm4(ad + 64 * kk + 32 * e, a0, a1, a2, a3);
                mma_bf(d1, a0, a1, a2, a3, w[2 * e], w[2 * e + 1]);
                mma_bf(d2, a0, a1, a2, a3, a0, a2);
                mma_bf(d3, a0, a1, a2, a3, a1, a3);
                mma_bf(d4, ones, ones ^ z, ones + z, ones - z, w[2 * e], w[2 * e + 1]);
            }
        }
        float* part = (float*)(smem + SM_PART + hw * 256) + g * 4;
        if (t == 0) {
            *(float2*)part = make_float2(d1[0], d1[1]);
            *(float2*)(part + 32) = make_float2(d1[2], d1[3]);
            part[3] = d4[1];
            part[35] = d4[1];
        }
        if (t == (g >> 1)) {
            part[2] = (g & 1) ? d2[1] : d2[0];
            part[34] = (g & 1) ? d3[3] : d3[2];
        }
        bar_sync(1, 192);
        if (hw == 0 && lane < 16) {
            float4 s = *(const float4*)(smem + SM_PART + lane * 16);
#pragma unroll
            for (int w = 1; w < 6; w++) {
                const float4 v = *(const float4*)(smem + SM_PART + w * 256 + lane * 16);
                s.x += v.x; s.y += v.y; s.z += v.z; s.w += v.w;
            }
            const float mean = s.x * (1.f / 576.f);
            const float var = fmaxf(s.z * (1.f / 576.f) - mean * mean, 0.f);
            const uint32_t mm = pack_bf(mean, mean);
            const float mu = bf_lo(mm), sd = bf_round(sqrt_ap(bf_round(bf_round(var) + 1e-5f))), ri = rcpf(sd);
            const uint32_t hi = pack_bf(ri, ri);
            const float rl = ri - bf_lo(hi);
            sts16(S + SM_STA + 2 * lane, mm); sts16(S + SM_STA + 32 + 2 * lane, hi); sts16(S + SM_STA + 64 + 2 * lane, pack_bf(rl, rl));
            const uint32_t rb = pack_bf(0.f, (s.y - mu * s.w) * ri);
            const int row = bid * 16 + lane;
            p.s->stat[row] = (mm & 0xFFFFu) | __float_as_uint(sd) | (tag << 31);
            p.s->key[row] = ((rb ^ (((int)rb >> 31) | 0x80000000u)) & 0xFFFF0000u) | (tag << 15) | (2047 - row);
        }
        bar_sync(1, 192);
        if (tid == 256) mbar_arrive(S + B_P1 * 8);
        {
            const uint2 sm = lds64(S + SM_STA + 8 * t), sh = lds64(S + SM_STA + 32 + 8 * t), sl = lds64(S + SM_STA + 64 + 8 * t);
            const uint32_t at = S + SM_ROWS + (4 * (j >> 1) + (j & 1) + 2 * (mi & 1)) * ROW_STRIDE + 32 * hw + 16 * (mi >> 1);
            uint2* dst = (uint2*)p.s->x + (4 * hw + (g >> 2)) * 2048 + bid * 16 + (g & 3) * 4 + t;
            uint32_t r4[6][4];
#pragma unroll
            for (int n = 5; n >= 0; n--) ldm4t(at + 192 * n, r4[n][0], r4[n][1], r4[n][2], r4[n][3]);
#pragma unroll
            for (int n = 5; n >= 0; n--) {
                uint32_t o[4];
#pragma unroll
                for (int e = 0; e < 4; e++) {
                    const uint32_t v = (e & 1) ? norm2(r4[n][e], sm.y, sh.y, sl.y) : norm2(r4[n][e], sm.x, sh.x, sl.x);
                    o[e] = pack_h(bf_lo(v), bf_hi(v));
                }
                dst[n * 49152] = make_uint2((o[0] & ~1u) | tag, o[1]);
                dst[n * 49152 + 4096] = make_uint2((o[2] & ~1u) | tag, o[3]);
            }
        }
        bar_sync(1, 192);
    }

    if (has) {
        asm volatile("" : "+r"(kp.ldt), "+r"(kp.are), "+r"(kp.aim), "+r"(kp.bre), "+r"(kp.bim), "+r"(kp.cre), "+r"(kp.cim));

        const uint32_t scr = warp < 8 ? S + SM_STG + warp * KG_SCR : S + EX_HAND + hw * KG_SCR;
        kgen(kp, scr, warp < 8 ? scr : S + EX_FAR + hw * 2576, warp < 8 ? 0 : warp & 1, warp < 8 ? 2 : (warp & 1) + 1, rowcta ? S + B_P1 * 8 : 0);
        if (warp >= 8) { __syncwarp(); if (lane == 0) mbar_arrive(S + B_TAB * 8); }
    }
    if (warp < 8 || warp == 15) {
        if (warp < 8 ? has : big) {
            if (warp < 8) bar_sync(4 + slot, 64); else mbar_wait(S + B_TAB * 8, 0);
            ktables(warp < 8 ? S + SM_STG + slot * KG_SCR : S + EX_FAR, warp < 8 ? 4 * KG_SCR : 2576, warp < 8 ? 2 : 4, S + SM_XS + slot * KR_STRIDE,
                    S + (warp < 8 ? SM_KT + slot * KT_STRIDE : EX_KT), S + SM_KINF + slot * 16, warp < 8 ? 1 + (warp >> 2) : 3);
        }
        if (lane == 0) { mbar_arrive(S + B_KG * 8); if (warp == 15) mbar_arrive(S + B_TAB1 * 8); }
    }

    if (!rowcta && warp < 8 && !has) {
        const int w4 = (warp >> 2) * 2 + (warp & 1), i = 32 * w4 + lane;
#pragma unroll 1
        for (int pass = 1; pass < 2; pass++) {
        uint4 k[4];
        if (pass) spin_until(t0, p.tn.t_svc - 1500);
#pragma unroll 1
        for (int it = 0; it < SPIN_LIMIT; it++) {
            if (!pass) {
#pragma unroll
                for (int q = 0; q < 4; q++) k[q] = make_uint4(16 * i + 4 * q, 16 * i + 4 * q + 1, 16 * i + 4 * q + 2, 16 * i + 4 * q + 3);
                break;
            }
            uint32_t bad = 0;
#pragma unroll
            for (int q = 0; q < 4; q++) k[q] = ld_rlx4(&p.s->key[4 * i + 512 * q]);
#pragma unroll
            for (int q = 0; q < 4; q++) bad |= tag ? ~(k[q].x & k[q].y & k[q].z & k[q].w) : (k[q].x | k[q].y | k[q].z | k[q].w);
            if (!(bad & 0x8000u)) break;
            __nanosleep(100);
        }
        const uint32_t sc = S + SM_XS + ((bid & 1) ? 0 : 2) * KR_STRIDE;
        auto pk = [](uint32_t v) { return ((v >> 16) << 11) | (v & 2047u); };
        auto gt = [](uint32_t a, uint32_t b) { return (b - a) >> 31; };
        uint32_t mx = 0;
#pragma unroll
        for (int q = 0; q < 4; q++) {
            k[q] = make_uint4(pk(k[q].x), pk(k[q].y), pk(k[q].z), pk(k[q].w));
            mx = max(max(mx, max(k[q].x, k[q].y)), max(k[q].z, k[q].w));
        }
        bar_sync(1, 128);
        sts32(sc + 4 * i, mx);
        if (i == 0) sts32(sc + 1024, 0u);
        bar_sync(1, 128);
        int rank;
        {
            int c[8] = {0, 0, 0, 0, 0, 0, 0, 0};
#pragma unroll 1
            for (int q = 0; q < 32; q += 4) {
                uint4 v[4];
#pragma unroll
                for (int e = 0; e < 4; e++) v[e] = lds128(sc + 16 * (q + e));
#pragma unroll
                for (int e = 0; e < 4; e++) {
                    c[(2 * e) & 7] += gt(v[e].x, mx); c[(2 * e + 1) & 7] += gt(v[e].y, mx);
                    c[(2 * e + 4) & 7] += gt(v[e].z, mx); c[(2 * e + 5) & 7] += gt(v[e].w, mx);
                }
            }
            rank = ((c[0] + c[1]) + (c[2] + c[3])) + ((c[4] + c[5]) + (c[6] + c[7]));
        }
        if (rank == 7) sts32(sc + 1028, mx);
        bar_sync(1, 128);
        if (rank < 8) {
            const uint32_t lb = lds32(sc + 1028);
            int cq[4];
#pragma unroll
            for (int q = 0; q < 4; q++) cq[q] = (gt(lb, k[q].x) + gt(lb, k[q].y)) + (gt(lb, k[q].z) + gt(lb, k[q].w));
            const int c = 16 - ((cq[0] + cq[1]) + (cq[2] + cq[3]));
            uint32_t pos;
            asm volatile("atom.shared.add.u32 %0, [%1], %2;" : "=r"(pos) : "r"(sc + 1024), "r"(c) : "memory");
            pos = sc + 512 + 4 * pos;
#pragma unroll
            for (int q = 0; q < 4; q++) {
                if (k[q].x >= lb) { sts32(pos, k[q].x); pos += 4; }
                if (k[q].y >= lb) { sts32(pos, k[q].y); pos += 4; }
                if (k[q].z >= lb) { sts32(pos, k[q].z); pos += 4; }
                if (k[q].w >= lb) { sts32(pos, k[q].w); pos += 4; }
            }
        }
        bar_sync(1, 128);
        const int n = lds32(sc + 1024);
        if (i < n) {
            const uint32_t mine = lds32(sc + 512 + 4 * i);
            rank = 0;
#pragma unroll 1
            for (int q = 0; q < n; q += 4) {
                const uint4 v = lds128(sc + 512 + 4 * q);
                rank += ((v.x > mine) + (q + 1 < n && v.y > mine)) + ((q + 2 < n && v.z > mine) + (q + 3 < n && v.w > mine));
            }
            const uint32_t k32 = (mine >> 11) << 16, rb = (k32 ^ ((~(int)k32 >> 31) | 0x80000000u)) & 0xFFFF0000u;
            if (rank < 8 && pass) st_rlx(&p.s->sel[bid - NMAIN][rank], (2047 - (mine & 2047)) | (tag << 15) | (pack_bf(rcpf(1.f + ex2f(-1.4426950408889634f * __uint_as_float(rb))), 0.f) << 16));
        }
        }
    }

    if (warp == 13 || warp == 14) {
        const int i = tid - 416;
        if (i == 0) sts32(S + SM_EPOCH, tag);
        if (rowcta) {
            if (p.tn.t_marg <= 600) {
                const uint32_t back = ld_rlx(p.s->x + 2 * ((4 * hw + 2 + (g >> 2)) * 2048 + bid * 16 + (g & 3) * 4 + t));
                if (back == 0xFFFFFFFFu) __nanosleep(20);
            }
            spin_until(clk32(), p.tn.t_marg);
        } else {
            spin_until(t0, p.tn.t_svc);
        }
        const uint4* xa = (const uint4*)p.s->x + xd * 1024 + i;
        const int e = bid - NDOWN;
        const uint4* xe = (const uint4*)p.s->x + (128 + (e >> 2)) * 1024 + (i >> 1) * 8 + (e & 3) * 2 + (i & 1);
        const uint32_t da = S + SM_X0 + ((i >> 1) & 3) * X0_STRIDE + ((i & 1) ? X0_ODD : 0) + 128 + 16 * (i >> 3);
        const uint32_t de = S + SM_EX + ((i & 1) ? X0_ODD : 0) + 128 + 16 * (i >> 1);
        uint4 v[2][10];
        auto fetch = [&](int half) {
#pragma unroll
            for (int k = 0; k < 10; k++) {
                v[half][k].x = v[half][k].z = tag;
                if (k < 8 || big) v[half][k] = ld_rlx4(k < 8 ? xa + 512 * half + 64 * k : xe + 512 * half + 256 * (k - 8));
            }
        };
        fetch(0); fetch(1);
#pragma unroll
        for (int half = 0; half < 2; half++) {
#pragma unroll 1
            for (int it = 0; it < SPIN_LIMIT; it++) {
                uint32_t bad = 0;
#pragma unroll
                for (int k = 0; k < 10; k++) bad |= (v[half][k].x ^ tag) | (v[half][k].z ^ tag);
                if (!(bad & 1)) break;
                __nanosleep(60);
                fetch(half);
            }
#pragma unroll
            for (int k = 0; k < 10; k++)
                if (k < 8 || big) sts128(k < 8 ? da + 1024 * half + 128 * k : de + 1024 * half + 512 * (k - 8), v[half][k].x & ~1u, v[half][k].y, v[half][k].z & ~1u, v[half][k].w);
            __syncwarp();
            if (lane == 0) mbar_arrive(S + (B_X0 + half) * 8);
        }
    }

    if (warp < 12) {
        const bool cw = warp >= 8;
        if (has) {
            const uint32_t xb = S + (cw ? SM_EX : SM_X0 + slot * X0_STRIDE), kt = S + (cw ? EX_KT : SM_KT + slot * KT_STRIDE);
            const int g0 = cw ? warp - 8 : 0, g1 = cw ? warp - 7 : 4;
            const uint32_t park = (cw ? S + EX_HAND + g0 * 2048 : kt) + lane * 16;
            if (cw) mbar_wait(S + B_TAB1 * 8, 0);
            const uint4 ki = lds128(S + SM_KINF + slot * 16);
            const float inv = __uint_as_float(ki.x);
            if (warp >= 4) {
                const uint32_t fa = S + (cw ? EX_FAR : SM_FAR + slot * FAR_STRIDE);
                mbar_wait(S + (cw ? B_X1 : B_X0) * 8, 0);
                mbar_wait(S + B_KG * 8, 0);
#pragma unroll 1
                for (int rho = cw ? g0 : 0; rho < (cw ? 7 : 4); rho += cw ? 4 : 1) box_round(xb, fa, (!cw && rho == 3) ? 6 : rho, lane);
                if (cw) bar_sync(2, 128); else __syncwarp();
                const int dd = g - 2 * t, gf = g0 ? g0 : 1;
                const uint32_t tb0 = dd == -5 ? ki.z : (dd == -4 ? ki.z << 16 : 0u), tb1 = dd == 3 ? ki.z : (dd == 4 ? ki.z << 16 : 0u);
                uint32_t tad = xb + (mi == 1 ? 144 : mi == 2 ? 128 : X0_ODD + 128) + 16 * j + 512 * gf - 1024;
                uint32_t ad8 = fa + (mi == 0 ? FB9E : mi == 1 ? FB7O : mi == 2 ? FB9O + 16 : FB7E) + 112 - 16 * j + 512 * gf - 768;
                uint32_t ad4 = fa + ((mi & 1) ? FB3 : FB5) + 240 + 16 * (8 * (mi >> 1) - j) + 1024 * gf - 640;
                const uint32_t p4 = kt + KT_P4 + 16 * (g + t), p8 = kt + KT_P8 + 8 * (g + 2 * t);
#pragma unroll 1
                for (int grp = gf; grp < g1; grp++) {
                    float a[4][4], e[2][4], o[2][4];
#pragma unroll
                    for (int k = 0; k < 4; k++) a[0][k] = a[1][k] = a[2][k] = a[3][k] = e[0][k] = e[1][k] = o[0][k] = o[1][k] = 0.f;
                    {
                        if (!cw && grp == 2) {
                            mbar_wait(S + B_X1 * 8, 0);
#pragma unroll 1
                            for (int rho = 3; rho < 6; rho++) box_round(xb, fa, rho, lane);
                            __syncwarp();
                        }
                        {
                            uint4 A4[10];
#pragma unroll
                            for (int s = 0; s < 10; s++) A4[s] = lds128(p4 + 64 * s);
                            auto s4 = [&](int m) {
                                uint32_t b[4];
                                ldm4t(ad4 - 256 * m, b[0], b[1], b[2], b[3]);
#pragma unroll
                                for (int h = 1; h >= 0; h--)
#pragma unroll
                                    for (int i = 0; i < 4; i++) {
                                        const int s = 2 * m - 2 + 2 * i + (1 - h), k = m + (i & 2);
                                        if (k <= 5 && k >= ((i & 1) ? 0 : 1) && !((i & 1) && k == 5)) mma_h(a[i], A4[s >= 0 && s < 10 ? s : 0].x, A4[s >= 0 && s < 10 ? s : 0].y, A4[s >= 0 && s < 10 ? s : 0].z, A4[s >= 0 && s < 10 ? s : 0].w, b[2 * h], b[2 * h + 1]);
                                    }
                            };
                            auto tap = [&](int i) {
                                uint32_t b[4];
                                ldm4(tad + 128 * i, b[0], b[1], b[2], b[3]);
                                mma_h(a[i], b[0], b[1], b[2], b[3], tb1, tb0);
                            };
                            s4(1); s4(0); s4(2); s4(-1); tap(3); s4(-2);
                            if (grp >= 2) { s4(3); tap(0); s4(4); tap(1); s4(5); tap(2); }
                        }
                        {
                            uint32_t A8[9][4];
#pragma unroll
                            for (int k = 0; k < 9; k++) { A8[k][0] = lds32(p8 + 64 * k); A8[k][1] = lds32(p8 + 64 * k + 64); A8[k][2] = lds32(p8 + 64 * k + 4); A8[k][3] = lds32(p8 + 64 * k + 68); }
                            auto s8 = [&](int m) {
                                uint32_t b[4];
                                ldm4t(ad8 - 128 * m, b[0], b[1], b[2], b[3]);
                                mma_h(e[1], A8[m + 2][0], A8[m + 2][1], A8[m + 2][2], A8[m + 2][3], b[0], b[1]);
                                mma_h(o[1], A8[m + 2][0], A8[m + 2][1], A8[m + 2][2], A8[m + 2][3], b[2], b[3]);
                                if (m >= 0) {
                                    mma_h(e[0], A8[m >= 0 ? m : 0][0], A8[m >= 0 ? m : 0][1], A8[m >= 0 ? m : 0][2], A8[m >= 0 ? m : 0][3], b[0], b[1]);
                                    mma_h(o[0], A8[m >= 0 ? m : 0][0], A8[m >= 0 ? m : 0][1], A8[m >= 0 ? m : 0][2], A8[m >= 0 ? m : 0][3], b[2], b[3]);
                                }
                            };
                            s8(-2);
                            if (grp >= 2) {
                                s8(-1); s8(0); s8(1); s8(2);
                                if (grp >= 3) { s8(3); s8(4); s8(5); s8(6); }
                            }
                        }
                    }
                    tad += 512; ad8 += 512; ad4 += 1024;
#pragma unroll
                    for (int pp = 0; pp < 2; pp++) {
                        if (!cw) {
#pragma unroll 1
                            for (int it = 0; it < SPIN_LIMIT && !__all_sync(~0u, lds32v(park + (2 * pp + 1) * 512) == SLOT_FREE); it++) __nanosleep(32);
                        }
#pragma unroll
                        for (int i = 0; i < 2; i++)
                            sts128(park + (2 * pp + i) * 512, __float_as_uint((a[2 * pp + i][0] + e[pp][2 * i]) * inv), __float_as_uint((a[2 * pp + i][1] + e[pp][2 * i + 1]) * inv),
                                   __float_as_uint((a[2 * pp + i][2] + o[pp][2 * i]) * inv), __float_as_uint((a[2 * pp + i][3] + o[pp][2 * i + 1]) * inv));
                    }
                }
            }
            if ((warp & 12) != 4) {
                uint32_t R[66], x[5];
#pragma unroll
                for (int i = 0; i < 66; i++) R[i] = lds32(kt + 4 * (8 + g - 2 * t) + 32 * i);
                float w[5][4];
#pragma unroll
                for (int i = 0; i < 5; i++) w[i][0] = w[i][1] = w[i][2] = w[i][3] = 0.f;
                uint32_t xa = xb + ((lane & 8) ? X0_ODD + 16 : 16) + 16 * j + 512 * g0;
                uint2* yo = (uint2*)p.s->y + (32 * g0 + g) * 2304 + ch * 4 + t;
                mbar_wait(S + B_X0 * 8, 0);
                const uint32_t ytag = lds32(S + SM_EPOCH);
                if (g0 == 0) {
                    const uint32_t x01 = lds32(xb + 128);
                    const float c0 = lane == 31 ? __uint_as_float(ki.y) * inv * h_lo(x01) : 0.f, c1 = lane == 31 ? c0 + __uint_as_float(ki.y) * inv * h_hi(x01) : 0.f;
                    __syncwarp();
#pragma unroll
                    for (int i = 0; i < 4; i++) sts128(park + i * 512, 0u, 0u, i == 3 ? __float_as_uint(c0) : 0u, i == 3 ? __float_as_uint(c1) : 0u);
                }
                ldm2(xa - 16, x[1], x[0]);
                ldm2(xa, x[1], x[2]);
                ldm2(xa + 16, x[3], x[4]);
                uint32_t zz = z, pk = park;
                float sc = inv;
                const bool direct = g0 == 0;
                uint32_t dir = direct;
                asm volatile("" : "+r"(pk));
#pragma unroll 1
                for (int gq = g0; gq < g1; gq++) {
                    uint32_t pa = pk;
#pragma unroll 1
                    for (int n = 4; n > 0; n--) {
                        asm volatile("" : "+r"(zz), "+f"(sc), "+r"(pa), "+r"(dir));
                        sweep_steps<1, 5>(w, R, xa, x, zz);
                        uint4 v = lds128v(pa | (x[4] & zz));
                        sweep_steps<6, 8>(w, R, xa, x, zz);
                        xa += 128;
                        if (__any_sync(~0u, v.x == SLOT_FREE)) {
#pragma unroll 1
                            for (int it = 0; it < SPIN_LIMIT; it++) {
                                v = lds128v(pa);
                                if (!__any_sync(~0u, v.x == SLOT_FREE)) break;
                            }
                        }
                        const float y0 = fmaf(w[0][0], sc, __uint_as_float(v.x)), y1 = fmaf(w[0][1], sc, __uint_as_float(v.y));
                        const float y2 = fmaf(w[0][2], sc, __uint_as_float(v.z)), y3 = fmaf(w[0][3], sc, __uint_as_float(v.w));
                        if (dir) {
                            *yo = make_uint2((pack_bf(y0, y1) & ~1u) | ytag, pack_bf(y2, y3));
                            sts32(pa, SLOT_FREE);
                        } else {
                            sts128(pa, __float_as_uint(y0), __float_as_uint(y1), __float_as_uint(y2), __float_as_uint(y3));
                        }
                        yo += 18432;
                        pa += 512;
                    }
                    if (direct && lane == 0) red_add(&p.s->cnt[(8 + gq) * 32]);
                }
                __syncwarp();
                if (lane == 0) mbar_arrive(S + (direct ? B_EM : B_SP + g0) * 8);
                if (cw && g0 < 3) {
                    mbar_wait(S + (B_SP + g0 + 1) * 8, 0);
#pragma unroll
                    for (int i = 0; i < 4; i++) {
                        const uint4 v = lds128(park + 2048 + i * 512);
                        yo[i * 18432] = make_uint2((pack_bf(fmaf(w[i + 1][0], inv, __uint_as_float(v.x)), fmaf(w[i + 1][1], inv, __uint_as_float(v.y))) & ~1u) | ytag,
                                                   pack_bf(fmaf(w[i + 1][2], inv, __uint_as_float(v.z)), fmaf(w[i + 1][3], inv, __uint_as_float(v.w))));
                    }
                    if (lane == 0) red_add(&p.s->cnt[(8 + g0 + 1) * 32]);
                }
            }
        }
        if (rowcta && (warp & 12) == 4) {
            bar_sync(10, 128);
            const int i = tid - 128, rb0 = 16 * (bid >> 2), c0 = 144 * (bid & 3);
            if (i == 0) mbar_arrive(S + B_FD * 8);
#pragma unroll 3
            for (int v = i; v < 1152; v += 128) {
                const int row = (v * 3641) >> 16, vv = v - 18 * row;
                cp16(S + SM_ROWS + row * 304 + 16 * vv, (const uint4*)(p.u + (size_t)(512 * (row >> 4) + rb0 + (row & 15)) * D_ + c0) + vv);
            }
            if (i < 64) {
                const uint32_t sw = ld_stat(&p.s->stat[512 * (i >> 4) + rb0 + (i & 15)], lds32(S + SM_EPOCH));
                const float ri = rcpf(bf_hi(sw));
                const uint32_t hi = pack_bf(ri, ri);
                const float rl = ri - bf_lo(hi);
                sts128(S + SM_KT + KT_P4 + 16 * i, prmt(sw, sw, 0x1010), hi, pack_bf(rl, rl), 0u);
            }
            asm volatile("cp.async.wait_all;" ::: "memory");
            __syncwarp();
            if (lane == 0) mbar_arrive(S + B_OUT * 8);
        }
        if (!rowcta) return;

        const int rb0 = 16 * (bid >> 2), c0 = 144 * (bid & 3);
        mbar_wait(S + B_OUT * 8, 0);
        mbar_wait(S + B_XS * 8, 0);
        const uint32_t otag = lds32(S + SM_EPOCH) * 0x00010001u;
        const uint2 skip = lds64(S + SM_SKIP);
        const int pi_g = (g & 1) + 8 * ((g >> 1) & 1) + 2 * (g >> 2), pi_j = (j & 1) + 8 * ((j >> 1) & 1) + 2 * (j >> 2);
#pragma unroll 1
        for (int un = warp; un < 36; un += 12) {
            const int q = (un * 57) >> 9, cu = un - 9 * q;
            const uint32_t rw = S + SM_ROWS + 16 * q * 304 + 32 * cu;
            const uint32_t ad = rw + (pi_j + 4 * (mi & 1)) * 304 + 16 * (mi >> 1);
            const uint32_t dk0 = __ldg((const uint32_t*)p.dskip + (c0 >> 1) + 8 * cu + t), dk1 = __ldg((const uint32_t*)p.dskip + (c0 >> 1) + 8 * cu + 4 + t);
            const uint4 sa = lds128(S + SM_KT + KT_P4 + 16 * (16 * q + pi_g)), sb = lds128(S + SM_KT + KT_P4 + 16 * (16 * q + 4 + pi_g));
            uint32_t x[4], tt[4], gt[4], y[4];
            ldm4(ad, x[0], x[1], x[2], x[3]);
#pragma unroll
            for (int e = 0; e < 4; e++) {
                const uint4 s = (e & 1) ? sb : sa;
                const uint32_t xn = norm2(x[e], s.x, s.y, s.z);
                tt[e] = bmul(xn, e < 2 ? dk0 : dk1);
                gt[e] = pack_bf(silu_f(bf_lo(xn)), silu_f(bf_hi(xn)));
            }
            mbar_wait(S + (B_YIN + q) * 8, 0);
            const uint32_t yb = S + SM_STG + q * 4608 + 512 * cu;
#pragma unroll 1
            for (int it = 0; it < SPIN_LIMIT; it++) {
                ldm4t(yb + (8 * (mi >> 1) + j) * 32 + 16 * (mi & 1), y[0], y[1], y[2], y[3]);
                const uint32_t bad = ((y[0] ^ otag) | (y[1] ^ otag) | (y[2] ^ otag) | (y[3] ^ otag)) & 0x00010001u;
                if (!__any_sync(~0u, (g & 3) == 0 && bad)) break;
                const uint4 v = ld_rlx4((const uint4*)(p.s->y + (32 * q + (bid >> 2)) * 4608 + (bid & 3) * 1152 + 128 * cu) + lane);
                __syncwarp();
                sts128(yb + 16 * lane, v.x, v.y, v.z, v.w);
                __syncwarp();
            }
#pragma unroll
            for (int e = 0; e < 4; e++) y[e] = badd(x[e], bmul(badd(y[e], tt[e]), gt[e]));
            stm4(ad, y[0], y[1], y[2], y[3]);
            __syncwarp();
            const int row = lane >> 1;
            const uint4 o = lds128(rw + row * 304 + 16 * (lane & 1));
            if (!((((q & 2) ? skip.y : skip.x) >> (16 * (q & 1) + row)) & 1))
                *((uint4*)(p.out + (size_t)(512 * q + rb0 + row) * D_ + c0 + 16 * cu) + (lane & 1)) = o;
        }
        return;
    }

    {
        const int fw = warp - 13;
        if (fw < nsl) {
            st_rlx(&p.s->h[tag ^ 1][(32 * (sl0 + fw) + 16 * r) * 4 + lane], 0u);
            st_rlx(&p.s->h[tag ^ 1][(32 * (sl0 + fw) + 16 * r) * 4 + 32 + lane], 0u);
        }
        if (fw == 2) {
            spin_until(t0, p.tn.t_xs);
            uint32_t sv = 0;
#pragma unroll 1
            for (int it = 0; it < SPIN_LIMIT; it++) {
                sv = ld_rlx(&p.s->sel[bid & 3][j]);
                if (__all_sync(~0u, ((sv >> 15) & 1) == tag)) break;
                __nanosleep(40);
            }
            mbar_wait(S + B_KG * 8, 0);
            if (lane == 0) { fence_async(); mbar_expect(S + B_BOX * 8, 8 * 1152); }
            __syncwarp();
            if (lane < 8) bulk_g2s(S + SM_XS + lane * ROW_STRIDE, p.u + (size_t)(sv & 2047) * D_, 1152, S + B_BOX * 8);
            const uint32_t st = ld_stat(&p.s->stat[sv & 2047], tag);
            const float ri = rcpf(bf_hi(st));
            const uint32_t hi = pack_bf(ri, ri);
            const float rl = ri - bf_lo(hi);
            if (lane == 0) sts64(S + SM_SKIP, 0u, 0u);
            __syncwarp();
            if (lane < 8) {
                const int row = sv & 2047;
                if (((row >> 4) & 31) == (bid >> 2)) asm volatile("red.shared.or.b32 [%0], %1;" ::"r"(S + SM_SKIP + 4 * (row >> 10)), "r"(1u << (16 * ((row >> 9) & 1) + (row & 15))) : "memory");
                sts32(S + SM_XS + 8 * ROW_STRIDE + 4 * lane, sv);
                sts128(S + SM_RP + 16 * lane, prmt(st, st, 0x1010), hi, pack_bf(rl, rl), 0u);
            }
        }
        asm volatile("barrier.cluster.wait.aligned;" ::: "memory");
        bar_sync(9, 96);
        mbar_wait(S + B_BOX * 8, 0);
#pragma unroll
        for (int k = 0; k < 6; k++) {
            const int v = tid - 416 + 96 * k, tk = (v * 911) >> 16;
            const uint4 x = lds128(S + SM_XS + 16 * (v + tk)), st = lds128(S + SM_RP + 16 * tk);
            sts128(S + SM_XS + 16 * (v + tk), norm2(x.x, st.x, st.y, st.z), norm2(x.y, st.x, st.y, st.z), norm2(x.z, st.x, st.y, st.z), norm2(x.w, st.x, st.y, st.z));
        }
        bar_sync(9, 96);
        if (tid == 416) mbar_arrive(S + B_XS * 8);
        const uint32_t ob = mapa(S, r ^ 1);
        if (fw == 2) {
            if (elect()) {
#pragma unroll 1
                for (int st = 0; st < (down ? 24 : 6 * nsl); st++) {
                    if (st == 12 && down) break;
                    mbar_wait(S + (B_W + st) * 8, 0);
                    if (st % 3 == 2) mbar_arrive(S + (B_GU + st / 3) * 8);
                }
            }
            __syncwarp();
        }
        if (fw < 2) {
            const uint32_t bad = S + SM_XS + j * ROW_STRIDE + mi * 16;
            uint32_t aad = (SW + (8 * (mi >> 1) + j) * 64 + 16 * ((mi & 1) ^ (j >> 1))) ^ ((r ^ fw) * 32);
            uint32_t b[18][4];
#pragma unroll
            for (int k = 0; k < 18; k++) ldm4(bad + 64 * k, b[k][0], b[k][1], b[k][2], b[k][3]);
#pragma unroll 1
            for (int u = 0; u < nsl; u++) {
                float d[4][4];
#pragma unroll
                for (int i = 0; i < 4; i++) d[i][0] = d[i][1] = d[i][2] = d[i][3] = 0.f;
#pragma unroll
                for (int hf = 0; hf < 2; hf++) {
                    mbar_wait(S + (B_GU + 2 * u + hf) * 8, 0);
#pragma unroll
                    for (int sub = 0; sub < 3; sub++) {
                        uint32_t a[6][4];
#pragma unroll
                        for (int k = 0; k < 6; k++) ldm4t(aad + 1024 * k, a[k][0], a[k][1], a[k][2], a[k][3]);
#pragma unroll
                        for (int k = 0; k < 6; k++) {
                            const int kb = 9 * hf + 3 * sub + (k >> 1);
                            mma_bf(d[k & 3], a[k][0], a[k][1], a[k][2], a[k][3], b[kb][2 * (k & 1)], b[kb][2 * (k & 1) + 1]);
                        }
                        aad += STAGE;
                    }
                }
                const uint32_t k0 = pack_bf((d[0][0] + d[1][0]) + (d[2][0] + d[3][0]), (d[0][1] + d[1][1]) + (d[2][1] + d[3][1]));
                const uint32_t k1 = pack_bf((d[0][2] + d[1][2]) + (d[2][2] + d[3][2]), (d[0][3] + d[1][3]) + (d[2][3] + d[3][3]));
                if (fw == 1) {
                    asm volatile("st.async.shared::cluster.mbarrier::complete_tx::bytes.v2.b32 [%0], {%1, %2}, [%3];" ::"r"(ob + SM_PART + u * 256 + lane * 8), "r"(k0), "r"(k1), "r"(ob + (B_GX + u) * 8) : "memory");
                } else {
                    mbar_wait(S + (B_GX + u) * 8, 0);
                    const uint2 o = lds64(S + SM_PART + u * 256 + lane * 8);
#pragma unroll
                    for (int i = 0; i < 2; i++) {
                        const uint32_t mine = i ? k1 : k0, other = i ? o.y : o.x, gb = r ? other : mine, ub = r ? mine : other;
                        uint32_t hv = bmul(pack_bf(silu_f(bf_lo(gb)), silu_f(bf_hi(gb))), ub);
                        if ((hv & 0xFFFFu) == 0) hv |= 0x8000u;
                        if ((hv >> 16) == 0) hv |= 0x80000000u;
                        st_rlx(&p.s->h[tag][(32 * (sl0 + u) + 16 * r) * 4 + 32 * i + lane], hv);
                    }
                    __syncwarp();
                    if (lane < 8) red_add(&p.s->cnt[lane * 32]);
                }
            }
        }
        if (!down) return;

        const int fi = 32 * fw + lane, tok = 4 * r + ((fi >> 4) & 3), cc = 16 * pr + (fi & 15);
        const uint32_t sel = lds32(S + SM_XS + 8 * ROW_STRIDE + 4 * tok);
        const int row = sel & 2047;
        const uint32_t* ya = p.s->y + (row >> 4) * 4608 + cc * 8 + (row & 6);
        const float xraw = __bfloat162float(p.u[(size_t)row * D_ + cc]), dsk = __bfloat162float(p.dskip[cc]);
        const float xn = bf_lo(lds16(S + SM_XS + tok * ROW_STRIDE + 2 * cc));
        if (fw == 0) {
#pragma unroll 1
            for (int st = 12; st < 24; st++) mbar_wait(S + (B_W + st) * 8, 0);
        }
        if (fw == 2 && elect()) wait_count(&p.s->cnt[(bid & 7) * 32], epoch * 288u);
        bar_sync(9, 96);
        float dn[4][4];
        uint2 yv2 = make_uint2(tag ^ 1, 0u);
#pragma unroll 1
        for (int ph = 0; ph < 64; ph++) {
            if (fw == 2 && elect()) {
                fence_async();
                fence_async_g();
                mbar_expect(S + B_H * 8, 36864);
                bulk_g2s(SW, (const char*)p.s->h[tag] + r * 36864, 36864, S + B_H * 8);
            }
            asm volatile("ld.relaxed.gpu.global.v2.u32 {%0,%1}, [%2];" : "=r"(yv2.x), "=r"(yv2.y) : "l"(ya) : "memory");
            mbar_wait(S + B_H * 8, ph & 1);
#pragma unroll
            for (int i = 0; i < 4; i++) dn[i][0] = dn[i][1] = dn[i][2] = dn[i][3] = 0.f;
            uint32_t bq[4] = {~0u, ~0u, ~0u, ~0u};
            const int fr = j + 8 * (mi >> 1);
            uint32_t wa = SW + 12 * STAGE + fw * 2048 + fr * 32 + (((mi & 1) ^ ((fr >> 2) & 1)) << 4), ha = SW + fw * 1024 + lane * 16;
#pragma unroll 1
            for (int s0 = 0; s0 < 12; s0 += 3) {
                uint32_t a[6][8], b[6][4];
#pragma unroll
                for (int s = 0; s < 3; s++) {
                    if (s == 2 && s0 == 9) wa += S + SM_W_LAST - (SW + 23 * STAGE);
#pragma unroll
                    for (int e = 0; e < 2; e++) {
                        ldm4t(ha + e * 512, b[2 * s + e][0], b[2 * s + e][1], b[2 * s + e][2], b[2 * s + e][3]);
                        ldm4t(wa + e * 1024, a[2 * s + e][0], a[2 * s + e][1], a[2 * s + e][2], a[2 * s + e][3]);
                        ldm4t(wa + e * 1024 + 512, a[2 * s + e][4], a[2 * s + e][5], a[2 * s + e][6], a[2 * s + e][7]);
                    }
                    wa += STAGE; ha += 3072;
                }
#pragma unroll
                for (int k = 0; k < 6; k++) {
                    mma_bf(dn[2 * (k & 1)], a[k][0], a[k][1], a[k][2], a[k][3], b[k][0], b[k][1]);
                    mma_bf(dn[2 * (k & 1) + 1], a[k][4], a[k][5], a[k][6], a[k][7], b[k][2], b[k][3]);
#pragma unroll
                    for (int q = 0; q < 4; q++) bq[q] = __vminu2(bq[q], b[k][q]);
                }
            }
            const uint32_t bm = __vminu2(__vminu2(bq[0], bq[1]), __vminu2(bq[2], bq[3])), bd = (bm - 0x00010001u) & ~bm;
            uint32_t anybad;
            asm volatile("{.reg .pred p, q; setp.ne.u32 p, %1, 0; bar.red.or.pred q, 9, 96, p; selp.u32 %0, 1, 0, q;}" : "=r"(anybad) : "r"(bd & 0x80008000u) : "memory");
            if (!anybad) break;
        }
        float* red = (float*)(smem + SM_RED + fw * 512);
        red[(2 * t) * 16 + g] = (dn[0][0] + dn[1][0]) + (dn[2][0] + dn[3][0]);
        red[(2 * t + 1) * 16 + g] = (dn[0][1] + dn[1][1]) + (dn[2][1] + dn[3][1]);
        red[(2 * t) * 16 + g + 8] = (dn[0][2] + dn[1][2]) + (dn[2][2] + dn[3][2]);
        red[(2 * t + 1) * 16 + g + 8] = (dn[0][3] + dn[1][3]) + (dn[2][3] + dn[3][3]);
        bar_sync(9, 96);
        if (fw < 2) {
            const float* rs = (const float*)(smem + SM_RED);
            const int mine = 64 * r + fi, other = mine ^ 64;
            st_async32(ob + SM_RP + 4 * fi, __float_as_uint(rs[other] + rs[128 + other] + rs[256 + other]), ob + B_RED * 8);
            const float s = rs[mine] + rs[128 + mine] + rs[256 + mine];
#pragma unroll 1
            for (int it = 0; it < SPIN_LIMIT && (yv2.x & 1) != tag; it++)
                asm volatile("ld.relaxed.gpu.global.v2.u32 {%0,%1}, [%2];" : "=r"(yv2.x), "=r"(yv2.y) : "l"(ya) : "memory");
            const uint32_t yw = (row & 8) ? yv2.y : yv2.x;
            const float sg = bf_round(((row & 1) ? bf_hi(yw) : bf_lo(yw)) + bf_round(xn * dsk));
            mbar_wait(S + B_RED * 8, 0);
            const float o = *(const float*)(smem + SM_RP + 4 * fi);
            const float yv = bf_round(bf_round(r == 0 ? s + o : o + s) * bf_hi(sel));
            p.out[(size_t)row * D_ + cc] = __float2bfloat16(xraw + bf_round(sg * bf_round(silu_f(bf_round(xn + yv)))));
            if (bid == 0 && fi == 0) st_rlx(&p.s->cnt[16 * 32], epoch);
        }
    }
}

typedef CUresult (*EncodeFn)(CUtensorMap*, CUtensorMapDataType, cuuint32_t, void*, const cuuint64_t*, const cuuint64_t*, const cuuint32_t*,
                             const cuuint32_t*, CUtensorMapInterleave, CUtensorMapSwizzle, CUtensorMapL2promotion, CUtensorMapFloatOOBfill);

static void make2d(EncodeFn enc, CUtensorMap* m, const void* base, uint64_t cols, uint64_t rows, uint32_t bc, uint32_t br, CUtensorMapSwizzle sw) {
    cuuint64_t gd[2] = {cols, rows};
    cuuint64_t gs[1] = {cols * 2};
    cuuint32_t bd[2] = {bc, br}, es[2] = {1, 1};
    enc(m, CU_TENSOR_MAP_DATA_TYPE_BFLOAT16, 2, const_cast<void*>(base), gd, gs, bd, es, CU_TENSOR_MAP_INTERLEAVE_NONE, sw,
        CU_TENSOR_MAP_L2_PROMOTION_L2_128B, CU_TENSOR_MAP_FLOAT_OOB_FILL_NONE);
}

static Tune g_tune = {2000, 9000, 3, 5, 8, 5000, 7500, 0, 9000, 1, 0, 0};


static void launch(void* const* d_in, void* d_out) {
    static EncodeFn enc = nullptr;
    static Scratch* gs = nullptr;
    if (!enc) {
        void* fn = nullptr;
        cudaDriverEntryPointQueryResult qr;
        cudaGetDriverEntryPoint("cuTensorMapEncodeTiled", &fn, cudaEnableDefault, &qr);
        enc = (EncodeFn)fn;
        cudaFuncSetAttribute(fused_kernel, cudaFuncAttributeMaxDynamicSharedMemorySize, SM_TOTAL);
        cudaGetSymbolAddress((void**)&gs, g_s);
    }
    Hot p;
    Maps m;
    auto in = [&](int i) { return (const __nv_bfloat16*)d_in[i]; };
    p.u = in(0); p.are = in(1); p.aim = in(2); p.bre = in(3); p.bim = in(4); p.cre = in(5); p.cim = in(6);
    p.logdt = in(7); p.dskip = in(8); p.wr = in(10); p.pwg = in(11); p.pwu = in(12); p.pwd = in(13);
    p.out = (__nv_bfloat16*)d_out;
    p.tn = g_tune;
    p.s = gs;
    make2d(enc, &m.wg, p.pwg, F_, D_, 32, 96, CU_TENSOR_MAP_SWIZZLE_64B);
    make2d(enc, &m.wu, p.pwu, F_, D_, 32, 96, CU_TENSOR_MAP_SWIZZLE_64B);
    make2d(enc, &m.wd, p.pwd, D_, F_, 16, 192, CU_TENSOR_MAP_SWIZZLE_32B);
    fused_kernel<<<NCTA, NTHREADS, SM_TOTAL>>>(p, m);
}

}

extern "C" void kernel_launch(void* const* d_in, const int* in_sizes, int n_in, void* d_out, int out_size) {
    static int clusters = -1;
    if (clusters < 0) clusters = v3::max_clusters();
    if (clusters < 15 || !v3::launch(d_in, d_out)) v2::launch(d_in, d_out);
}
```

```cpp
#include <cuda_runtime.h>
#include <cuda_bf16.h>
#include <cuda_fp16.h>
#include <cuda.h>
#include <stdint.h>
#include <stddef.h>
#include <type_traits>


namespace v3 {

constexpr bool LD4 = false, ZZ = true;

constexpr int D_ = 576, F_ = 4608;
constexpr int NCTA = 120, NTHREADS = 512;
constexpr int SPIN_LIMIT = 1 << 16;

enum { B_Y = 0, B_X = 8, B_TOP = 10, B_XS = 12, B_UP = 13, B_RAW = 15, B_FULL = 16, B_FIN = 43, B_SEL = 44, B_EMPTY = 38  , B_ROWS = 66, B_WR = 67 };
constexpr int SM_SKIP = 544, SM_SEL = 576;
constexpr int SM_ST = 640;
constexpr int SM_RAW = 2688, PITCH = 80;
constexpr int SM_CH = SM_RAW + 256 * PITCH, CH = 18304;
constexpr int TAB = 0, FT = 3072, XX = 3712, BOX = 8064, YIN = 14208;
constexpr int SM_B = SM_CH + 5 * CH, BP = 1168;
constexpr int SM_CAND = SM_B + 8 * BP, SM_PROG = SM_CAND + 256, SM_DUMP = SM_PROG + 128;
constexpr int NRING = 12, SM_W = SM_B + 10240, SM_FIN = SM_W + NRING * 8192, SM_TOTAL = 232448;
static_assert(SM_W % 1024 == 0 && SM_FIN + 8192 <= SM_TOTAL && SM_TOTAL - 18432 >= SM_W + 10 * 8192, "smem");

struct Tune { int t_tile, stag, tail, win0, s0, t_rows, da, t_pf, zero; };

struct Scratch {
    uint32_t h[8 * 2304];
    uint2 stat[2048];
    uint32_t ep[NCTA * 8];
};
__device__ __align__(1024) Scratch g_s;

struct Hot {
    const __nv_bfloat16* u;
    int bre, bim, cre, cim, are, aim, logdt, dskip, wr, ep;
    Scratch* s;
    __nv_bfloat16* out;
    const __nv_bfloat16* wg;
    Tune tn;
};
struct Maps { CUtensorMap w[3], u; };

__device__ __forceinline__ uint32_t smem_u32(const void* p) { return (uint32_t)__cvta_generic_to_shared(p); }
__device__ __forceinline__ void mbar_init(uint32_t b, int c) { asm volatile("mbarrier.init.shared::cta.b64 [%0], %1;" ::"r"(b), "r"(c) : "memory"); }
__device__ __forceinline__ void mbar_expect(uint32_t b, int bytes) { asm volatile("mbarrier.arrive.expect_tx.shared::cta.b64 _, [%0], %1;" ::"r"(b), "r"(bytes) : "memory"); }
__device__ __forceinline__ void mbar_arrive(uint32_t b) { asm volatile("mbarrier.arrive.shared::cta.b64 _, [%0];" ::"r"(b) : "memory"); }
__device__ __forceinline__ bool elect() { uint32_t d; asm volatile("{.reg .pred p; elect.sync _|p, 0xffffffff; selp.u32 %0,1,0,p;}" : "=r"(d)); return d; }
__device__ __forceinline__ void mbar_wait(uint32_t b, int par) {
    asm volatile("{\n.reg .pred p;\nLW:\nmbarrier.try_wait.parity.shared::cta.b64 p, [%0], %1, 2000;\n@!p bra LW;\n}" ::"r"(b), "r"(par) : "memory");
}
__device__ __forceinline__ void mbar_wait_short(uint32_t b) {
    asm volatile("{\n.reg .pred p;\nLW:\nmbarrier.try_wait.parity.shared::cta.b64 p, [%0], 0;\n@!p bra LW;\n}" ::"r"(b) : "memory");
}
__device__ __forceinline__ uint32_t mapa(uint32_t a, uint32_t rank) { uint32_t d; asm("mapa.shared::cluster.u32 %0, %1, %2;" : "=r"(d) : "r"(a), "r"(rank)); return d; }
__device__ __forceinline__ void tma2d(uint32_t dst, const CUtensorMap* m, int c0, int c1, uint32_t bar) {
    asm volatile("cp.async.bulk.tensor.2d.shared::cluster.global.mbarrier::complete_tx::bytes [%0], [%1, {%3, %4}], [%2];" ::"r"(dst), "l"(m), "r"(bar), "r"(c0), "r"(c1) : "memory");
}
__device__ __forceinline__ void bulk_g2s(uint32_t dst, const void* src, int bytes, uint32_t bar) {
    asm volatile("cp.async.bulk.shared::cluster.global.mbarrier::complete_tx::bytes [%0], [%1], %2, [%3];" ::"r"(dst), "l"(src), "r"(bytes), "r"(bar) : "memory");
}
__device__ __forceinline__ void bulk_mc(uint32_t dst, const void* src, int bytes, uint32_t bar) {
    asm volatile("cp.async.bulk.shared::cluster.global.mbarrier::complete_tx::bytes.multicast::cluster [%0], [%1], %2, [%3], %4;"
                 ::"r"(dst), "l"(src), "r"(bytes), "r"(bar), "h"((uint16_t)255) : "memory");
}
__device__ __forceinline__ void bar_sync(int id, int n) { asm volatile("bar.sync %0, %1;" ::"r"(id), "r"(n) : "memory"); }
__device__ __forceinline__ void bar_arrive(int id, int n) { asm volatile("bar.arrive %0, %1;" ::"r"(id), "r"(n) : "memory"); }
__device__ __forceinline__ uint4 ld_rlx4(const void* p) { uint4 v; asm volatile("ld.relaxed.gpu.global.v4.u32 {%0,%1,%2,%3}, [%4];" : "=r"(v.x), "=r"(v.y), "=r"(v.z), "=r"(v.w) : "l"(p) : "memory"); return v; }
__device__ __forceinline__ uint2 ld_rlx2(const void* p) { uint2 v; asm volatile("ld.relaxed.gpu.global.v2.u32 {%0,%1}, [%2];" : "=r"(v.x), "=r"(v.y) : "l"(p) : "memory"); return v; }
__device__ __forceinline__ uint32_t ld_rlx(const void* p) { uint32_t v; asm volatile("ld.relaxed.gpu.global.u32 %0, [%1];" : "=r"(v) : "l"(p) : "memory"); return v; }
__device__ __forceinline__ void st_rlx(void* p, uint32_t v) { asm volatile("st.relaxed.gpu.global.u32 [%0], %1;" ::"l"(p), "r"(v) : "memory"); }
__device__ __forceinline__ void st_rlx2(void* p, uint32_t x, uint32_t y) { asm volatile("st.relaxed.gpu.global.v2.u32 [%0], {%1,%2};" ::"l"(p), "r"(x), "r"(y) : "memory"); }
__device__ __forceinline__ uint4 ldg4(const void* p) { uint4 v; asm volatile("ld.global.nc.v4.u32 {%0,%1,%2,%3}, [%4];" : "=r"(v.x), "=r"(v.y), "=r"(v.z), "=r"(v.w) : "l"(p)); return v; }
__device__ __forceinline__ uint32_t ldg1(const void* p) { uint32_t v; asm volatile("ld.global.nc.u32 %0, [%1];" : "=r"(v) : "l"(p)); return v; }
__device__ __forceinline__ uint32_t ldg16(const void* p) { uint16_t v; asm volatile("ld.global.nc.u16 %0, [%1];" : "=h"(v) : "l"(p)); return v; }
__device__ __forceinline__ const void* at256(const void* b, int o) { const void* r; asm("mad.wide.s32 %0, %1, 256, %2;" : "=l"(r) : "r"(o), "l"(b)); return r; }
__device__ __forceinline__ int laneid() { int v; asm volatile("mov.u32 %0, %%laneid;" : "=r"(v)); return v; }
__device__ __forceinline__ uint32_t keep(uint32_t v) { return __shfl_xor_sync(~0u, v, 0); }
__device__ __forceinline__ int ctaid() { int v; asm volatile("mov.u32 %0, %%ctaid.x;" : "=r"(v)); return v; }
__device__ __forceinline__ uint32_t lds32(uint32_t a) { uint32_t v; asm volatile("ld.shared.u32 %0, [%1];" : "=r"(v) : "r"(a) : "memory"); return v; }
__device__ __forceinline__ uint32_t lds32v(uint32_t a) { uint32_t v; asm volatile("ld.volatile.shared.u32 %0, [%1];" : "=r"(v) : "r"(a) : "memory"); return v; }
__device__ __forceinline__ uint32_t lds16(uint32_t a) { uint16_t v; asm volatile("ld.shared.u16 %0, [%1];" : "=h"(v) : "r"(a) : "memory"); return v; }
__device__ __forceinline__ uint2 lds64(uint32_t a) { uint2 v; asm volatile("ld.shared.v2.u32 {%0,%1}, [%2];" : "=r"(v.x), "=r"(v.y) : "r"(a) : "memory"); return v; }
__device__ __forceinline__ uint4 lds128(uint32_t a) { uint4 v; asm volatile("ld.shared.v4.u32 {%0,%1,%2,%3}, [%4];" : "=r"(v.x), "=r"(v.y), "=r"(v.z), "=r"(v.w) : "r"(a) : "memory"); return v; }
__device__ __forceinline__ void sts16(uint32_t a, uint32_t v) { asm volatile("st.shared.u16 [%0], %1;" ::"r"(a), "h"((uint16_t)v) : "memory"); }
__device__ __forceinline__ void sts32(uint32_t a, uint32_t v) { asm volatile("st.shared.u32 [%0], %1;" ::"r"(a), "r"(v) : "memory"); }
__device__ __forceinline__ void sts32v(uint32_t a, uint32_t v) { asm volatile("st.volatile.shared.u32 [%0], %1;" ::"r"(a), "r"(v) : "memory"); }
__device__ __forceinline__ void sts64(uint32_t a, uint32_t x, uint32_t y) { asm volatile("st.shared.v2.u32 [%0], {%1,%2};" ::"r"(a), "r"(x), "r"(y) : "memory"); }
__device__ __forceinline__ void sts128(uint32_t a, uint32_t x, uint32_t y, uint32_t z, uint32_t w) { asm volatile("st.shared.v4.u32 [%0], {%1,%2,%3,%4};" ::"r"(a), "r"(x), "r"(y), "r"(z), "r"(w) : "memory"); }
__device__ __forceinline__ void sts128v(uint32_t a, uint32_t x, uint32_t y, uint32_t z, uint32_t w) { asm volatile("st.volatile.shared.v4.u32 [%0], {%1,%2,%3,%4};" ::"r"(a), "r"(x), "r"(y), "r"(z), "r"(w) : "memory"); }
__device__ __forceinline__ void sts128f(uint32_t a, float x, float y, float z, float w) { asm volatile("st.shared.v4.f32 [%0], {%1,%2,%3,%4};" ::"r"(a), "f"(x), "f"(y), "f"(z), "f"(w) : "memory"); }
__device__ __forceinline__ void st_async4(uint32_t a, uint32_t x, uint32_t y, uint32_t z, uint32_t w, uint32_t bar) {
    asm volatile("st.async.shared::cluster.mbarrier::complete_tx::bytes.v4.b32 [%0], {%1,%2,%3,%4}, [%5];" ::"r"(a), "r"(x), "r"(y), "r"(z), "r"(w), "r"(bar) : "memory");
}
__device__ __forceinline__ void st_async2(uint32_t a, uint32_t x, uint32_t y, uint32_t bar) {
    asm volatile("st.async.shared::cluster.mbarrier::complete_tx::bytes.v2.b32 [%0], {%1,%2}, [%3];" ::"r"(a), "r"(x), "r"(y), "r"(bar) : "memory");
}
__device__ __forceinline__ void st_async2f(uint32_t a, float x, float y, uint32_t bar) {
    asm volatile("st.async.shared::cluster.mbarrier::complete_tx::bytes.v2.f32 [%0], {%1,%2}, [%3];" ::"r"(a), "f"(x), "f"(y), "r"(bar) : "memory");
}
__device__ __forceinline__ void ldm4(uint32_t a, uint32_t& r0, uint32_t& r1, uint32_t& r2, uint32_t& r3) {
    asm volatile("ldmatrix.sync.aligned.m8n8.x4.shared.b16 {%0,%1,%2,%3}, [%4];" : "=r"(r0), "=r"(r1), "=r"(r2), "=r"(r3) : "r"(a) : "memory");
}
__device__ __forceinline__ void ldm4t(uint32_t a, uint32_t (&r)[4]) {
    asm volatile("ldmatrix.sync.aligned.m8n8.x4.trans.shared.b16 {%0,%1,%2,%3}, [%4];" : "=r"(r[0]), "=r"(r[1]), "=r"(r[2]), "=r"(r[3]) : "r"(a) : "memory");
}
__device__ __forceinline__ void ldm2(uint32_t a, uint32_t& r0, uint32_t& r1) {
    asm volatile("ldmatrix.sync.aligned.m8n8.x2.shared.b16 {%0,%1}, [%2];" : "=r"(r0), "=r"(r1) : "r"(a) : "memory");
}
__device__ __forceinline__ void ldm2t(uint32_t a, uint32_t& r0, uint32_t& r1) {
    asm volatile("ldmatrix.sync.aligned.m8n8.x2.trans.shared.b16 {%0,%1}, [%2];" : "=r"(r0), "=r"(r1) : "r"(a) : "memory");
}
__device__ __forceinline__ void stm4(uint32_t a, uint32_t r0, uint32_t r1, uint32_t r2, uint32_t r3) {
    asm volatile("stmatrix.sync.aligned.m8n8.x4.shared.b16 [%0], {%1,%2,%3,%4};" ::"r"(a), "r"(r0), "r"(r1), "r"(r2), "r"(r3) : "memory");
}
__device__ __forceinline__ void stm4t(uint32_t a, uint32_t r0, uint32_t r1, uint32_t r2, uint32_t r3) {
    asm volatile("stmatrix.sync.aligned.m8n8.x4.trans.shared.b16 [%0], {%1,%2,%3,%4};" ::"r"(a), "r"(r0), "r"(r1), "r"(r2), "r"(r3) : "memory");
}
__device__ __forceinline__ void stm2t(uint32_t a, uint32_t r0, uint32_t r1) {
    asm volatile("stmatrix.sync.aligned.m8n8.x2.trans.shared.b16 [%0], {%1,%2};" ::"r"(a), "r"(r0), "r"(r1) : "memory");
}
__device__ __forceinline__ uint32_t movm(uint32_t a) { uint32_t d; asm volatile("movmatrix.sync.aligned.m8n8.trans.b16 %0, %1;" : "=r"(d) : "r"(a)); return d; }
__device__ __forceinline__ void mma_bf(float (&c)[4], uint32_t a0, uint32_t a1, uint32_t a2, uint32_t a3, uint32_t b0, uint32_t b1) {
    asm volatile("mma.sync.aligned.m16n8k16.row.col.f32.bf16.bf16.f32 {%0,%1,%2,%3},{%4,%5,%6,%7},{%8,%9},{%0,%1,%2,%3};"
                 : "+f"(c[0]), "+f"(c[1]), "+f"(c[2]), "+f"(c[3]) : "r"(a0), "r"(a1), "r"(a2), "r"(a3), "r"(b0), "r"(b1));
}
__device__ __forceinline__ void mma_bf8(float (&c)[4], uint32_t a0, uint32_t a1, uint32_t b0) {
    asm volatile("mma.sync.aligned.m16n8k8.row.col.f32.bf16.bf16.f32 {%0,%1,%2,%3},{%4,%5},{%6},{%0,%1,%2,%3};"
                 : "+f"(c[0]), "+f"(c[1]), "+f"(c[2]), "+f"(c[3]) : "r"(a0), "r"(a1), "r"(b0));
}
__device__ __forceinline__ void mma_h(float (&c)[4], uint32_t a0, uint32_t a1, uint32_t a2, uint32_t a3, uint32_t b0, uint32_t b1) {
    asm volatile("mma.sync.aligned.m16n8k16.row.col.f32.f16.f16.f32 {%0,%1,%2,%3},{%4,%5,%6,%7},{%8,%9},{%0,%1,%2,%3};"
                 : "+f"(c[0]), "+f"(c[1]), "+f"(c[2]), "+f"(c[3]) : "r"(a0), "r"(a1), "r"(a2), "r"(a3), "r"(b0), "r"(b1));
}
__device__ __forceinline__ void mma_h8(float (&c)[4], uint32_t a0, uint32_t a1, uint32_t b0) {
    asm volatile("mma.sync.aligned.m16n8k8.row.col.f32.f16.f16.f32 {%0,%1,%2,%3},{%4,%5},{%6},{%0,%1,%2,%3};"
                 : "+f"(c[0]), "+f"(c[1]), "+f"(c[2]), "+f"(c[3]) : "r"(a0), "r"(a1), "r"(b0));
}
template <int LIM>
__device__ __forceinline__ void mma_hp(int n, float (&d)[4], const float (&c)[4], uint32_t a0, uint32_t a1, uint32_t a2, uint32_t a3, uint32_t b0, uint32_t b1) {
    asm volatile("{.reg .pred p; setp.gt.s32 p, %14, %15;\n"
                 "@p mma.sync.aligned.m16n8k16.row.col.f32.f16.f16.f32 {%0,%1,%2,%3},{%4,%5,%6,%7},{%8,%9},{%10,%11,%12,%13};}"
                 : "+f"(d[0]), "+f"(d[1]), "+f"(d[2]), "+f"(d[3])
                 : "r"(a0), "r"(a1), "r"(a2), "r"(a3), "r"(b0), "r"(b1), "f"(c[0]), "f"(c[1]), "f"(c[2]), "f"(c[3]), "r"(n), "n"(LIM));
}
template <int LIM>
__device__ __forceinline__ void mma_hq(int n, float (&d)[4], uint32_t a0, uint32_t a1, uint32_t a2, uint32_t a3, uint32_t b0, uint32_t b1) {
    asm volatile("{.reg .pred p; setp.gt.s32 p, %10, %11;\n"
                 "@p mma.sync.aligned.m16n8k16.row.col.f32.f16.f16.f32 {%0,%1,%2,%3},{%4,%5,%6,%7},{%8,%9},{%0,%1,%2,%3};}"
                 : "+f"(d[0]), "+f"(d[1]), "+f"(d[2]), "+f"(d[3]) : "r"(a0), "r"(a1), "r"(a2), "r"(a3), "r"(b0), "r"(b1), "r"(n), "n"(LIM));
}
__device__ __forceinline__ void mma_hc(float (&d)[4], const float (&c)[4], uint32_t a0, uint32_t a1, uint32_t a2, uint32_t a3, uint32_t b0, uint32_t b1) {
    asm volatile("mma.sync.aligned.m16n8k16.row.col.f32.f16.f16.f32 {%0,%1,%2,%3},{%4,%5,%6,%7},{%8,%9},{%10,%11,%12,%13};"
                 : "=f"(d[0]), "=f"(d[1]), "=f"(d[2]), "=f"(d[3]) : "r"(a0), "r"(a1), "r"(a2), "r"(a3), "r"(b0), "r"(b1), "f"(c[0]), "f"(c[1]), "f"(c[2]), "f"(c[3]));
}
__device__ __forceinline__ uint32_t pack_bf(float lo, float hi) { uint32_t r; asm("cvt.rn.bf16x2.f32 %0, %1, %2;" : "=r"(r) : "f"(hi), "f"(lo)); return r; }
__device__ __forceinline__ uint32_t pack_h(float lo, float hi) { uint32_t r; asm("cvt.rn.f16x2.f32 %0, %1, %2;" : "=r"(r) : "f"(hi), "f"(lo)); return r; }
__device__ __forceinline__ float bf_lo(uint32_t w) { return __uint_as_float(w << 16); }
__device__ __forceinline__ float bf_hi(uint32_t w) { return __uint_as_float(w & 0xFFFF0000u); }
__device__ __forceinline__ float bf_round(float x) { return __uint_as_float(pack_bf(0.f, x)); }
__device__ __forceinline__ uint32_t badd(uint32_t a, uint32_t b) { uint32_t r; asm("add.rn.bf16x2 %0, %1, %2;" : "=r"(r) : "r"(a), "r"(b)); return r; }
__device__ __forceinline__ uint32_t bsub(uint32_t a, uint32_t b) { uint32_t r; asm("sub.rn.bf16x2 %0, %1, %2;" : "=r"(r) : "r"(a), "r"(b)); return r; }
__device__ __forceinline__ uint32_t bmul(uint32_t a, uint32_t b) { uint32_t r; asm("mul.rn.bf16x2 %0, %1, %2;" : "=r"(r) : "r"(a), "r"(b)); return r; }
__device__ __forceinline__ uint32_t bfma(uint32_t a, uint32_t b, uint32_t c) { uint32_t r; asm("fma.rn.bf16x2 %0, %1, %2, %3;" : "=r"(r) : "r"(a), "r"(b), "r"(c)); return r; }
__device__ __forceinline__ uint32_t hadd(uint32_t a, uint32_t b) { uint32_t r; asm("add.rn.f16x2 %0, %1, %2;" : "=r"(r) : "r"(a), "r"(b)); return r; }
__device__ __forceinline__ uint32_t prmt(uint32_t a, uint32_t b, uint32_t s) { uint32_t r; asm("prmt.b32 %0, %1, %2, %3;" : "=r"(r) : "r"(a), "r"(b), "r"(s)); return r; }
__device__ __forceinline__ uint32_t lop_ne(uint32_t a, uint32_t b, uint32_t c) { uint32_t r; asm("lop3.b32 %0, %1, %2, %3, 0x7E;" : "=r"(r) : "r"(a), "r"(b), "r"(c)); return r; }
__device__ __forceinline__ float ex2f(float x) { float r; asm("ex2.approx.ftz.f32 %0, %1;" : "=f"(r) : "f"(x)); return r; }
__device__ __forceinline__ float rcpf(float x) { float r; asm("rcp.approx.ftz.f32 %0, %1;" : "=f"(r) : "f"(x)); return r; }
__device__ __forceinline__ float sqrt_ap(float x) { float r; asm("sqrt.approx.ftz.f32 %0, %1;" : "=f"(r) : "f"(x)); return r; }
__device__ __forceinline__ float tanh_ap(float x) { float r; asm("tanh.approx.f32 %0, %1;" : "=f"(r) : "f"(x)); return r; }
__device__ __forceinline__ float sigm(float x) { return rcpf(1.f + ex2f(-1.4426950408889634f * x)); }
__device__ __forceinline__ float silu_half(float h) { return fmaf(h, tanh_ap(h), h); }
__device__ __forceinline__ uint32_t clk32() { uint32_t c; asm volatile("mov.u32 %0, %%clock;" : "=r"(c)); return c; }
__device__ __forceinline__ void spin_until(uint32_t t0, int dt) {
#pragma unroll 1
    while ((int)(clk32() - t0) < dt) __nanosleep(32);
}
__device__ __forceinline__ void cp16(uint32_t dst, const void* src) { asm volatile("cp.async.cg.shared.global [%0], [%1], 16;" ::"r"(dst), "l"(src) : "memory"); }

__device__ __forceinline__ uint32_t xslot(int s, int h) { return XX + 32 * (s & ~1) + 16 * ((2 * h + (s & 1)) ^ ((s >> 1) & 2)); }

struct cf { float x, y; };
__device__ __forceinline__ cf cmul(cf a, cf b) { return {a.x * b.x - a.y * b.y, a.x * b.y + a.y * b.x}; }
__device__ __forceinline__ cf csq(cf a) { return {a.x * a.x - a.y * a.y, (a.x + a.x) * a.y}; }
__device__ __forceinline__ cf cpow_direct(float zr2, float zi, float l) {
    const float mag = ex2f(zr2 * l), th = zi * l;
    return {mag * __cosf(th), mag * __sinf(th)};
}
struct hp { uint32_t re, im; };
struct hm { __half2 v; };
__device__ __forceinline__ __half2 as_h2(uint32_t v) { return *reinterpret_cast<__half2*>(&v); }
__device__ __forceinline__ uint32_t as_u32(__half2 v) { return *reinterpret_cast<uint32_t*>(&v); }
__device__ __forceinline__ hp mk2(cf a, cf b) { return {pack_h(a.x, b.x), pack_h(a.y, b.y)}; }
__device__ __forceinline__ hm mk1(cf a) { return {as_h2(pack_h(a.x, a.y))}; }
__device__ __forceinline__ hp his(hp a, hp b) { return {prmt(a.re, b.re, 0x7632), prmt(a.im, b.im, 0x7632)}; }
__device__ __forceinline__ hp operator*(hp a, hm b) {
    const __half2 c = __low2half2(b.v), s = __high2half2(b.v), x = as_h2(a.re), y = as_h2(a.im);
    return {as_u32(__hfma2(x, c, __hneg2(__hmul2_rn(y, s)))), as_u32(__hfma2(x, s, __hmul2_rn(y, c)))};
}
struct KParams { uint32_t are, aim, bre, bim, cre, cim, ldt, dsk, sa, la, lb; };

__device__ __forceinline__ uint32_t kgen(KParams kp, uint32_t scr, uint32_t oth, int bar, int lane, float (&d)[5][4], float& k0, int nc, uint32_t pause) {
    const float dt = bf_round(ex2f(bf_lo(kp.ldt) * 1.4426950408889634f));
    cf w = cmul({bf_lo(kp.cre), bf_lo(kp.cim)}, {dt * bf_lo(kp.bre), dt * bf_lo(kp.bim)});
    cf w1 = cmul({bf_hi(kp.cre), bf_hi(kp.cim)}, {dt * bf_hi(kp.bre), dt * bf_hi(kp.bim)});
    const float dk = bf_lo(kp.dsk), dt2 = dt * 1.4426950408889634f;
    uint32_t z = prmt(kp.are, kp.aim, 0x5410), z1 = prmt(kp.are, kp.aim, 0x7632);
    uint32_t eb = __reduce_max_sync(~0u, __float_as_uint(fmaxf(fmaxf(fmaxf(fabsf(w.x), fabsf(w.y)), fmaxf(fabsf(w1.x), fabsf(w1.y))), fabsf(dk) * 0x1p-20f)));
    k0 = w.x + w1.x;
    const uint32_t sa = kp.sa, la = kp.la, lb = kp.lb;
    sts128(oth + 2048 + 16 * lane, __float_as_uint(w1.x), __float_as_uint(w1.y), z1, __float_as_uint(k0));
    sts32(oth + 2560, eb);
    bar_sync(bar, 64);
    const uint4 ov = lds128(sa + 2048);
    eb = min(max(max(eb, lds32(scr + 2560)) & 0x7F800000u, 0x00800000u), 0x7A000000u);
    const float sc = __uint_as_float(0x7B000000u - eb);
    k0 = fmaf(dk, sc, 0x1p-28f * __reduce_add_sync(~0u, __float2int_rn((k0 + __uint_as_float(ov.w)) * sc * 0x1p28f)));
#pragma unroll
    for (int i = 0; i < 5; i++) d[i][0] = d[i][1] = d[i][2] = d[i][3] = 0.f;
    auto st = [&](int grp, hp a, hp b, hp c, hp e) { sts128v(sa + 1024 * grp, a.re, b.re, c.re, e.re); sts128v(sa + 1024 * grp + 512, a.im, b.im, c.im, e.im); };
#pragma unroll 1
    do {
        const float zr2 = dt2 * bf_lo(z), zi = dt * bf_hi(z);
        const cf ws = {w.x * sc, w.y * sc};
        z = z1; w = w1;
        z1 = ov.z; w1 = {__uint_as_float(ov.x), __uint_as_float(ov.y)};
        const cf a1 = cpow_direct(zr2, zi, 1.f), a256 = cpow_direct(zr2, zi, 256.f);
        uint32_t a[4][4];
        {
            const cf b1 = cpow_direct(-zr2, zi, -16.f), b2 = csq(b1), b4 = csq(b2), b8 = csq(b4);
            const hm m2 = mk1(b2), m4 = mk1(b4), m8 = mk1(b8);
            const hp u0 = mk2({1.f, 0.f}, b1), u1 = u0 * m2, u2 = u0 * m4, u3 = u1 * m4;
            __syncwarp();
            st(1, u0 * m8, u1 * m8, u2 * m8, u3 * m8);
            st(0, u0, u1, u2, u3);
            __syncwarp();
#pragma unroll
            for (int k = 0; k < 4; k++) ldm4t(la + 128 * k, a[k]);
        }
        auto tile = [&](int T, int grp) {
#pragma unroll
            for (int e = 0; e < 2; e++) {
                uint32_t b[4];
                ldm4t(lb + 1024 * grp + 256 * e, b);
                mma_h(d[T], a[2 * e][0], a[2 * e][1], a[2 * e][2], a[2 * e][3], b[0], b[1]);
                mma_h(d[T], a[2 * e + 1][0], a[2 * e + 1][1], a[2 * e + 1][2], a[2 * e + 1][3], b[2], b[3]);
            }
        };
        const cf a2 = csq(a1), a4 = csq(a2), a8 = csq(a4), a512 = csq(a256), a1024 = csq(a512);
        const hm m2 = mk1(a2), m4 = mk1(a4), m8 = mk1(a8), m256 = mk1(a256), m512 = mk1(a512);
        const hp v1 = mk2(cmul(ws, a1), cmul(ws, a2)), v3 = v1 * m2, v5 = v1 * m4, v7 = v3 * m4, v15 = v7 * m8;
        const hp e1 = his(v1, v3) * m256, e2 = e1 * m4;
        hp f0 = his(v3, v7), g0 = his(v7, v15);
        asm volatile("" : "+r"(f0.re), "+r"(f0.im), "+r"(g0.re), "+r"(g0.im));
        __syncwarp();
        st(2, e1, e2, e1 * m8, e2 * m8);
        st(0, v1, v5, v1 * m8, v5 * m8);
        st(1, v3, v7, v3 * m8, v15);
        __syncwarp();
        tile(0, 0); tile(1, 1); tile(2, 2);
        const hp f1 = f0 * m512, f2 = f1 * m8, g1 = g0 * mk1(a1024), g2 = g1 * m256;
        __syncwarp();
        st(0, f1, f2, f1 * m256, f2 * m256);
        st(1, g1, g2, g1 * m512, g2 * m512);
        __syncwarp();
        tile(3, 0); tile(4, 1);
        if (pause && nc > 1) mbar_wait_short(pause);
    } while (--nc);
    return eb;
}

__device__ __forceinline__ void near_lags(uint32_t S, int k, uint32_t yo, uint32_t eb, const uint32_t (&xa)[8]) {
    const int lane = threadIdx.x & 31, g = lane >> 2, t = lane & 3, mi = lane >> 3, j = lane & 7, warp = k;
    const uint32_t cb = S + SM_CH + k * CH;
    uint32_t R[66], x[5];
#pragma unroll
    for (int i = 0; i < 66; i++) R[i] = lds32(cb + TAB + 4 * (7 + g - 2 * t) + 32 * i);
    bar_arrive(1 + k, 64);
    float w[5][4];
#pragma unroll
    for (int i = 0; i < 5; i++) w[i][0] = w[i][1] = w[i][2] = w[i][3] = 0.f;
    uint32_t xo = cb;
    uint32_t fa = xa[0], idm = 0;
    uint32_t ya = S + SM_DUMP + 8 * lane, ybar = S + 61 * 8, dy = 0, db = 0;
    const uint32_t sc = prmt(eb + 0x04800000u, 0, 0x3232);
    uint32_t z = lds32(cb + XX + 4 * lane);
    int n = 16;
    mbar_wait(S + B_X * 8, 0);
    uint32_t A[3][4];
    if (LD4) {
        ldm4(xo + xa[0], A[0][0], A[0][1], A[0][2], A[0][3]);
        ldm4(xo + xa[1], A[1][0], A[1][1], A[1][2], A[1][3]);
    } else {
        ldm2(xo + xa[0], x[1], x[0]);
        ldm2(xo + xa[1], x[1], x[2]);
        ldm2(xo + xa[2], x[3], x[4]);
    }
    auto send = [&]() { st_async2(ya, bmul(pack_bf(w[0][0], w[0][1]), sc), bmul(pack_bf(w[0][2], w[0][3]), sc), ybar); };
    auto tile = [&](auto nj) {
        constexpr int NJ = decltype(nj)::value;
        asm volatile("" : "+r"(z), "+r"(xo));
        uint32_t f0, f1;
        ldm2(xo + fa, f0, f1);
        send();
#pragma unroll
        for (int q = 1; q <= 8; q++) {
            uint32_t n0, n1, a2, a3;
            if (LD4) {
                ldm4(xo + xa[(q + 1) & 7] + 32 * ((q + 1) & 8), A[2][0], A[2][1], A[2][2], A[2][3]);
                x[1] = A[0][0]; x[2] = A[0][1]; a2 = A[0][2]; a3 = A[0][3];
#pragma unroll
                for (int e = 0; e < 4; e++) { A[0][e] = A[1][e]; A[1][e] = A[2][e]; }
            } else {
                ldm2(xo + xa[(q + 2) & 7] + 32 * ((q + 2) & 8), n0, n1);
                a2 = x[0] | z; a3 = x[1] | z;
            }
#pragma unroll
            for (int i = 0; i < NJ; i++) {
                const int s = 16 * i + 16 - 2 * q;
                if (q == 1) mma_hc(w[i], w[i + 1], x[1], x[2], a2, a3, R[s], R[s + 1]);
                else mma_h(w[i], x[1], x[2], a2, a3, R[s], R[s + 1]);
            }
            if (q == 4) mma_h8(w[1], f0, f1, idm);
            if (q == 7 && ZZ) {
                const uint32_t zz = x[1] & z;
                ya += dy + zz; ybar += db + zz; dy = 512 - dy; db = 8 - db;
            }
            if (q == 8 && NJ == 4) {
                const float zero[4] = {0.f, 0.f, 0.f, 0.f};
                mma_hc(w[4], zero, x[1], x[2], a2, a3, R[64], R[65]);
            }
            if (!LD4) { x[0] = x[2]; x[1] = x[3]; x[2] = x[4]; x[3] = n0; x[4] = n1; }
        }
        xo += 256; if (!ZZ) { ya += dy; ybar += db; dy = 512 - dy; db = 8 - db; }
    };
    int lim = 15;
#pragma unroll 1
    for (;;) {
        n -= lim;
#pragma unroll 1
        do tile(std::integral_constant<int, 4>()); while (--n);
        n = lim;
        if (n < 5) break;
        const int lane = laneid(), g = lane >> 2, t = lane & 3;
        if (n == 15) {
            ybar = mapa(S + B_Y * 8, g >> 1);
            db = dy = mapa(S + B_Y * 8, 4 + (g >> 1)) - ybar;
            ya = ybar - B_Y * 8 + SM_CH + k * CH + YIN + (yo ^ (8 * (lane & 7)));
        }
        if (n == 13) { fa = TAB - 768 + 16 * (lane & 15); idm = g == 2 * t ? 0x3C00u : (g == 2 * t + 1 ? 0x3C000000u : 0u); }
#pragma unroll 1
        while ((lim = lds32v(S + SM_PROG + 4 * k)) >= n) __nanosleep(40);
        if (n == 15) lim = 13;
    }
#pragma unroll 1
    for (; n > 0; n--) tile(std::integral_constant<int, 2>());
    send();
}

__global__ void __cluster_dims__(8, 1, 1) __launch_bounds__(NTHREADS, 1) fused_kernel(const __grid_constant__ Hot p, const __grid_constant__ Maps m) {
    extern __shared__ __align__(1024) char smem[];
    const uint32_t t0 = clk32();
    const int tid = threadIdx.x, lane = tid & 31, bx = blockIdx.x;
    {
        const uint32_t a = min(tid >> 5, 5), ln = 10 * bx + lane;
        const void* pa = at256(p.u + ln * 64, (&p.bre)[a]);
        asm volatile("{.reg .pred p; setp.lt.u32 p, %1, 10; setp.lt.and.u32 p, %2, 192, p; setp.lt.and.u32 p, %3, 1152, p;\n@p prefetch.global.L2 [%0];}"
                     ::"l"(pa), "r"(lane), "r"(tid), "r"(ln) : "memory");
    }
    const int g = lane >> 2, t = lane & 3, mi = lane >> 3, j = lane & 7;
    const uint32_t role = __shfl_sync(~0u, (tid >> 5) | ((uint32_t)((bx < 24 ? 0x5776666632103210ull : 0x5436666621043210ull) >> ((tid >> 3) & 60)) & 15) << 8 |
                                               max(4 * (bx >> 3), 5 * (bx >> 3) - 3) << 16 | bx << 24, 0);
    const int warp = role & 255, k = (role >> 8) & 255, cbase = (role >> 13) & 0x7F8, bid = role >> 24, r = bid & 7, cl = role >> 27;
    const int pair = cl > 2, nch = 4 + pair;
    uint32_t S = smem_u32(smem);
    asm volatile("" : "+r"(S));

    const int half = warp >= nch;
    const bool two = cl == 1 || cl == 2, extra = two && k == 7, svcwarp = (warp >> 2) == 2;
    KParams kp;
    uint32_t epoch, pre[8];
    if (k < nch) {
        const uint32_t ch = cbase + 8 * k + r;
        const char* pb = (const char*)p.u + (ch * 256 + half * 128 + lane * 4);
        kp.bre = ldg1(at256(pb, p.bre)); kp.bim = ldg1(at256(pb, p.bim));
        kp.cre = ldg1(at256(pb, p.cre)); kp.cim = ldg1(at256(pb, p.cim));
        kp.ldt = ldg16(at256(p.u + ch, lane & 1 ? p.dskip : p.logdt));
        kp.are = ldg1(at256(pb, p.are)); kp.aim = ldg1(at256(pb, p.aim));
        sts128(S + SM_CH + k * CH + 16 * lane + (half ? FT : (lane < 2 ? TAB : (lane < 8 ? TAB + 2048 : FT + 384))), 0u, 0u, 0u, 0u);
        sts32(S + SM_PROG + 4 * k, 13);
        const uint32_t scr = S + SM_CH + k * CH + BOX + 3072 * half + 16 * j;
        if (half) {
            const uint32_t a0 = BOX + 16 + 576 * (j & 1) + 16 * (j >> 1);
            pre[0] = keep(a0 + (mi == 1 ? 1152 : (mi == 2 ? 1136 : 0)));
            pre[1] = keep(a0 + 2304 + 1152 * (mi & 1) + 64 * (mi >> 1));
            pre[2] = keep(BOX + 16 + 4608 + 576 * (mi & 1) + 128 * (mi >> 1) + 16 * j);
            pre[3] = keep(BOX + 16 + (lane < 2 ? 1152 + 576 * lane : 2896));
            pre[4] = keep(xslot(8 + lane, 0));
            pre[5] = keep(xslot(7 + lane, 0));
            pre[6] = keep(FT + 56 + 128 * (t >> 1) + 8 * g + 4 * (t & 1));
            pre[7] = keep(g == 2 * t ? 0x4432 : (g == 2 * t + 1 ? 0x3244 : 0x4444));
        } else {
            const uint32_t v = xslot(lane & 15, lane >> 4);
#pragma unroll
            for (int i = 0; i < 8; i++) pre[i] = __shfl_sync(~0u, v, LD4 ? j + i + (mi == 1 ? 17 : (mi == 2 ? 16 : 1)) : j + 2 * (lane & 8) + i);
        }
        kp.sa = keep(scr + 128 * mi);
        kp.la = keep(scr + 1024 * (mi & 1) + 512 * (mi >> 1));
        kp.lb = keep(scr + 512 * (mi & 1) + 128 * (mi >> 1));
    } else if (warp == 12) {
        if (elect()) {
            mbar_init(S + B_WR * 8, 1);
            mbar_init(S + B_ROWS * 8, 1);
            mbar_expect(S + B_WR * 8, 1152);
            bulk_g2s(S + SM_B + 2048, (const char*)p.u + p.wr * 256ll, 1152, S + B_WR * 8);
            while ((int)(clk32() - t0) < p.tn.t_rows) {}
            mbar_expect(S + B_ROWS * 8, two ? 36864 : 18432);
            const __nv_bfloat16* src = p.u + (8 * (cl & 14) + 2 * r + (cl & 1)) * 9216;
            bulk_g2s(S + SM_TOTAL - 18432, src, 18432, S + B_ROWS * 8);
            if (two) bulk_g2s(S + SM_CH + 4 * CH - 128, p.u + (113 + 2 * r) * 9216, 18432, S + B_ROWS * 8);
        }
    } else if (svcwarp) {
        if (elect()) {
#pragma unroll
            for (int i = 0; i < 16; i++) mbar_init(S + (warp & 3) * 128 + i * 8, warp > (i < 14 ? 10 : 9) ? 4 : 1);
            asm volatile("fence.mbarrier_init.release.cluster;" ::: "memory");
        }
        __syncwarp();
        sts128(S + SM_B + 16 * tid, 0x3F803F80u, 0x3F803F80u, 0x3F803F80u, 0x3F803F80u);
        if (tid < 256 + B_RAW) mbar_expect(S + lane * 8, (uint32_t)(0x0808480101180804ull >> (8 * max(lane - 7, 0)) & 255) * (lane < B_TOP ? 128 * nch : 128));
    }
    if (svcwarp || extra) epoch = ld_rlx(at256(p.u + bid * 16, p.ep));
    __syncthreads();
    asm volatile("barrier.cluster.arrive.relaxed.aligned;" ::: "memory");
    const uint2* sp = &p.s->stat[256 * r + 2 * (tid & 127)];
    uint4 sw;
    if (svcwarp) sw = ld_rlx4(sp);
    if (svcwarp || extra) {
        const uint32_t tag = ~epoch & 1;
        const int tile = extra ? 15 : cl, wj = extra ? warp + 2 * cl - 15 : warp & 3;
        float d2[4] = {0, 0, 0, 0}, d3[4] = {0, 0, 0, 0}, d4[4] = {0, 0, 0, 0}, d5[4] = {0, 0, 0, 0}, d6[4] = {0, 0, 0, 0}, d7[4] = {0, 0, 0, 0};
        const uint32_t xa = S + (extra ? SM_CH + 4 * CH - 128 : SM_TOTAL - 18432) + (8 * (mi >> 1) + 2 * wj + (mi & 1)) * 1152 + 16 * j;
        const uint32_t wa = S + SM_B + 4104 - 2056 * (g & 1) + 64 * (g >> 2) + 16 * t + 2 * (g & 2), ones = 0x3F803F80u;
        uint32_t wv[18];
        mbar_wait_short(S + B_WR * 8);
#pragma unroll
        for (int i = 0; i < 18; i++) wv[i] = lds32(wa + 128 * (i >> 1) + 8 * (i & 1));
#pragma unroll
        for (int i = 0; i < 9; i++) mma_bf(d5, ones, ones, ones, ones, wv[2 * i], wv[2 * i + 1]);
        float wsum = d5[1] + __shfl_xor_sync(~0u, d5[1], 1);
        wsum += __shfl_xor_sync(~0u, wsum, 2);
        mbar_wait_short((S + B_ROWS * 8) | (__float_as_uint(wsum) & p.tn.zero));
        __syncwarp();
#pragma unroll
        for (int i = 0; i < 9; i++) {
            const uint4 x = lds128(xa + 128 * i);
            mma_bf8(d3, x.x, x.y, x.x);
            mma_bf8(d4, x.x, x.y, x.y);
            mma_bf8(d6, x.z, x.w, x.z);
            mma_bf8(d7, x.z, x.w, x.w);
            mma_bf(d2, x.x, x.y, x.z, x.w, wv[2 * i], wv[2 * i + 1]);
        }
        float sx = d2[0] + d2[2], sq = (g & 1) ? (d3[1] + d4[3]) + (d6[1] + d7[3]) : (d3[0] + d4[2]) + (d6[0] + d7[2]);
        float dot = (t & 1) ? d2[3] : d2[1];
        sx += __shfl_xor_sync(~0u, sx, 4);
        sq = __shfl_sync(~0u, sq, 9 * mi) + __shfl_sync(~0u, sq, 9 * mi + 4);
        dot += __shfl_xor_sync(~0u, dot, 1);
        dot += __shfl_xor_sync(~0u, dot, 6);
        const float mean = sx * (1.f / 576.f), var = fmaxf(sq * (1.f / 576.f) - mean * mean, 0.f);
        const float mu = bf_round(mean), sd = bf_round(sqrt_ap(bf_round(bf_round(var) + 1e-5f)));
        const uint32_t idx = 2047 - (128 * (tile & 14) + 32 * r + 16 * (tile & 1) + 8 * (mi >> 1) + 2 * wj + (mi & 1));
        const uint32_t rb = pack_bf(0.f, (dot - mu * wsum) * rcpf(sd));
        uint2 v = make_uint2((__float_as_uint(mu) >> 16) | __float_as_uint(sd), (((rb ^ (((int)rb >> 31) | 0x80000000u)) >> 1) & 0x7FFF8000u) | (tag << 31) | idx);
        uint2* const dst = &p.s->stat[256 * r + 16 * tile];
        if (extra) {
            if (j == 0) st_rlx2(dst + 4 * wj + mi, v.x, v.y);
            bar_arrive(13, 224);
        } else {
        const uint32_t ga = S + SM_B + 3200 + 32 * wj;
        if (j == 0) sts64(ga + 8 * mi, v.x, v.y);
        bar_sync(15, 128);
        if (tid < 272) {
            v = lds64(ga + 8 * lane);
            st_rlx2(dst + lane, v.x, v.y);
        }
        if (lane == 0) mbar_arrive(S + (B_EMPTY + 10) * 8);
        }
    }

    if (k < nch) {
        const uint32_t cb = S + SM_CH + k * CH, scr = cb + BOX + 3072 * half, oth = cb + BOX + 3072 - 3072 * half;
        float d[5][4], k0;
        kp.dsk = __shfl_sync(~0u, kp.ldt, 1);
        kp.ldt = __shfl_sync(~0u, kp.ldt, 0);
        const uint32_t eb = kgen(kp, scr, oth, 1 + k, lane, d, k0, k > 7 - nch ? 3 - 2 * half : 2, ((p.tn.stag >> warp) & 1) ? S + (B_EMPTY + 10) * 8 : 0);
        __syncwarp();
#pragma unroll
        for (int i = 0; i < 5; i++)
            if (half == (i < 3)) sts128f(kp.sa + i * 512, d[i][0], d[i][1], d[i][2], d[i][3]);
        bar_sync(1 + k, 64);
        auto both = [&](int i, uint32_t& w0, uint32_t& w1) {
            const uint4 v = lds128(oth + i * 512 + lane * 16);
            w0 = pack_h(d[i][0] + __uint_as_float(v.x), d[i][1] + __uint_as_float(v.y));
            w1 = pack_h(d[i][2] + __uint_as_float(v.z), d[i][3] + __uint_as_float(v.w));
        };
        if (half) {
            uint32_t a0, a1, b0, b1;
            both(3, a0, a1); both(4, b0, b1);
            const uint32_t o = cb + pre[6], q = cb + FT + 376 + 64 * t + 4 * g;
            sts32(o, a0); sts32(o + 64, a1); sts32(q, b0); sts32(q + 32, b1);
            bar_sync(1 + k, 64);
        } else {
            {
                uint32_t a[2], b[2], c[2], last = pack_h(k0, k0);
                both(0, a[0], a[1]); both(1, b[0], b[1]); both(2, c[0], c[1]);
                const uint32_t o = cb + TAB + 32 + 16 * lane;
                sts16(cb + TAB + 28, last);
#pragma unroll
                for (int h = 0; h < 4; h++) {
                    const uint32_t e = h < 2 ? b[h] : c[h - 2], pv = __shfl_sync(~0u, lane == 31 ? last : e, lane - 1);
                    if (h < 2) sts128(o + 512 * h, prmt(a[h], pv, 0x7610), prmt(a[h], 0, 0x1032), prmt(e, a[h], 0x7610), prmt(e, 0, 0x1032));
                    else sts128(o + 512 * h, prmt(pv, 0, 0x3232), prmt(e, pv, 0x7610), prmt(e, 0, 0x1032), prmt(e, 0, 0x3232));
                    last = e;
                }
                if (lane == 31) sts128(o + 1552, prmt(last, 0, 0x3232), prmt(last, 0, 0x3232), last & 0xFFFF0000u, 0u);
                __syncwarp();
            }
            near_lags(S, k, 64 * r + 16 * ((2 * k + (cbase >> 2) + (r >> 2)) & 3), eb, pre);
            return;
        }
    }

    const int ph0 = pair & ~r, f0 = pair ? 32 * (bid & ~1) + 768 : 64 * bid;
    if (k == 7) {
        spin_until(t0, p.tn.t_pf);
#pragma unroll 1
        for (int e = tid - 224; e < 576; e += 64) {
            asm volatile("prefetch.global.L2 [%0];" ::"l"(p.wg + e * F_ + f0) : "memory");
            __nanosleep(100);
        }
        return;
    }
    if (warp == 12) {
        if (elect()) {
            asm volatile("prefetch.tensormap [%0];" ::"l"(&m.u) : "memory");
            spin_until(t0, p.tn.t_tile);
            mbar_expect(S + B_RAW * 8, 256 * PITCH);
            asm volatile("cp.async.bulk.tensor.5d.shared::cluster.global.mbarrier::complete_tx::bytes [%0], [%1, {%3, 0, %4, 0, 0}], [%2];"
                         ::"r"(S + SM_RAW), "l"(&m.u), "r"(S + B_RAW * 8), "r"(cbase), "r"(4 * r) : "memory");
            uint32_t bar = S + B_FULL * 8, dst = S + SM_W, em = 0x1249400u, wm = ~(1u << p.tn.s0) << (p.tn.win0 + 2 - 2 * pair), wb = bar;
#pragma unroll 1
            for (int ph = ph0; ph < 3; ph += 1 + (pair & r)) {
                const int c0 = ph < 2 ? f0 : cbase, c1 = ph < 2 ? 0 : 576 * r;
#pragma unroll 1
                for (int n = 0; n < 576; n += 64) {
                    if (wm & 1) { mbar_wait(wb, 0); wb += 8; }
                    if (em & 1) mbar_wait(bar + 8 * (B_EMPTY - B_FULL), 0);
                    mbar_expect(bar, ph < 2 ? 8192 : 128 * 40);
                    tma2d(dst, m.w + ph, c0, c1 + n, bar);
                    bar += 8; em >>= 1; wm >>= 1;
                    dst = dst == S + SM_W + (NRING - 1) * 8192 ? S + SM_W : dst + 8192;
                }
            }
        }
        return;
    }

    if (warp == 15) {
        asm volatile("barrier.cluster.wait.aligned;" ::: "memory");
        sts32(S + SM_SKIP + 4 * j, 0u);
        const uint32_t ob = mapa(S, g);
        bar_sync(13, two ? 224 : 160);
        const uint4 ka = lds128(S + SM_B + 256 + 16 * lane), kb = lds128(S + SM_B + 768 + 16 * lane);
        uint32_t k0 = ka.x, k1 = ka.y, mine = 0, c = 0;
        int rank = lane;
#pragma unroll 1
        for (int pass = 0;; pass++) {
#pragma unroll 1
            for (int n = 0; n < (pass < 2 ? 4 : 8); n++) {
                const uint32_t a = __viaddmin_u32(k0, c, __viaddmin_u32(k1, c, ka.z + c)), b = __viaddmin_u32(ka.w, c, __viaddmin_u32(kb.x, c, kb.y + c));
                c += ~__reduce_min_sync(~0u, __vimin3_u32(a, b, __viaddmin_u32(kb.z, c, kb.w + c)));
                if ((pass < 2 ? t : j) == n) mine = c;
            }
            if (pass == 2) break;
            asm volatile("st.async.shared::cluster.mbarrier::complete_tx::bytes.b32 [%0], %1, [%2];" ::"r"(ob + SM_CAND + 128 * pass + 16 * r + 4 * t), "r"(~mine), "r"(ob + (B_TOP + pass) * 8) : "memory");
            mbar_wait_short(S + (B_TOP + pass) * 8);
            const uint32_t v = lds32(S + SM_CAND + 4 * lane);
            if (pass) {
                k0 = v; k1 = lds32(S + SM_CAND + 128 + 4 * lane); c = 0;
            } else {
                uint32_t cn[4] = {0, 0, 0, 0};
#pragma unroll 4
                for (int e = 0; e < 128; e += 16) {
                    const uint4 o = lds128(S + SM_CAND + e);
                    cn[0] += (o.x - v) >> 31; cn[1] += (o.y - v) >> 31; cn[2] += (o.z - v) >> 31; cn[3] += (o.w - v) >> 31;
                }
                const int rk = (cn[0] + cn[1]) + (cn[2] + cn[3]);
                if (!__any_sync(~0u, t == 3 && rk < 8)) { rank = rk; mine = ~v; break; }
            }
        }
        const uint32_t row = ~mine & 2047, ix = (row & 0xE0) * 8 + ((row >> 3) & 0xE0) + (row & 0x11) + ((row >> 2) & 2) + (row & 6) * 2;
        const uint32_t mr = __reduce_or_sync(~0u, rank == r ? row : 0u);
        if (elect()) {
            bulk_mc(S + SM_B + BP * r, p.u + mr * D_, 1152, S + B_XS * 8);
        }
        const bool own = rank < 8 && (ix >> 8) == r;
        const uint32_t m2 = 2 * mine, rb = (m2 ^ ((~(int)m2 >> 31) | 0x80000000u)) & 0xFFFF0000u;
        if (rank < 8) sts64(S + SM_SEL + 8 * rank, ix | rb, row | ((row & 0x700) + 32 * (row & 6) + 2 * (row & 24) + 8 * (row & 1)) << 16);
        if (own) asm volatile("red.shared.or.b32 [%0], %1;" ::"r"(S + SM_SKIP + 4 * (ix & 7)), "r"(1u << ((ix >> 3) & 31)) : "memory");
        const int no = __popc(__ballot_sync(~0u, own));
        if (lane < 2) mbar_expect(S + (B_FIN + lane) * 8, lane ? 0 : no * (nch - 2) * 256);
    }

    if (svcwarp) {
        const uint32_t tag = ~epoch & 1;
        const int fw = warp & 3, i = tid & 127;
        uint32_t xbar = mapa(S + B_X * 8, g), xd = keep(xbar - B_X * 8 + SM_CH + xslot(8 + 2 * r + (t >> 1), t & 1) + 256 * (fw & 2));
        uint32_t ra = keep(S + SM_RAW + (64 * mi + j + 4 * (fw & 2)) * PITCH), sa = keep(S + SM_ST + 16 * t + 128 * (fw & 2));
        const uint32_t ta = keep(S + SM_ST + 16 * (i & 0x71) + 32 * (i & 6) + 4 * (i & 8));
        asm volatile("barrier.cluster.wait.aligned;" ::: "memory");
        mbar_wait_short(S + B_RAW * 8);
#pragma unroll 1
        for (int it = 0; it < SPIN_LIMIT && (int)((sw.y ^ -tag) | (sw.w ^ -tag)) < 0; it++) sw = ld_rlx4(sp);
        sts64(S + SM_B + 256 + 8 * i, ~sw.y, ~sw.w);
        {
            const float r0 = 0.5f * rcpf(bf_hi(sw.x)), r1 = 0.5f * rcpf(bf_hi(sw.z));
            sts128f(ta, r0, -bf_lo(sw.x) * r0, r1, -bf_lo(sw.z) * r1);
        }
        bar_sync(13, two ? 224 : 160);
        if (i == 0) st_rlx(&p.s->ep[bid * 8], epoch + 1);
        {
#pragma unroll 1
            for (int u = fw; u < fw + 4; u++) {
                uint4 s[4];
#pragma unroll
                for (int e = 0; e < 4; e++) s[e] = lds128(sa + 64 * e);
#pragma unroll 1
                for (int n = u & 1; n < nch; n += 2) {
                    uint32_t a[4];
                    ldm4t(ra + 16 * n, a);
#pragma unroll
                    for (int e = 0; e < 4; e++)
                        a[e] = pack_h(fmaf(bf_lo(a[e]), __uint_as_float(s[e].x), __uint_as_float(s[e].y)), fmaf(bf_hi(a[e]), __uint_as_float(s[e].z), __uint_as_float(s[e].w)));
                    st_async4(xd + n * CH, a[0], a[1], a[2], a[3], xbar);
                }
                xd += 1024; ra += 16 * PITCH; sa += 512; xbar |= 8;
            }
        }
        const int mt = (fw + 3) & 3;
        const uint32_t bw = keep(S + SM_B + BP * j + 16 * (i >> 3)), ba = keep(S + SM_B + BP * j + 16 * mi);
        const uint32_t aa = keep(S + SM_W + (8 * (mi >> 1) + j) * 128 + (((2 * mt + (mi & 1)) ^ j) << 4));
        uint32_t bar = S + B_FULL * 8, of = 0;
        mbar_wait_short(S + B_SEL * 8);
        const uint2 sv = lds64(S + SM_SEL + 8 * j);
        float r0, r1;
        {
            float sa, sb;
            asm volatile("ld.shared::cluster.v2.f32 {%0, %1}, [%2];" : "=f"(sa), "=f"(sb) : "r"(mapa(S + SM_ST + (sv.y >> 16), (sv.x >> 8) & 7)) : "memory");
            const float m1 = -sb * rcpf(sa);
            mbar_wait_short(S + B_XS * 8);
            uint4 v[5];
#pragma unroll
            for (int n = 0; n < 5; n++) v[n] = lds128(bw + 256 * n);
            const uint32_t mu = pack_bf(m1, m1);
#pragma unroll
            for (int n = 0; n < 5; n++)
                if (n < 4 || fw < 2) sts128(bw + 256 * n, bsub(v[n].x, mu), bsub(v[n].y, mu), bsub(v[n].z, mu), bsub(v[n].w, mu));
            const float ri = sa + sa;
            r0 = __shfl_sync(~0u, ri, 2 * t); r1 = __shfl_sync(~0u, ri, 2 * t + 1);
        }
        const uint32_t tx = clk32();
        float d[4][4];
#pragma unroll 1
        for (int ph = ph0;; ph++) {
            if (ph == 2) {
                bar_sync(15, 128);
                spin_until(tx, p.tn.da);
                r0 = r1 = 1.f;
                const uint32_t* const hp = p.s->h + 2304 * r + 4 * i;
                uint4 v[5];
                const uint32_t tm = -tag;
#pragma unroll 1
                for (int it = 0; it < SPIN_LIMIT; it++) {
                    uint32_t bad = 0;
#pragma unroll
                    for (int n = 0; n < 5; n++) v[n] = ld_rlx4(hp + (n < 4 ? 512 * n : 1792));
#pragma unroll
                    for (int n = 0; n < 5; n++) bad |= lop_ne(v[n].x, v[n].z, tm);
                    if (!(bad & 1)) break;
                }
#pragma unroll
                for (int n = 0; n < 5; n++) sts128(bw + (n < 4 ? 256 * n : 896), v[n].x, v[n].y, v[n].z, v[n].w);
            }
            if (ph == ph0 || ph == 2) bar_sync(15, 128);
            if (ph == 2 && mt >= nch - 2) break;
#pragma unroll
            for (int e = 0; e < 4; e++) d[0][e] = d[1][e] = d[2][e] = d[3][e] = 0.f;
#pragma unroll 1
            for (int n = 0; n < 1152; n += 384) {
                uint32_t a[12][4], b[24];
                mbar_wait(bar + 8 * min(lane, 2), 0);
                __syncwarp();
#pragma unroll
                for (int e = 0; e < 12; e++) {
                    if (!(e & 1)) ldm4(ba + n + 32 * e, b[2 * e], b[2 * e + 1], b[2 * e + 2], b[2 * e + 3]);
                    ldm4t(aa + of + 2048 * e, a[e]);
                }

#pragma unroll
                for (int e = 0; e < 12; e++) mma_bf(d[e & 3], a[e][0], a[e][1], a[e][2], a[e][3], b[2 * e], b[2 * e + 1]);
                if (lane == 0) mbar_arrive(min(bar + (B_EMPTY + NRING - B_FULL) * 8, S + 63 * 8));
                bar += 24;
                of = of == 8192 * (NRING - 3) ? 0 : of + 24576;
            }
#pragma unroll
            for (int e = 0; e < 4; e++) d[0][e] = (d[0][e] + d[1][e]) + (d[2][e] + d[3][e]);
            uint32_t k0 = pack_bf(d[0][0] * r0, d[0][1] * r1), k1 = pack_bf(d[0][2] * r0, d[0][3] * r1);
            const uint32_t ea = SM_FIN + 6144 + 8 * i, eb = B_UP * 8;
            if (ph == 0) {
                const uint32_t ob = mapa(S, r & ~pair);
                st_async2(ob + ea, k0, k1, ob + eb);
                ph += pair;
                continue;
            }
            if (ph == 1) {
                k0 = pack_bf(silu_half(0.5f * bf_lo(k0)), silu_half(0.5f * bf_hi(k0))); k1 = pack_bf(silu_half(0.5f * bf_lo(k1)), silu_half(0.5f * bf_hi(k1)));
                mbar_wait_short((S + eb) | (k0 & k1 & p.tn.zero));
                const uint2 v = lds64(S + ea);
                k0 = bmul(k0, v.x); k1 = bmul(k1, v.y);
                __syncwarp();
            }
            k0 = movm(k0); k1 = movm(k1);
            if (ph == 2) {
                const uint32_t ob = mapa(S, (__shfl_sync(~0u, sv.x, g) >> 8) & 7);
                st_async2(ob + SM_FIN + 768 * g + 96 * r + 32 * mt + 8 * t, k0, k1, ob + B_FIN * 8);
                break;
            }
            const uint32_t o = __shfl_xor_sync(~0u, (lane & 1) ? k0 : k1, 1);
            st_rlx2(p.s->h + 4 * f0 + 64 * mt + 31 * (lane & 1) + lane, (((lane & 1) ? o : k0) & ~1u) | tag, (lane & 1) ? k1 : o);
        }
        const int l = min(lane, 4 * nch - 1);
        int n = fw;
#pragma unroll 1
        for (uint32_t own = __ballot_sync(~0u, ((sv.x >> 8) & 7) == r) & 255; own; own &= own - 1) {
            if (n-- & 3) continue;
            const int tk = __ffs(own) - 1;
            const uint2 e = lds64(S + SM_SEL + 8 * tk), st = lds64(S + SM_ST + (e.y >> 16));
            const uint32_t ix = e.x, x = lds32(S + SM_RAW + (16 * (ix & 12) + ((ix >> 2) & 60) + (ix & 3)) * PITCH + 4 * l);
            const uint32_t yb = S + SM_CH + YIN + (l >> 2) * CH + 16 * (ix & 0xE0) + 128 * (l & 3) + 16 * (((ix >> 3) ^ ((l >> 1) + (cbase >> 2))) & 3) + 2 * (ix & 7);
            const float sg = 0.5f * sigm(bf_hi(ix));
            const uint32_t hx = pack_bf(fmaf(bf_lo(x), __uint_as_float(st.x), __uint_as_float(st.y)), fmaf(bf_hi(x), __uint_as_float(st.x), __uint_as_float(st.y))), sg2 = pack_bf(sg, sg);
            mbar_wait((S + B_FIN * 8) | (hx & sg2 & p.tn.zero), 0);
            float a[2] = {0.f, 0.f}, b[2] = {0.f, 0.f};
#pragma unroll
            for (int q = 0; q < 8; q++) {
                const uint32_t v = lds32(S + SM_FIN + 768 * tk + 96 * q + 4 * (l & 24) + 8 * (l & 3) + (l & 4));
                a[q & 1] += bf_lo(v); b[q & 1] += bf_hi(v);
            }
            const uint32_t hv = badd(hx, bmul(pack_bf(a[0] + a[1], b[0] + b[1]), sg2)), gt = pack_bf(silu_half(bf_lo(hv)), silu_half(bf_hi(hv)));
            mbar_wait((S + B_Y * 8 + ((ix >> 2) & 56)) | (gt & p.tn.zero), 0);
            *(uint32_t*)(p.out + (e.y & 2047) * D_ + cbase + 2 * l) = bfma(lds16(yb) | (lds16(yb + 64) << 16), gt, x);
        }
        return;
    }

    mbar_wait(S + B_X * 8, 0);
    if (k < nch) {
        const uint32_t cb = S + SM_CH + k * CH, bx = cb + BOX + 16;
        float u[4][4], v[4][4], w[4][4];
#pragma unroll
        for (int i = 0; i < 4; i++) v[i][0] = v[i][1] = v[i][2] = v[i][3] = w[i][0] = w[i][1] = w[i][2] = w[i][3] = 0.f;
        uint2 T4[10];
        const uint32_t ta = cb + FT + 4 * (g - t);
#pragma unroll
        for (int e = 0; e < 10; e++) T4[e] = lds64(ta + 24 + 32 * e + 4 * (g - t));
        const uint32_t tb = prmt(lds32(cb + FT + 308), 0, pre[7]);
        const uint32_t a4 = cb + pre[0], a8 = cb + pre[1], at = cb + pre[2], hb = cb + pre[3], o = bx + 16 * lane;
        uint32_t xi = cb + pre[4], xp = cb + pre[5], hs = cb + XX;
#pragma unroll 1
        for (int n = 9; n > 0; n -= 4) {
            {
                const uint4 hv = lds128(hs);
                hs = hb + 496;
                const uint2 v0 = lds64(xp + 8);
                const uint4 v1 = lds128(xp ^ 32), v2 = lds128(xi), v3 = lds128(xi ^ 32);
                xi += 1024; xp += 1024;
                __syncwarp();
                if (lane < 3) sts128(hb - 16, hv.x, hv.y, hv.z, hv.w);
                const uint32_t P[13] = {v0.x, v0.y, v1.x, v1.y, v1.z, v1.w, v2.x, v2.y, v2.z, v2.w, v3.x, v3.y, v3.z};
                uint32_t Q[12], s2[12], s4[10], b3[11], b5[9];
#pragma unroll
                for (int e = 0; e < 12; e++) { Q[e] = prmt(P[e], P[e + 1], 0x5432); s2[e] = hadd(P[e], Q[e]); }
#pragma unroll
                for (int e = 0; e < 11; e++) b3[e] = hadd(Q[e], s2[e + 1]);
#pragma unroll
                for (int e = 0; e < 10; e++) s4[e] = hadd(s2[e], s2[e + 1]);
#pragma unroll
                for (int e = 0; e < 9; e++) b5[e] = hadd(s4[e + 1], P[e + 3]);
                sts128(o, b3[3], b3[4], b3[5], b3[6]);
                sts128(o + 1152, b3[7], b3[8], b3[9], b3[10]);
                sts128(o + 576, b5[0], b5[1], b5[2], b5[3]);
                sts128(o + 1728, b5[4], b5[5], b5[6], b5[7]);
                if (n > 4) {
                    sts128(o + 4608, s2[4], s2[5], s2[6], s2[7]);
                    sts128(o + 5184, s2[8], s2[9], s2[10], s2[11]);
                    sts128(o + 2304, hadd(b3[0], s4[2]), hadd(b3[1], s4[3]), hadd(b3[2], s4[4]), hadd(b3[3], s4[5]));
                    sts128(o + 3456, hadd(b3[4], s4[6]), hadd(b3[5], s4[7]), hadd(b3[6], s4[8]), hadd(b3[7], s4[9]));
                    sts128(o + 4032, hadd(s4[0], b5[1]), hadd(s4[1], b5[2]), hadd(s4[2], b5[3]), hadd(s4[3], b5[4]));
                    sts128(o + 2896, hadd(s4[4], b5[5]), hadd(s4[5], b5[6]), hadd(s4[6], b5[7]), hadd(s4[7], b5[8]));
                }
                __syncwarp();
            }
            uint32_t A[8][4];
#pragma unroll
            for (int e = 0; e < 8; e++) ldm4t(a4 + 64 * e, A[e]);
#pragma unroll
            for (int e = 0; e < 8; e++)
#pragma unroll
                for (int b = 3; b >= e / 2; b--) {
                    const uint2 T = T4[2 * (b - e / 2) + 1 - (e & 1)];
                    if (e == 0) mma_hc(u[b], v[b], A[e][0], A[e][1], A[e][2], A[e][3], T.x, T.y);
                    else mma_h(u[b], A[e][0], A[e][1], A[e][2], A[e][3], T.x, T.y);
                }
            if (n == 9) mbar_wait_short(S + (B_X + 1) * 8);
#pragma unroll
            for (int e = 0; e < 2; e++)
                stm4t(cb + TAB + 2304 - 256 * n + 512 * e + 16 * lane, pack_h(u[2 * e][0], u[2 * e][1]), pack_h(u[2 * e][2], u[2 * e][3]),
                      pack_h(u[2 * e + 1][0], u[2 * e + 1][1]), pack_h(u[2 * e + 1][2], u[2 * e + 1][3]));
            __syncwarp();
            sts32v(S + SM_PROG + 4 * k, n > 1 ? n : p.tn.tail);
            if (n == 1) break;
            uint32_t C[4][4], E[2][4], T8[16];
#pragma unroll
            for (int e = 0; e < 4; e++) ldm4t(a8 + 128 * e, C[e]);
#pragma unroll
            for (int e = 0; e < 2; e++) ldm4t(at + 256 * e, E[e]);
#pragma unroll
            for (int e = 0; e < 8; e++) T8[e] = lds32(ta + 376 + 32 * (e >> 1) - 16 * (e & 1));
#pragma unroll
            for (int e = 7; e >= 0; e--)
#pragma unroll
                for (int b = 0; b <= e / 2; b++) {
                    const uint2 T = T4[2 * (4 + b - e / 2) + 1 - (e & 1)];
                    if (e == 7) mma_hc(v[b], w[b], A[e][0], A[e][1], A[e][2], A[e][3], T.x, T.y);
                    else mma_h(v[b], A[e][0], A[e][1], A[e][2], A[e][3], T.x, T.y);
                }
#pragma unroll
            for (int e = 3; e >= 0; e--) {
                mma_h8(v[e], E[e >> 1][2 * (e & 1)], E[e >> 1][2 * (e & 1) + 1], tb);
#pragma unroll
                for (int b = 3; b >= e; b--) mma_h(v[b], C[e][0], C[e][1], C[e][2], C[e][3], T8[2 * (b - e)], T8[2 * (b - e) + 1]);
            }
            if (n == 9) {
#pragma unroll
                for (int e = 8; e < 16; e++) T8[e] = lds32(ta + 376 + 32 * (e >> 1) - 16 * (e & 1));
#pragma unroll
                for (int e = 3; e >= 0; e--)
#pragma unroll
                    for (int b = 0; b < 4; b++) mma_h(w[b], C[e][0], C[e][1], C[e][2], C[e][3], T8[2 * (4 + b - e)], T8[2 * (4 + b - e) + 1]);
            }
        }
    }

  {
    int lane;
    asm volatile("mov.u32 %0, %%laneid;" : "=r"(lane));
    const int g = lane >> 2, t = lane & 3, mi = lane >> 3, j = lane & 7, sh = (cbase >> 3) & 1;
    mbar_wait_short(S + B_SEL * 8);
    if (k < nch - 2 || k == 5) {
        const int one = k == 2, st = k == 5 ? 1 : 2, kk = one ? 4 - 4 * sh : sh + 2 * st - 2;
        const int q0 = k == 1, qx = q0 + (one & (t >> 1)), cx = 16 * kk + 8 * (one ? t & 1 : t);
        uint32_t xa = S + SM_RAW + (16 * (g & 4) + (g & 3) + 8 * qx) * PITCH + cx, sa = S + SM_ST + 16 * (g & 4) + 8 * (g & 3) + 256 * qx, bar = S + (B_Y + qx) * 8;
        uint32_t ya = S + SM_CH + YIN + kk * CH + (j >> 2) * (one ? 512 : CH) + 128 * (j & 2) + 128 * (mi & 1) + 64 * (j & 1) + 512 * q0 +
                      16 * ((mi >> 1) ^ (one ? 2 * sh + ((j >> 1) & 1) : j >> 1));
        uint32_t sk = lds32(S + SM_SKIP + 4 * g) >> (4 * qx);
        char* o = (char*)p.out + ((256 * qx + 32 * r + 4 * (g & 2) + 2 * (g >> 2) + (g & 1)) * D_ + cbase) * 2 + cx;
#pragma unroll 1
        for (int n = 0; n < 8; n += st) {
            uint2 x[4];
            uint32_t gt[8], y[2][4];
#pragma unroll
            for (int e = 0; e < 4; e++) {
                x[e] = lds64(xa + (128 * (e & 1) + 2 * (e & 2)) * PITCH);
                const uint2 s = lds64(sa + 128 * (e & 1) + 16 * (e & 2));
                const float a = __uint_as_float(s.x), b = __uint_as_float(s.y);
                gt[2 * e] = pack_bf(silu_half(fmaf(bf_lo(x[e].x), a, b)), silu_half(fmaf(bf_hi(x[e].x), a, b)));
                gt[2 * e + 1] = pack_bf(silu_half(fmaf(bf_lo(x[e].y), a, b)), silu_half(fmaf(bf_hi(x[e].y), a, b)));
            }
            mbar_wait(bar | (((gt[0] | gt[1] | gt[2]) | (gt[3] | gt[4] | gt[5]) | (gt[6] | gt[7])) & p.tn.zero), 0);
            __syncwarp();
            ldm4t(ya, y[0]);
            ldm4t(ya ^ 32, y[1]);
#pragma unroll
            for (int e = 0; e < 4; e++)
                asm volatile("{.reg .pred p; setp.eq.u32 p, %3, 0;\n@p st.global.v2.u32 [%0], {%1, %2};}" ::"l"(o + (8 * (e & 1) + 16 * (e & 2)) * D_),
                             "r"(bfma(y[e >> 1][2 * (e & 1)], gt[2 * e], x[e].x)), "r"(bfma(y[e >> 1][2 * (e & 1) + 1], gt[2 * e + 1], x[e].y)), "r"(sk & (1 << e)) : "memory");
            xa += 8 * PITCH * st; sa += 256 * st; ya += 512 * st; bar += 8 * st; sk >>= 4 * st; o += 512 * D_ * st;
        }
    }
  }
}

typedef CUresult (*EncodeFn)(CUtensorMap*, CUtensorMapDataType, cuuint32_t, void*, const cuuint64_t*, const cuuint64_t*, const cuuint32_t*,
                             const cuuint32_t*, CUtensorMapInterleave, CUtensorMapSwizzle, CUtensorMapL2promotion, CUtensorMapFloatOOBfill);

static void make2d(EncodeFn enc, CUtensorMap* m, const void* base, uint64_t cols, uint64_t rows, uint32_t bc = 64) {
    cuuint64_t gd[2] = {cols, rows};
    cuuint64_t gs[1] = {cols * 2};
    cuuint32_t bd[2] = {bc, 64}, es[2] = {1, 1};
    enc(m, CU_TENSOR_MAP_DATA_TYPE_BFLOAT16, 2, const_cast<void*>(base), gd, gs, bd, es, CU_TENSOR_MAP_INTERLEAVE_NONE, CU_TENSOR_MAP_SWIZZLE_128B,
        CU_TENSOR_MAP_L2_PROMOTION_L2_128B, CU_TENSOR_MAP_FLOAT_OOB_FILL_NONE);
}

static void make5d(EncodeFn enc, CUtensorMap* m, const void* base, uint32_t cols, CUtensorMapSwizzle sw) {
    cuuint64_t gd[5] = {D_, 2, 32, 8, 4};
    cuuint64_t gs[4] = {D_ * 2, D_ * 16, D_ * 512, D_ * 4};
    cuuint32_t bd[5] = {cols, 2, 4, 8, 4}, es[5] = {1, 1, 1, 1, 1};
    enc(m, CU_TENSOR_MAP_DATA_TYPE_BFLOAT16, 5, const_cast<void*>(base), gd, gs, bd, es, CU_TENSOR_MAP_INTERLEAVE_NONE, sw,
        CU_TENSOR_MAP_L2_PROMOTION_NONE, CU_TENSOR_MAP_FLOAT_OOB_FILL_NONE);
}

static Tune g_tune = {2200, 102, 2, 2, 4, 800, 5200, 6500, 0};

static int max_clusters() {
    cudaFuncSetAttribute(fused_kernel, cudaFuncAttributeMaxDynamicSharedMemorySize, SM_TOTAL);
    cudaLaunchConfig_t cfg = {};
    cudaLaunchAttribute at[1];
    at[0].id = cudaLaunchAttributeClusterDimension;
    at[0].val.clusterDim.x = 8; at[0].val.clusterDim.y = 1; at[0].val.clusterDim.z = 1;
    cfg.gridDim = dim3(NCTA); cfg.blockDim = dim3(NTHREADS); cfg.dynamicSmemBytes = SM_TOTAL; cfg.attrs = at; cfg.numAttrs = 1;
    int n = 0;
    if (cudaOccupancyMaxActiveClusters(&n, fused_kernel, &cfg) != cudaSuccess) { cudaGetLastError(); n = 0; }
    return n;
}

static bool launch(void* const* d_in, void* d_out) {
    static EncodeFn enc = nullptr;
    static Scratch* gs = nullptr;
    if (!enc) {
        void* fn = nullptr;
        cudaDriverEntryPointQueryResult qr;
        cudaGetDriverEntryPoint("cuTensorMapEncodeTiled", &fn, cudaEnableDefault, &qr);
        enc = (EncodeFn)fn;
        cudaFuncSetAttribute(fused_kernel, cudaFuncAttributeMaxDynamicSharedMemorySize, SM_TOTAL);
        cudaGetSymbolAddress((void**)&gs, g_s);
    }
    Hot p;
    Maps m;
    auto in = [&](int i) { return (const __nv_bfloat16*)d_in[i]; };
    bool ok = true;
    auto off = [&](const void* q) {
        const long long d = (const char*)q - (const char*)d_in[0];
        ok = ok && d / 256 * 256 == d && (int)(d / 256) == d / 256;
        return (int)(d / 256);
    };
    p.u = in(0); p.are = off(in(1)); p.aim = off(in(2)); p.bre = off(in(3)); p.bim = off(in(4)); p.cre = off(in(5)); p.cim = off(in(6));
    p.logdt = off(in(7)); p.dskip = off(in(8)); p.wr = off(in(10)); p.ep = off(gs->ep);
    if (!ok) return false;
    p.out = (__nv_bfloat16*)d_out;
    p.wg = in(11);
    p.tn = g_tune;
    p.s = gs;
    make2d(enc, &m.w[0], in(12), F_, D_);
    make2d(enc, &m.w[1], in(11), F_, D_);
    make2d(enc, &m.w[2], in(13), D_, F_, 40);
    make5d(enc, &m.u, in(0), 40, CU_TENSOR_MAP_SWIZZLE_NONE);
    fused_kernel<<<NCTA, NTHREADS, SM_TOTAL>>>(p, m);
    return true;
}

}

namespace v2 {

constexpr int L_ = 2048, D_ = 576, F_ = 4608;
constexpr int NDOWN = 72, NMAIN = 128, NCTA = 132, NTHREADS = 512;
constexpr int SPIN_LIMIT = 1 << 16;
constexpr uint32_t SLOT_FREE = 0x7FFFABCDu;

constexpr int SM_PART = 544;
constexpr int SM_RED = SM_PART;
constexpr int SM_STA = 2080;
constexpr int SM_ONES = 2176;
constexpr int SM_KINF = 2192;
constexpr int SM_RP = 2272;
constexpr int SM_XS = 2704;
constexpr int KR_STRIDE = 1296;
constexpr int SM_X0 = 12080, X0_STRIDE = 4512, X0_ODD = 2240;
constexpr int SM_KT = 30128, KT_STRIDE = 3584, KT_P4 = 2144, KT_P8 = 2896;
constexpr int SM_FAR = 44544, FAR_STRIDE = 11328;
constexpr int FB5 = 0, FB3 = 3328, FB9E = 6656, FB9O = 7824, FB7E = 8992, FB7O = 10160;
constexpr int SM_ROWS = SM_FAR, ROW_STRIDE = 1168;
constexpr int SM_STG = SM_FAR + 19968;
constexpr int KG_SCR = 3072;
constexpr int SM_EX = 89856;
constexpr int EX_KT = SM_EX + X0_STRIDE, EX_FAR = EX_KT + KT_STRIDE, EX_HAND = 109312;
constexpr int SM_W_DOWN = 90112, SM_W_BIG = 121856, STAGE = 6144;
constexpr int SM_W_LAST = 12288;
constexpr int SM_TOTAL = 232448;
constexpr int SM_EPOCH = 2528, SM_SKIP = 2536;
static_assert(SM_STG + 8 * KG_SCR <= SM_EX && SM_STG % 128 == 0 && EX_HAND % 128 == 0 && EX_FAR + FAR_STRIDE <= EX_HAND && EX_HAND + 12288 <= SM_W_BIG, "scratch");

enum { B_ROWS = 0, B_KG, B_X0, B_X1, B_BOX  , B_TAB, B_EM = 6, B_SP = 10, B_OUT = 14, B_H = 15, B_RED = 16, B_TAB1 = 17, B_XS = 18, B_GX = 19, B_YIN = 22, B_P1 = 26, B_FD, B_GU = 28, B_W = 34, B_COUNT = 58 };

struct Tune { short f_start, f_t3, w2, w2b, w3, t_xs, t_svc, t_marg, f_t2, w1, zero, pad; };

struct Scratch {
    uint32_t x[144 * 4096];
    uint32_t y[128 * 4608];
    uint32_t h[2][F_ * 4];
    uint32_t key[L_];
    uint32_t stat[L_];
    uint32_t sel[4][32];
    uint32_t cnt[17 * 32];
};
__device__ __align__(1024) Scratch g_s;

struct Hot {
    const __nv_bfloat16* u;
    Scratch* s;
    const __nv_bfloat16 *wr, *are, *aim, *bre, *bim, *cre, *cim, *logdt;
    Tune tn;
    const __nv_bfloat16 *dskip, *pwg, *pwu, *pwd;
    __nv_bfloat16* out;
};
struct Maps { CUtensorMap wg, wu, wd; };

__device__ __forceinline__ uint32_t smem_u32(const void* p) { return (uint32_t)__cvta_generic_to_shared(p); }
__device__ __forceinline__ void mbar_init(uint32_t b, int c) { asm volatile("mbarrier.init.shared::cta.b64 [%0], %1;" ::"r"(b), "r"(c) : "memory"); }
__device__ __forceinline__ void mbar_expect(uint32_t b, int bytes) { asm volatile("mbarrier.arrive.expect_tx.shared::cta.b64 _, [%0], %1;" ::"r"(b), "r"(bytes) : "memory"); }
__device__ __forceinline__ void mbar_arrive(uint32_t b) { asm volatile("mbarrier.arrive.shared::cta.b64 _, [%0];" ::"r"(b) : "memory"); }
__device__ __forceinline__ bool elect() { uint32_t d; asm volatile("{.reg .pred p; elect.sync _|p, 0xffffffff; selp.u32 %0,1,0,p;}" : "=r"(d)); return d; }
__device__ __forceinline__ bool mbar_test(uint32_t b, int par) {
    uint32_t d;
    asm volatile("{.reg .pred p; mbarrier.test_wait.parity.shared::cta.b64 p, [%1], %2; selp.u32 %0,1,0,p;}" : "=r"(d) : "r"(b), "r"(par) : "memory");
    return d;
}
#define WAIT_LOOP(ins) "{\n.reg .pred p;\n.reg .u32 n;\nmov.u32 n, 0;\nLW:\n" ins " p, [%0], %1;\n@p bra LD;\nadd.u32 n, n, 1;\nsetp.lt.u32 p, n, 16384;\n@p bra LW;\nLD:\n}"
__device__ __forceinline__ void mbar_wait(uint32_t b, int par) { asm volatile(WAIT_LOOP("mbarrier.try_wait.parity.shared::cta.b64")::"r"(b), "r"(par) : "memory"); }
__device__ __forceinline__ uint32_t mapa(uint32_t a, uint32_t rank) { uint32_t d; asm("mapa.shared::cluster.u32 %0, %1, %2;" : "=r"(d) : "r"(a), "r"(rank)); return d; }
__device__ __forceinline__ void bulk_g2s(uint32_t dst, const void* src, int bytes, uint32_t bar) {
    asm volatile("cp.async.bulk.shared::cluster.global.mbarrier::complete_tx::bytes [%0], [%1], %2, [%3];" ::"r"(dst), "l"(src), "r"(bytes), "r"(bar) : "memory");
}
__device__ __forceinline__ void tma2d(uint32_t dst, const CUtensorMap* m, int c0, int c1, uint32_t bar) {
    asm volatile("cp.async.bulk.tensor.2d.shared::cluster.global.mbarrier::complete_tx::bytes [%0], [%1, {%3, %4}], [%2];" ::"r"(dst), "l"(m), "r"(bar), "r"(c0), "r"(c1) : "memory");
}
__device__ __forceinline__ void pf_tmap(const CUtensorMap* m) { asm volatile("prefetch.tensormap [%0];" ::"l"(m) : "memory"); }
__device__ __forceinline__ void bar_sync(int id, int n) { asm volatile("bar.sync %0, %1;" ::"r"(id), "r"(n) : "memory"); }
__device__ __forceinline__ uint4 ld_rlx4(const void* p) { uint4 v; asm volatile("ld.relaxed.gpu.global.v4.u32 {%0,%1,%2,%3}, [%4];" : "=r"(v.x), "=r"(v.y), "=r"(v.z), "=r"(v.w) : "l"(p) : "memory"); return v; }
__device__ __forceinline__ uint32_t ld_rlx(const void* p) { uint32_t v; asm volatile("ld.relaxed.gpu.global.u32 %0, [%1];" : "=r"(v) : "l"(p) : "memory"); return v; }
__device__ __forceinline__ void st_rlx(void* p, uint32_t v) { asm volatile("st.relaxed.gpu.global.u32 [%0], %1;" ::"l"(p), "r"(v) : "memory"); }
__device__ __forceinline__ uint32_t lds32(uint32_t a) { uint32_t v; asm volatile("ld.shared.u32 %0, [%1];" : "=r"(v) : "r"(a) : "memory"); return v; }
__device__ __forceinline__ uint32_t lds32v(uint32_t a) { uint32_t v; asm volatile("ld.volatile.shared.u32 %0, [%1];" : "=r"(v) : "r"(a) : "memory"); return v; }
__device__ __forceinline__ uint4 lds128v(uint32_t a) { uint4 v; asm volatile("ld.volatile.shared.v4.u32 {%0,%1,%2,%3}, [%4];" : "=r"(v.x), "=r"(v.y), "=r"(v.z), "=r"(v.w) : "r"(a) : "memory"); return v; }
__device__ __forceinline__ uint32_t lds16(uint32_t a) { uint16_t v; asm volatile("ld.shared.u16 %0, [%1];" : "=h"(v) : "r"(a) : "memory"); return v; }
__device__ __forceinline__ uint2 lds64(uint32_t a) { uint2 v; asm volatile("ld.shared.v2.u32 {%0,%1}, [%2];" : "=r"(v.x), "=r"(v.y) : "r"(a) : "memory"); return v; }
__device__ __forceinline__ uint4 lds128(uint32_t a) { uint4 v; asm volatile("ld.shared.v4.u32 {%0,%1,%2,%3}, [%4];" : "=r"(v.x), "=r"(v.y), "=r"(v.z), "=r"(v.w) : "r"(a) : "memory"); return v; }
__device__ __forceinline__ void sts16(uint32_t a, uint32_t v) { asm volatile("st.shared.u16 [%0], %1;" ::"r"(a), "h"((uint16_t)v) : "memory"); }
__device__ __forceinline__ void sts32(uint32_t a, uint32_t v) { asm volatile("st.shared.u32 [%0], %1;" ::"r"(a), "r"(v) : "memory"); }
__device__ __forceinline__ void sts64(uint32_t a, uint32_t x, uint32_t y) { asm volatile("st.shared.v2.u32 [%0], {%1,%2};" ::"r"(a), "r"(x), "r"(y) : "memory"); }
__device__ __forceinline__ void sts128(uint32_t a, uint32_t x, uint32_t y, uint32_t z, uint32_t w) { asm volatile("st.shared.v4.u32 [%0], {%1,%2,%3,%4};" ::"r"(a), "r"(x), "r"(y), "r"(z), "r"(w) : "memory"); }
__device__ __forceinline__ void st_async32(uint32_t a, uint32_t v, uint32_t bar) {
    asm volatile("st.async.shared::cluster.mbarrier::complete_tx::bytes.b32 [%0], %1, [%2];" ::"r"(a), "r"(v), "r"(bar) : "memory");
}
__device__ __forceinline__ void ldm4(uint32_t a, uint32_t& r0, uint32_t& r1, uint32_t& r2, uint32_t& r3) {
    asm volatile("ldmatrix.sync.aligned.m8n8.x4.shared.b16 {%0,%1,%2,%3}, [%4];" : "=r"(r0), "=r"(r1), "=r"(r2), "=r"(r3) : "r"(a) : "memory");
}
__device__ __forceinline__ void ldm4t(uint32_t a, uint32_t& r0, uint32_t& r1, uint32_t& r2, uint32_t& r3) {
    asm volatile("ldmatrix.sync.aligned.m8n8.x4.trans.shared.b16 {%0,%1,%2,%3}, [%4];" : "=r"(r0), "=r"(r1), "=r"(r2), "=r"(r3) : "r"(a) : "memory");
}
__device__ __forceinline__ void ldm2(uint32_t a, uint32_t& r0, uint32_t& r1) {
    asm volatile("ldmatrix.sync.aligned.m8n8.x2.shared.b16 {%0,%1}, [%2];" : "=r"(r0), "=r"(r1) : "r"(a) : "memory");
}
__device__ __forceinline__ void stm4(uint32_t a, uint32_t r0, uint32_t r1, uint32_t r2, uint32_t r3) {
    asm volatile("stmatrix.sync.aligned.m8n8.x4.shared.b16 [%0], {%1,%2,%3,%4};" ::"r"(a), "r"(r0), "r"(r1), "r"(r2), "r"(r3) : "memory");
}
__device__ __forceinline__ void mma_bf(float& c0, float& c1, float& c2, float& c3, uint32_t a0, uint32_t a1, uint32_t a2, uint32_t a3, uint32_t b0, uint32_t b1) {
    asm volatile("mma.sync.aligned.m16n8k16.row.col.f32.bf16.bf16.f32 {%0,%1,%2,%3},{%4,%5,%6,%7},{%8,%9},{%0,%1,%2,%3};"
                 : "+f"(c0), "+f"(c1), "+f"(c2), "+f"(c3) : "r"(a0), "r"(a1), "r"(a2), "r"(a3), "r"(b0), "r"(b1));
}
__device__ __forceinline__ void mma_bf(float (&c)[4], uint32_t a0, uint32_t a1, uint32_t a2, uint32_t a3, uint32_t b0, uint32_t b1) { mma_bf(c[0], c[1], c[2], c[3], a0, a1, a2, a3, b0, b1); }
__device__ __forceinline__ void mma_h(float (&c)[4], uint32_t a0, uint32_t a1, uint32_t a2, uint32_t a3, uint32_t b0, uint32_t b1) {
    asm volatile("mma.sync.aligned.m16n8k16.row.col.f32.f16.f16.f32 {%0,%1,%2,%3},{%4,%5,%6,%7},{%8,%9},{%0,%1,%2,%3};"
                 : "+f"(c[0]), "+f"(c[1]), "+f"(c[2]), "+f"(c[3]) : "r"(a0), "r"(a1), "r"(a2), "r"(a3), "r"(b0), "r"(b1));
}
__device__ __forceinline__ void mma_bf8(float (&c)[4], uint32_t a0, uint32_t a1, uint32_t b0) {
    asm volatile("mma.sync.aligned.m16n8k8.row.col.f32.bf16.bf16.f32 {%0,%1,%2,%3},{%4,%5},{%6},{%0,%1,%2,%3};"
                 : "+f"(c[0]), "+f"(c[1]), "+f"(c[2]), "+f"(c[3]) : "r"(a0), "r"(a1), "r"(b0));
}
__device__ __forceinline__ uint32_t pack_bf(float lo, float hi) { uint32_t r; asm("cvt.rn.bf16x2.f32 %0, %1, %2;" : "=r"(r) : "f"(hi), "f"(lo)); return r; }
__device__ __forceinline__ uint32_t pack_h(float lo, float hi) { uint32_t r; asm("cvt.rn.f16x2.f32 %0, %1, %2;" : "=r"(r) : "f"(hi), "f"(lo)); return r; }
__device__ __forceinline__ float bf_lo(uint32_t w) { return __uint_as_float(w << 16); }
__device__ __forceinline__ float bf_hi(uint32_t w) { return __uint_as_float(w & 0xFFFF0000u); }
__device__ __forceinline__ float bf_round(float x) { return bf_lo(pack_bf(x, 0.f)); }
__device__ __forceinline__ uint32_t badd(uint32_t a, uint32_t b) { uint32_t r; asm("add.rn.bf16x2 %0, %1, %2;" : "=r"(r) : "r"(a), "r"(b)); return r; }
__device__ __forceinline__ uint32_t bsub(uint32_t a, uint32_t b) { uint32_t r; asm("sub.rn.bf16x2 %0, %1, %2;" : "=r"(r) : "r"(a), "r"(b)); return r; }
__device__ __forceinline__ uint32_t bmul(uint32_t a, uint32_t b) { uint32_t r; asm("mul.rn.bf16x2 %0, %1, %2;" : "=r"(r) : "r"(a), "r"(b)); return r; }
__device__ __forceinline__ uint32_t bfma(uint32_t a, uint32_t b, uint32_t c) { uint32_t r; asm("fma.rn.bf16x2 %0, %1, %2, %3;" : "=r"(r) : "r"(a), "r"(b), "r"(c)); return r; }
__device__ __forceinline__ uint32_t prmt(uint32_t a, uint32_t b, uint32_t s) { uint32_t r; asm("prmt.b32 %0, %1, %2, %3;" : "=r"(r) : "r"(a), "r"(b), "r"(s)); return r; }
__device__ __forceinline__ float ex2f(float x) { float r; asm("ex2.approx.ftz.f32 %0, %1;" : "=f"(r) : "f"(x)); return r; }
__device__ __forceinline__ float rcpf(float x) { float r; asm("rcp.approx.ftz.f32 %0, %1;" : "=f"(r) : "f"(x)); return r; }
__device__ __forceinline__ float silu_f(float x) { return x * rcpf(1.f + ex2f(-1.4426950408889634f * x)); }
__device__ __forceinline__ uint32_t norm2(uint32_t x, uint32_t m, uint32_t hi, uint32_t lo) { uint32_t d = bsub(x, m); return bfma(d, hi, bmul(d, lo)); }
__device__ __forceinline__ uint32_t clk32() { uint32_t c; asm volatile("mov.u32 %0, %%clock;" : "=r"(c)); return c; }
__device__ __forceinline__ void spin_until(uint32_t t0, int dt) {
#pragma unroll 1
    while ((int)(clk32() - t0) < dt) __nanosleep(32);
}
__device__ __forceinline__ float sqrt_ap(float x) { float r; asm("sqrt.approx.ftz.f32 %0, %1;" : "=f"(r) : "f"(x)); return r; }

__device__ __forceinline__ void cp16(uint32_t dst, const void* src) { asm volatile("cp.async.cg.shared.global [%0], [%1], 16;" ::"r"(dst), "l"(src) : "memory"); }
__device__ __forceinline__ void pf_l2(const void* p) { asm volatile("cp.async.bulk.prefetch.L2.global [%0], 16;" ::"l"(p) : "memory"); }
__device__ __forceinline__ void bulk_s2g(void* dst, uint32_t src, int bytes) {
    asm volatile("cp.async.bulk.global.shared::cta.bulk_group [%0], [%1], %2;" ::"l"(dst), "r"(src), "r"(bytes) : "memory");
}
__device__ __forceinline__ uint32_t ld_acq(const void* p) { uint32_t v; asm volatile("ld.acquire.gpu.global.u32 %0, [%1];" : "=r"(v) : "l"(p) : "memory"); return v; }
__device__ __forceinline__ void red_add(void* p) { asm volatile("red.relaxed.gpu.global.add.u32 [%0], 1;" ::"l"(p) : "memory"); }
__device__ __forceinline__ void fence_async() { asm volatile("fence.proxy.async.shared::cta;" ::: "memory"); }
__device__ __forceinline__ void fence_async_g() { asm volatile("fence.proxy.async.global;" ::: "memory"); }
__device__ __forceinline__ void red_rel(void* p) { asm volatile("red.release.gpu.global.add.u32 [%0], 1;" ::"l"(p) : "memory"); }
__device__ __forceinline__ void wait_count(const uint32_t* p, uint32_t want) {
#pragma unroll 1
    for (int it = 0; it < SPIN_LIMIT && ld_rlx(p) != want; it++) __nanosleep(20);
}
__device__ __forceinline__ uint32_t ld_stat(const uint32_t* p, uint32_t tag) {
    uint32_t v = 0;
#pragma unroll 1
    for (int it = 0; it < SPIN_LIMIT; it++) {
        v = ld_rlx(p);
        if ((v >> 31) == tag) break;
    }
    return v & 0x7FFFFFFFu;
}
__device__ __forceinline__ uint32_t hadd(uint32_t a, uint32_t b) { uint32_t r; asm("add.rn.f16x2 %0, %1, %2;" : "=r"(r) : "r"(a), "r"(b)); return r; }
__device__ __forceinline__ float h_lo(uint32_t w) { return __half2float(__ushort_as_half((unsigned short)w)); }
__device__ __forceinline__ float h_hi(uint32_t w) { return __half2float(__ushort_as_half((unsigned short)(w >> 16))); }
__device__ __forceinline__ uint32_t x0_chunk(uint32_t xb, int c) { return xb + ((c & 1) ? X0_ODD + 120 : 128) + 8 * c; }

struct cf { float x, y; };
__device__ __forceinline__ cf cmul(cf a, cf b) { return {a.x * b.x - a.y * b.y, a.x * b.y + a.y * b.x}; }
__device__ __forceinline__ cf csq(cf a) { return {a.x * a.x - a.y * a.y, (a.x + a.x) * a.y}; }
__device__ __forceinline__ cf cpow_direct(float zr2, float zi, float l) {
    const float mag = ex2f(zr2 * l), th = zi * l;
    return {mag * __cosf(th), mag * __sinf(th)};
}
__device__ __forceinline__ __half2 as_h2(uint32_t v) { return *reinterpret_cast<__half2*>(&v); }
__device__ __forceinline__ uint32_t as_u32(__half2 v) { return *reinterpret_cast<uint32_t*>(&v); }
struct hm { uint32_t v, s; };
__device__ __forceinline__ hm mk_hm(cf a) {
    const uint32_t v = pack_h(a.x, a.y);
    return {v, prmt(v, v, 0x1032) ^ 0x8000u};
}
__device__ __forceinline__ uint32_t hcmul(uint32_t x, hm y) {
    const __half2 xx = as_h2(x);
    return as_u32(__hfma2(__high2half2(xx), as_h2(y.s), __hmul2(__low2half2(xx), as_h2(y.v))));
}

struct KParams { uint32_t are, aim, bre, bim, cre, cim, ldt; };
__device__ __forceinline__ KParams kgen_load(const Hot& p, int ch, int half, int lane) {
    const uint32_t po = ch * 64 + half * 32 + lane;
    KParams k;
    k.are = __ldg((const uint32_t*)p.are + po); k.aim = __ldg((const uint32_t*)p.aim + po);
    k.bre = __ldg((const uint32_t*)p.bre + po); k.bim = __ldg((const uint32_t*)p.bim + po);
    k.cre = __ldg((const uint32_t*)p.cre + po); k.cim = __ldg((const uint32_t*)p.cim + po);
    k.ldt = __ldg((const uint16_t*)p.logdt + ch + (lane & p.tn.zero));
    return k;
}

__device__ __forceinline__ void kgen(KParams kp, uint32_t scr, uint32_t os, int c0, int c1, uint32_t pause) {
    const int lane = threadIdx.x & 31;
    const float dt = bf_round(ex2f(bf_lo(kp.ldt) * 1.4426950408889634f));
    const cf w0 = cmul({bf_lo(kp.cre), bf_lo(kp.cim)}, {dt * bf_lo(kp.bre), dt * bf_lo(kp.bim)});
    const cf w1 = cmul({bf_hi(kp.cre), bf_hi(kp.cim)}, {dt * bf_hi(kp.bre), dt * bf_hi(kp.bim)});
    uint32_t eb = __reduce_max_sync(~0u, __float_as_uint(fmaxf(fmaxf(fabsf(w0.x), fabsf(w0.y)), fmaxf(fabsf(w1.x), fabsf(w1.y))))) & 0x7F800000u;
    eb = min(max(eb, 0x00800000u), 0x7E800000u);
    const float sc = __uint_as_float(0x7F000000u - eb);
    float k0 = c0 ? 0.f : w0.x + w1.x;
#pragma unroll
    for (int o = 16; o > 0; o >>= 1) k0 += __shfl_xor_sync(~0u, k0, o);
    float d[5][4];
#pragma unroll
    for (int i = 0; i < 5; i++) d[i][0] = d[i][1] = d[i][2] = d[i][3] = 0.f;
    const int mi = lane >> 3, j = lane & 7;
    const uint32_t st0 = scr + mi * 128 + ((j ^ mi) << 4), st1 = st0 ^ 64;
    const uint32_t la = scr + (lane & 15) * 128 + (((lane >> 4) ^ j) << 4), lb = scr + j * 128 + ((mi ^ j) << 4);
    auto st = [&](int row, uint32_t a, uint32_t b, uint32_t c, uint32_t e) { stm4(((row & 4) ? st1 : st0) + row * 128, a, b, c, e); };
#pragma unroll 1
    for (int c = c0; c < c1; c++) {
        if (c > c0 && pause) mbar_wait(pause, 0);
        const float zr2 = dt * (c ? bf_hi(kp.are) : bf_lo(kp.are)) * 1.4426950408889634f;
        const float zi = dt * (c ? bf_hi(kp.aim) : bf_lo(kp.aim));
        const cf w = {(c ? w1.x : w0.x) * sc, (c ? w1.y : w0.y) * sc};
        const cf a1 = cpow_direct(zr2, zi, 1.f), a256 = cpow_direct(zr2, zi, 256.f);
        uint32_t a[4][4];
        {
            const cf a16 = cpow_direct(-zr2, zi, -16.f);
            const cf a32 = csq(a16), a48 = cmul(a32, a16), a64 = csq(a32), a128 = csq(a64), a192 = cmul(a128, a64);
            const uint32_t p1 = pack_h(a16.x, a16.y), p2 = pack_h(a32.x, a32.y), p3 = pack_h(a48.x, a48.y);
            const hm q1 = mk_hm(a64), q2 = mk_hm(a128), q3 = mk_hm(a192);
            __syncwarp();
            st(0, 0x00003C00u, p1, p2, p3);
            st(4, q1.v, hcmul(p1, q1), hcmul(p2, q1), hcmul(p3, q1));
            st(8, q2.v, hcmul(p1, q2), hcmul(p2, q2), hcmul(p3, q2));
            st(12, q3.v, hcmul(p1, q3), hcmul(p2, q3), hcmul(p3, q3));
            __syncwarp();
#pragma unroll
            for (int k = 0; k < 4; k++) ldm4(la ^ (k * 32), a[k][0], a[k][1], a[k][2], a[k][3]);
        }
        auto tile = [&](int T, int row) {
#pragma unroll
            for (int kp2 = 0; kp2 < 2; kp2++) {
                uint32_t b0, b1, b2, b3;
                ldm4((lb ^ (kp2 * 64)) + row * 128, b0, b1, b2, b3);
                mma_h(d[T], a[2 * kp2][0], a[2 * kp2][1], a[2 * kp2][2], a[2 * kp2][3], b0, b1);
                mma_h(d[T], a[2 * kp2 + 1][0], a[2 * kp2 + 1][1], a[2 * kp2 + 1][2], a[2 * kp2 + 1][3], b2, b3);
            }
        };
        const cf a2 = csq(a1), a4 = csq(a2), a8 = csq(a4), a12 = cmul(a8, a4);
        const cf u1 = cmul(w, a1), u2 = cmul(w, a2), u3 = cmul(u2, a1), u4 = cmul(w, a4);
        uint32_t v[16];
        v[0] = pack_h(u1.x, u1.y); v[1] = pack_h(u2.x, u2.y); v[2] = pack_h(u3.x, u3.y); v[3] = pack_h(u4.x, u4.y);
        const hm m4 = mk_hm(a4), m8 = mk_hm(a8), m12 = mk_hm(a12);
#pragma unroll
        for (int i = 0; i < 4; i++) { v[4 + i] = hcmul(v[i], m4); v[8 + i] = hcmul(v[i], m8); v[12 + i] = hcmul(v[i], m12); }
        const hm m256 = mk_hm(a256);
        __syncwarp();
#pragma unroll
        for (int i = 0; i < 4; i++) st(4 * i, v[4 * i], v[4 * i + 1], v[4 * i + 2], v[4 * i + 3]);
        st(16, hcmul(v[1], m256), hcmul(v[3], m256), hcmul(v[5], m256), hcmul(v[7], m256));
        st(20, hcmul(v[9], m256), hcmul(v[11], m256), hcmul(v[13], m256), hcmul(v[15], m256));
        __syncwarp();
        tile(0, 0); tile(1, 8); tile(2, 16);
        const cf a512 = csq(a256), a768 = cmul(a512, a256), a1024 = csq(a512);
        const cf a1280 = cmul(a1024, a256), a1536 = csq(a768), a1792 = cmul(a1024, a768);
        const hm m512 = mk_hm(a512), m768 = mk_hm(a768);
        const hm n0 = mk_hm(a1024), n1 = mk_hm(a1280), n2 = mk_hm(a1536), n3 = mk_hm(a1792);
        __syncwarp();
        st(0, hcmul(v[3], m512), hcmul(v[7], m512), hcmul(v[11], m512), hcmul(v[15], m512));
        st(4, hcmul(v[3], m768), hcmul(v[7], m768), hcmul(v[11], m768), hcmul(v[15], m768));
        st(8, hcmul(v[7], n0), hcmul(v[15], n0), hcmul(v[7], n1), hcmul(v[15], n1));
        st(12, hcmul(v[7], n2), hcmul(v[15], n2), hcmul(v[7], n3), hcmul(v[15], n3));
        __syncwarp();
        tile(3, 0); tile(4, 8);
    }
    __syncwarp();
#pragma unroll
    for (int i = 0; i < 5; i++) sts128(os + i * 512 + lane * 16, __float_as_uint(d[i][0]), __float_as_uint(d[i][1]), __float_as_uint(d[i][2]), __float_as_uint(d[i][3]));
    sts64(os + 2560, eb, __float_as_uint(k0));
}

__device__ __forceinline__ void ktables(uint32_t os, int ostep, int np, uint32_t kr, uint32_t kt, uint32_t kinf, int part) {
    const int lane = threadIdx.x & 31, g = lane >> 2, t = lane & 3;
    uint32_t eb = 0;
    float k0 = 0.f, f[4];
#pragma unroll
    for (int q = 0; q < 4; q++) {
        uint2 v = make_uint2(0u, 0u);
        if (q < np) v = lds64(os + q * ostep + 2560);
        eb = max(eb, v.x);
        k0 += __uint_as_float(v.y);
        f[q] = __uint_as_float(v.x);
    }
    const float rs = __uint_as_float(0x7F000000u - eb);
#pragma unroll
    for (int q = 0; q < 4; q++) f[q] *= rs;
#pragma unroll 1
    for (int i = (part & 1) ? 0 : 2; i < ((part & 2) ? 5 : 3); i++) {
        float a0 = 0.f, a1 = 0.f, a2 = 0.f, a3 = 0.f;
        uint4 v[4];
#pragma unroll
        for (int q = 0; q < 4; q++) {
            v[q] = make_uint4(0u, 0u, 0u, 0u);
            if (q < np) v[q] = lds128(os + q * ostep + i * 512 + lane * 16);
        }
#pragma unroll
        for (int q = 0; q < 4; q++) { a0 += __uint_as_float(v[q].x) * f[q]; a1 += __uint_as_float(v[q].y) * f[q]; a2 += __uint_as_float(v[q].z) * f[q]; a3 += __uint_as_float(v[q].w) * f[q]; }
        const int sg = 32 >> max(i - 1, 0);
        const uint32_t o = kr + 4 + (i < 2 ? 16 * i : 256 * i) + sg * g + (i < 3 ? 8 : 128) * (t >> 1) + (i < 4 ? 4 : 64) * (t & 1);
        sts32(o, pack_h(a0, a1));
        sts32(o + 8 * sg, pack_h(a2, a3));
    }
    sts32(kr, pack_h(0.f, k0 * rs));
    __syncwarp();
    if (part & 1) {
        uint32_t w0[4], w1[4], a[2], b[2];
#pragma unroll
        for (int r = 0; r < 4; r++) { w0[r] = lds32(kr + 4 * lane + 128 * r); w1[r] = lds32(kr + 4 * lane + 128 * r + 4); }
#pragma unroll
        for (int r = 0; r < 2; r++) { a[r] = lds32(kr + 512 + 4 * lane + 128 * r); b[r] = lds32(kr + 516 + 4 * lane + 128 * r); }
#pragma unroll
        for (int r = 0; r < 4; r++) sts64(kt + 8 * lane + 256 * r + 32, prmt(w0[r], w0[r], 0x1032), prmt(w0[r], w1[r], 0x3254));
        if (lane == 31) b[1] = pack_h(h_lo(b[1]) - h_hi(b[1]), 0.f);
#pragma unroll
        for (int r = 0; r < 2; r++)
            sts128(kt + 4 * 264 + 16 * lane + 512 * r, prmt(a[r], a[r], (r == 0 && lane == 0) ? 0x1032 : 0x3232), prmt(a[r], a[r], 0x3232), prmt(a[r], b[r], 0x3254), prmt(b[r], b[r], 0x1032));
        if (lane < 24) sts32(kt + 4 * (lane < 8 ? lane : 512 + lane), 0u);
    }
    if (part & 2) {
        const uint32_t k512 = lds16(kr + 2 * 385), k1024 = lds16(kr + 2 * 513);
        if (lane == 0) {
            sts128(kinf, eb, __float_as_uint(h_lo(k512)), k1024, 0u);
            sts16(kr + 2 * 512, pack_h(h_lo(lds16(kr + 2 * 512)) - h_lo(k1024), 0.f));
        }
#pragma unroll
        for (int r = 0; r < 3; r++)
            if (r < 2 || lane < 26) sts128(kt + KT_P4 + 16 * lane + 512 * r, 0u, 0u, 0u, 0u);
        __syncwarp();
        uint32_t x0[5], x1[5], y0[5], y1[5];
#pragma unroll
        for (int r = 0; r < 5; r++) {
            const int m = min(126 + lane + 32 * r, 256);
            x0[r] = lds16(kr + 2 * (257 + m)); x1[r] = lds16(kr + 2 * (259 + m)); y0[r] = lds16(kr + 2 * (385 + m)); y1[r] = lds16(kr + 2 * (387 + m));
        }
#pragma unroll
        for (int r = 0; r < 5; r++) {
            const int m = 126 + lane + 32 * r;
            if (m < 128) x0[r] = y0[r] = 0;
            if (m > 253) x1[r] = 0;
            if (m > 254) y1[r] = 0;
            if (m < 256) sts32(kt + KT_P4 + 4 * (((m - 96) & ~3) | ((m & 1) << 1) | ((m >> 1) & 1)), x0[r] | (x1[r] << 16));
            if (m < 257) sts32(kt + KT_P8 + 4 * (m - 96), y0[r] | (y1[r] << 16));
        }
    }
    __syncwarp();
}

__device__ __forceinline__ void mma_hc(float (&d)[4], const float (&c)[4], uint32_t a0, uint32_t a1, uint32_t a2, uint32_t a3, uint32_t b0, uint32_t b1) {
    asm volatile("mma.sync.aligned.m16n8k16.row.col.f32.f16.f16.f32 {%0,%1,%2,%3},{%4,%5,%6,%7},{%8,%9},{%10,%11,%12,%13};"
                 : "=f"(d[0]), "=f"(d[1]), "=f"(d[2]), "=f"(d[3]) : "r"(a0), "r"(a1), "r"(a2), "r"(a3), "r"(b0), "r"(b1), "f"(c[0]), "f"(c[1]), "f"(c[2]), "f"(c[3]));
}
template <int Q0, int Q1>
__device__ __forceinline__ void sweep_steps(float (&w)[5][4], const uint32_t (&R)[66], uint32_t xa, uint32_t (&x)[5], uint32_t z) {
#pragma unroll
    for (int q = Q0; q <= Q1; q++) {
        uint32_t n0, n1;
        ldm2(xa + 16 * (q + 1), n0, n1);
        const uint32_t a2 = x[0] | z, a3 = x[1] | z;
#pragma unroll
        for (int j = 0; j < 4; j++) {
            const int s = 8 * j + 8 - q;
            if (q == 1) mma_hc(w[j], w[j + 1], x[1], x[2], a2, a3, R[2 * s], R[2 * s + 1]);
            else mma_h(w[j], x[1], x[2], a2, a3, R[2 * s], R[2 * s + 1]);
        }
        if (q == 8) {
            const float zero[4] = {0.f, 0.f, 0.f, 0.f};
            mma_hc(w[4], zero, x[1], x[2], a2, a3, R[64], R[65]);
        }
        x[0] = x[2]; x[1] = x[3]; x[2] = x[4]; x[3] = n0; x[4] = n1;
    }
}

__device__ __forceinline__ void box_round(uint32_t xb, uint32_t fa, int rho, int lane) {
    if (rho == 6) {
        const int a = lane >> 3, j = lane & 7;
        sts128(fa + 3328 * (lane >> 4) + 16 * ((lane & 15) < 15 ? (lane & 15) : 207), 0u, 0u, 0u, 0u);
        sts128(fa + FB9E + 1168 * a + 16 * (j < 7 ? j : 71 + (a & 1)), 0u, 0u, 0u, 0u);
        __syncwarp();
    }
    const int c = rho < 6 ? 32 * rho + lane : -1;
    const uint4 pv = lds128(x0_chunk(xb, c - 1)), ow = lds128(x0_chunk(xb, c));
    const uint2 nx = lds64(x0_chunk(xb, c + 1));
    const uint32_t P[9] = {pv.y, pv.z, pv.w, ow.x, ow.y, ow.z, ow.w, nx.x, nx.y};
    uint32_t Q[8], b3[6], b5[4];
#pragma unroll
    for (int k = 0; k < 8; k++) Q[k] = prmt(P[k], P[k + 1], 0x5432);
#pragma unroll
    for (int k = 0; k < 6; k++) b3[k] = hadd(hadd(Q[k], Q[k + 1]), P[k + 1]);
#pragma unroll
    for (int k = 0; k < 4; k++) b5[k] = hadd(b3[k + 2], hadd(P[k + 2], P[k + 4]));
    sts128(fa + FB5 + 240 + 16 * c, b5[0], b5[1], b5[2], b5[3]);
    sts128(fa + FB3 + 240 + 16 * c, b3[0], b3[1], b3[2], b3[3]);
    if (rho < 4 || rho == 6) {
        uint32_t b7[4], b9[4];
#pragma unroll
        for (int k = 0; k < 4; k++) {
            b7[k] = hadd(b5[k], hadd(Q[k + 1], Q[k + 4]));
            b9[k] = hadd(b7[k], hadd(P[k + 1], P[k + 5]));
        }
        const uint32_t ad = fa + ((c & 1) ? FB9O + 120 : FB9E + 112) + 8 * c;
        sts128(ad, b9[0], b9[1], b9[2], b9[3]);
        sts128(ad + (FB7E - FB9E), b7[0], b7[1], b7[2], b7[3]);
    }
}

__global__ void __cluster_dims__(2, 1, 1) __launch_bounds__(NTHREADS, 1) fused_kernel(const Hot p, const __grid_constant__ Maps m) {
    extern __shared__ __align__(1024) char smem[];
    const uint32_t t0 = clk32();
    const int tid = (threadIdx.x + 32 * 0) & (NTHREADS - 1), lane = tid & 31, warp = __shfl_sync(~0u, tid >> 5, 0), bid = blockIdx.x;
    const uint32_t S = smem_u32(smem), z = (uint32_t)p.tn.zero;
    const bool down = bid < NDOWN, rowcta = bid < NMAIN, big = rowcta && !down;
    const int xd = rowcta ? bid : 142 + ((bid - NMAIN) >> 1);
    const int slot = warp < 8 ? (warp & 3) : 4;
    const bool has = warp < 8 ? (rowcta || (slot >> 1) == (bid & 1)) : (big && warp < 12);
    const int ch = slot < 4 ? 4 * xd + slot : 512 + bid - NDOWN;
    KParams kp;
    if (has) kp = kgen_load(p, ch, warp < 8 ? warp >> 2 : (warp >> 1) & 1, lane);
    if (elect()) {
#pragma unroll 1
        for (int i = warp; i < B_COUNT; i += 16) {
            const uint32_t c = i < 16 ? (uint32_t)((big ? 0x1411115555412290ull : 0x1411114444412290ull) >> (4 * i)) & 15 : 1;
            mbar_init(S + i * 8, c ? c : NTHREADS);
        }
        asm volatile("fence.mbarrier_init.release.cluster;" ::: "memory");
    }
    if (rowcta) {
#pragma unroll 1
        for (int i = tid; i < 1224; i += NTHREADS)
            cp16(S + SM_ROWS + 16 * (i + min((i * 911) >> 16, 16)), i < 1152 ? (const uint4*)p.u + bid * 1152 + i : (const uint4*)p.wr + (i - 1152));
    }
    if (tid >= 256 && tid < 336) {
        const int i = tid - 256;
        if (i < 64 || big) sts128(S + (i < 64 ? SM_X0 + (i >> 4) * X0_STRIDE : SM_EX) + ((i & 8) ? X0_ODD : 0) + 16 * (i & 7), 0u, 0u, 0u, 0u);
    }
    if (tid == 447) sts128(S + SM_ONES, 0x3F803F80u, 0x3F803F80u, 0x3F803F80u, 0x3F803F80u);
    __syncthreads();
    if (rowcta) asm volatile("cp.async.mbarrier.arrive.noinc.shared::cta.b64 [%0];" ::"r"(S + B_ROWS * 8) : "memory");
    if (warp == 15 && lane < 4) mbar_expect(S + (lane < 3 ? B_GX + lane : B_RED) * 8, 256);
    asm volatile("barrier.cluster.arrive.relaxed.aligned;" ::: "memory");
    const int g = lane >> 2, t = lane & 3, mi = lane >> 3, j = lane & 7;
    const uint32_t SW = S + (down ? SM_W_DOWN : SM_W_BIG);
    const int pr = bid >> 1, r = bid & 1, nsl = pr >= 54 ? 3 : 2, sl0 = pr < 54 ? 2 * pr : 3 * pr - 54;

    if (warp == 12) {
        if (elect()) {
            const int ng = 6 * nsl, ns = down ? 24 : ng;
            const CUtensorMap* mg = r ? &m.wu : &m.wg;
            pf_tmap(mg);
            if (down) pf_tmap(&m.wd);
            const uint32_t epoch = ld_rlx(&p.s->cnt[16 * 32]) + 1;
            spin_until(t0, p.tn.f_start);
            int done = 0;
#pragma unroll 1
            for (int s = 0; s < ns; s++) {
                if (s == ng) spin_until(t0, p.tn.f_t3);
                #pragma unroll 1
                for (int it = 0; it < SPIN_LIMIT; it++) {
                    const int w = s >= ng ? p.tn.w3 : ((int)(clk32() - t0) < p.tn.f_t2 ? p.tn.w1 : (nsl == 3 ? p.tn.w2b : p.tn.w2));
                    if (s - done < w) break;
                    if (mbar_test(S + (B_W + done) * 8, 0)) done++;
                    else __nanosleep(32);
                }
                const uint32_t bar = S + (B_W + s) * 8;
                uint32_t dst = SW + s * STAGE;
                if (s == 23) { mbar_wait(S + B_EM * 8, 0); fence_async(); dst = S + SM_W_LAST; }
                mbar_expect(bar, STAGE);
                const int u = (s * 43) >> 8;
                if (s < ng) tma2d(dst, mg, 32 * (sl0 + u), 96 * (s - 6 * u), bar);
                else tma2d(dst, &m.wd, 16 * pr, r * 2304 + 192 * (s - 12), bar);
            }
            if (rowcta) {
                mbar_wait(S + B_FD * 8, 0);
                fence_async();
#pragma unroll 1
                for (int q = 0; q < 4; q++) {
                    wait_count(&p.s->cnt[(8 + q) * 32], epoch * (uint32_t)D_);
                    fence_async_g();
                    mbar_expect(S + (B_YIN + q) * 8, 4608);
                    bulk_g2s(S + SM_STG + q * 4608, p.s->y + (32 * q + (bid >> 2)) * 4608 + (bid & 3) * 1152, 4608, S + (B_YIN + q) * 8);
                }
            }
        }
        return;
    }

    uint32_t epoch = 0;
    if (warp >= 8 || !rowcta) epoch = ld_rlx(&p.s->cnt[16 * 32] + (lane & z)) + 1;
    const uint32_t tag = epoch & 1;
    const int hw = warp < 12 ? warp - 8 : warp - 9;

    if (rowcta && warp >= 8 && warp < 15) {
        const uint32_t ad = S + SM_ROWS + (lane & 15) * ROW_STRIDE + 192 * hw + 16 * (lane >> 4);
        uint32_t wd = j ? S + SM_ROWS + 16 * ROW_STRIDE + 192 * hw + 16 * mi : S + SM_ONES;
        const uint32_t wstep = j ? 64 : 0, ones = 0x3F803F80u | z;
        float d1[4] = {0, 0, 0, 0}, d2[4] = {0, 0, 0, 0}, d3[4] = {0, 0, 0, 0}, d4[4] = {0, 0, 0, 0};
        mbar_wait(S + B_ROWS * 8, 0);
#pragma unroll
        for (int kk = 0; kk < 3; kk++) {
            uint32_t w[4];
            ldm4(wd, w[0], w[1], w[2], w[3]);
            wd += wstep;
#pragma unroll
            for (int e = 0; e < 2; e++) {
                uint32_t a0, a1, a2, a3;
                ldm4(ad + 64 * kk + 32 * e, a0, a1, a2, a3);
                mma_bf(d1, a0, a1, a2, a3, w[2 * e], w[2 * e + 1]);
                mma_bf(d2, a0, a1, a2, a3, a0, a2);
                mma_bf(d3, a0, a1, a2, a3, a1, a3);
                mma_bf(d4, ones, ones ^ z, ones + z, ones - z, w[2 * e], w[2 * e + 1]);
            }
        }
        float* part = (float*)(smem + SM_PART + hw * 256) + g * 4;
        if (t == 0) {
            *(float2*)part = make_float2(d1[0], d1[1]);
            *(float2*)(part + 32) = make_float2(d1[2], d1[3]);
            part[3] = d4[1];
            part[35] = d4[1];
        }
        if (t == (g >> 1)) {
            part[2] = (g & 1) ? d2[1] : d2[0];
            part[34] = (g & 1) ? d3[3] : d3[2];
        }
        bar_sync(1, 192);
        if (hw == 0 && lane < 16) {
            float4 s = *(const float4*)(smem + SM_PART + lane * 16);
#pragma unroll
            for (int w = 1; w < 6; w++) {
                const float4 v = *(const float4*)(smem + SM_PART + w * 256 + lane * 16);
                s.x += v.x; s.y += v.y; s.z += v.z; s.w += v.w;
            }
            const float mean = s.x * (1.f / 576.f);
            const float var = fmaxf(s.z * (1.f / 576.f) - mean * mean, 0.f);
            const uint32_t mm = pack_bf(mean, mean);
            const float mu = bf_lo(mm), sd = bf_round(sqrt_ap(bf_round(bf_round(var) + 1e-5f))), ri = rcpf(sd);
            const uint32_t hi = pack_bf(ri, ri);
            const float rl = ri - bf_lo(hi);
            sts16(S + SM_STA + 2 * lane, mm); sts16(S + SM_STA + 32 + 2 * lane, hi); sts16(S + SM_STA + 64 + 2 * lane, pack_bf(rl, rl));
            const uint32_t rb = pack_bf(0.f, (s.y - mu * s.w) * ri);
            const int row = bid * 16 + lane;
            p.s->stat[row] = (mm & 0xFFFFu) | __float_as_uint(sd) | (tag << 31);
            p.s->key[row] = ((rb ^ (((int)rb >> 31) | 0x80000000u)) & 0xFFFF0000u) | (tag << 15) | (2047 - row);
        }
        bar_sync(1, 192);
        if (tid == 256) mbar_arrive(S + B_P1 * 8);
        {
            const uint2 sm = lds64(S + SM_STA + 8 * t), sh = lds64(S + SM_STA + 32 + 8 * t), sl = lds64(S + SM_STA + 64 + 8 * t);
            const uint32_t at = S + SM_ROWS + (4 * (j >> 1) + (j & 1) + 2 * (mi & 1)) * ROW_STRIDE + 32 * hw + 16 * (mi >> 1);
            uint2* dst = (uint2*)p.s->x + (4 * hw + (g >> 2)) * 2048 + bid * 16 + (g & 3) * 4 + t;
            uint32_t r4[6][4];
#pragma unroll
            for (int n = 5; n >= 0; n--) ldm4t(at + 192 * n, r4[n][0], r4[n][1], r4[n][2], r4[n][3]);
#pragma unroll
            for (int n = 5; n >= 0; n--) {
                uint32_t o[4];
#pragma unroll
                for (int e = 0; e < 4; e++) {
                    const uint32_t v = (e & 1) ? norm2(r4[n][e], sm.y, sh.y, sl.y) : norm2(r4[n][e], sm.x, sh.x, sl.x);
                    o[e] = pack_h(bf_lo(v), bf_hi(v));
                }
                dst[n * 49152] = make_uint2((o[0] & ~1u) | tag, o[1]);
                dst[n * 49152 + 4096] = make_uint2((o[2] & ~1u) | tag, o[3]);
            }
        }
        bar_sync(1, 192);
    }

    if (has) {
        asm volatile("" : "+r"(kp.ldt), "+r"(kp.are), "+r"(kp.aim), "+r"(kp.bre), "+r"(kp.bim), "+r"(kp.cre), "+r"(kp.cim));

        const uint32_t scr = warp < 8 ? S + SM_STG + warp * KG_SCR : S + EX_HAND + hw * KG_SCR;
        kgen(kp, scr, warp < 8 ? scr : S + EX_FAR + hw * 2576, warp < 8 ? 0 : warp & 1, warp < 8 ? 2 : (warp & 1) + 1, rowcta ? S + B_P1 * 8 : 0);
        if (warp >= 8) { __syncwarp(); if (lane == 0) mbar_arrive(S + B_TAB * 8); }
    }
    if (warp < 8 || warp == 15) {
        if (warp < 8 ? has : big) {
            if (warp < 8) bar_sync(4 + slot, 64); else mbar_wait(S + B_TAB * 8, 0);
            ktables(warp < 8 ? S + SM_STG + slot * KG_SCR : S + EX_FAR, warp < 8 ? 4 * KG_SCR : 2576, warp < 8 ? 2 : 4, S + SM_XS + slot * KR_STRIDE,
                    S + (warp < 8 ? SM_KT + slot * KT_STRIDE : EX_KT), S + SM_KINF + slot * 16, warp < 8 ? 1 + (warp >> 2) : 3);
        }
        if (lane == 0) { mbar_arrive(S + B_KG * 8); if (warp == 15) mbar_arrive(S + B_TAB1 * 8); }
    }

    if (!rowcta && warp < 8 && !has) {
        const int w4 = (warp >> 2) * 2 + (warp & 1), i = 32 * w4 + lane;
#pragma unroll 1
        for (int pass = 1; pass < 2; pass++) {
        uint4 k[4];
        if (pass) spin_until(t0, p.tn.t_svc - 1500);
#pragma unroll 1
        for (int it = 0; it < SPIN_LIMIT; it++) {
            if (!pass) {
#pragma unroll
                for (int q = 0; q < 4; q++) k[q] = make_uint4(16 * i + 4 * q, 16 * i + 4 * q + 1, 16 * i + 4 * q + 2, 16 * i + 4 * q + 3);
                break;
            }
            uint32_t bad = 0;
#pragma unroll
            for (int q = 0; q < 4; q++) k[q] = ld_rlx4(&p.s->key[4 * i + 512 * q]);
#pragma unroll
            for (int q = 0; q < 4; q++) bad |= tag ? ~(k[q].x & k[q].y & k[q].z & k[q].w) : (k[q].x | k[q].y | k[q].z | k[q].w);
            if (!(bad & 0x8000u)) break;
            __nanosleep(100);
        }
        const uint32_t sc = S + SM_XS + ((bid & 1) ? 0 : 2) * KR_STRIDE;
        auto pk = [](uint32_t v) { return ((v >> 16) << 11) | (v & 2047u); };
        auto gt = [](uint32_t a, uint32_t b) { return (b - a) >> 31; };
        uint32_t mx = 0;
#pragma unroll
        for (int q = 0; q < 4; q++) {
            k[q] = make_uint4(pk(k[q].x), pk(k[q].y), pk(k[q].z), pk(k[q].w));
            mx = max(max(mx, max(k[q].x, k[q].y)), max(k[q].z, k[q].w));
        }
        bar_sync(1, 128);
        sts32(sc + 4 * i, mx);
        if (i == 0) sts32(sc + 1024, 0u);
        bar_sync(1, 128);
        int rank;
        {
            int c[8] = {0, 0, 0, 0, 0, 0, 0, 0};
#pragma unroll 1
            for (int q = 0; q < 32; q += 4) {
                uint4 v[4];
#pragma unroll
                for (int e = 0; e < 4; e++) v[e] = lds128(sc + 16 * (q + e));
#pragma unroll
                for (int e = 0; e < 4; e++) {
                    c[(2 * e) & 7] += gt(v[e].x, mx); c[(2 * e + 1) & 7] += gt(v[e].y, mx);
                    c[(2 * e + 4) & 7] += gt(v[e].z, mx); c[(2 * e + 5) & 7] += gt(v[e].w, mx);
                }
            }
            rank = ((c[0] + c[1]) + (c[2] + c[3])) + ((c[4] + c[5]) + (c[6] + c[7]));
        }
        if (rank == 7) sts32(sc + 1028, mx);
        bar_sync(1, 128);
        if (rank < 8) {
            const uint32_t lb = lds32(sc + 1028);
            int cq[4];
#pragma unroll
            for (int q = 0; q < 4; q++) cq[q] = (gt(lb, k[q].x) + gt(lb, k[q].y)) + (gt(lb, k[q].z) + gt(lb, k[q].w));
            const int c = 16 - ((cq[0] + cq[1]) + (cq[2] + cq[3]));
            uint32_t pos;
            asm volatile("atom.shared.add.u32 %0, [%1], %2;" : "=r"(pos) : "r"(sc + 1024), "r"(c) : "memory");
            pos = sc + 512 + 4 * pos;
#pragma unroll
            for (int q = 0; q < 4; q++) {
                if (k[q].x >= lb) { sts32(pos, k[q].x); pos += 4; }
                if (k[q].y >= lb) { sts32(pos, k[q].y); pos += 4; }
                if (k[q].z >= lb) { sts32(pos, k[q].z); pos += 4; }
                if (k[q].w >= lb) { sts32(pos, k[q].w); pos += 4; }
            }
        }
        bar_sync(1, 128);
        const int n = lds32(sc + 1024);
        if (i < n) {
            const uint32_t mine = lds32(sc + 512 + 4 * i);
            rank = 0;
#pragma unroll 1
            for (int q = 0; q < n; q += 4) {
                const uint4 v = lds128(sc + 512 + 4 * q);
                rank += ((v.x > mine) + (q + 1 < n && v.y > mine)) + ((q + 2 < n && v.z > mine) + (q + 3 < n && v.w > mine));
            }
            const uint32_t k32 = (mine >> 11) << 16, rb = (k32 ^ ((~(int)k32 >> 31) | 0x80000000u)) & 0xFFFF0000u;
            if (rank < 8 && pass) st_rlx(&p.s->sel[bid - NMAIN][rank], (2047 - (mine & 2047)) | (tag << 15) | (pack_bf(rcpf(1.f + ex2f(-1.4426950408889634f * __uint_as_float(rb))), 0.f) << 16));
        }
        }
    }

    if (warp == 13 || warp == 14) {
        const int i = tid - 416;
        if (i == 0) sts32(S + SM_EPOCH, tag);
        if (rowcta) {
            if (p.tn.t_marg <= 600) {
                const uint32_t back = ld_rlx(p.s->x + 2 * ((4 * hw + 2 + (g >> 2)) * 2048 + bid * 16 + (g & 3) * 4 + t));
                if (back == 0xFFFFFFFFu) __nanosleep(20);
            }
            spin_until(clk32(), p.tn.t_marg);
        } else {
            spin_until(t0, p.tn.t_svc);
        }
        const uint4* xa = (const uint4*)p.s->x + xd * 1024 + i;
        const int e = bid - NDOWN;
        const uint4* xe = (const uint4*)p.s->x + (128 + (e >> 2)) * 1024 + (i >> 1) * 8 + (e & 3) * 2 + (i & 1);
        const uint32_t da = S + SM_X0 + ((i >> 1) & 3) * X0_STRIDE + ((i & 1) ? X0_ODD : 0) + 128 + 16 * (i >> 3);
        const uint32_t de = S + SM_EX + ((i & 1) ? X0_ODD : 0) + 128 + 16 * (i >> 1);
        uint4 v[2][10];
        auto fetch = [&](int half) {
#pragma unroll
            for (int k = 0; k < 10; k++) {
                v[half][k].x = v[half][k].z = tag;
                if (k < 8 || big) v[half][k] = ld_rlx4(k < 8 ? xa + 512 * half + 64 * k : xe + 512 * half + 256 * (k - 8));
            }
        };
        fetch(0); fetch(1);
#pragma unroll
        for (int half = 0; half < 2; half++) {
#pragma unroll 1
            for (int it = 0; it < SPIN_LIMIT; it++) {
                uint32_t bad = 0;
#pragma unroll
                for (int k = 0; k < 10; k++) bad |= (v[half][k].x ^ tag) | (v[half][k].z ^ tag);
                if (!(bad & 1)) break;
                __nanosleep(60);
                fetch(half);
            }
#pragma unroll
            for (int k = 0; k < 10; k++)
                if (k < 8 || big) sts128(k < 8 ? da + 1024 * half + 128 * k : de + 1024 * half + 512 * (k - 8), v[half][k].x & ~1u, v[half][k].y, v[half][k].z & ~1u, v[half][k].w);
            __syncwarp();
            if (lane == 0) mbar_arrive(S + (B_X0 + half) * 8);
        }
    }

    if (warp < 12) {
        const bool cw = warp >= 8;
        if (has) {
            const uint32_t xb = S + (cw ? SM_EX : SM_X0 + slot * X0_STRIDE), kt = S + (cw ? EX_KT : SM_KT + slot * KT_STRIDE);
            const int g0 = cw ? warp - 8 : 0, g1 = cw ? warp - 7 : 4;
            const uint32_t park = (cw ? S + EX_HAND + g0 * 2048 : kt) + lane * 16;
            if (cw) mbar_wait(S + B_TAB1 * 8, 0);
            const uint4 ki = lds128(S + SM_KINF + slot * 16);
            const float inv = __uint_as_float(ki.x);
            if (warp >= 4) {
                const uint32_t fa = S + (cw ? EX_FAR : SM_FAR + slot * FAR_STRIDE);
                mbar_wait(S + (cw ? B_X1 : B_X0) * 8, 0);
                mbar_wait(S + B_KG * 8, 0);
#pragma unroll 1
                for (int rho = cw ? g0 : 0; rho < (cw ? 7 : 4); rho += cw ? 4 : 1) box_round(xb, fa, (!cw && rho == 3) ? 6 : rho, lane);
                if (cw) bar_sync(2, 128); else __syncwarp();
                const int dd = g - 2 * t, gf = g0 ? g0 : 1;
                const uint32_t tb0 = dd == -5 ? ki.z : (dd == -4 ? ki.z << 16 : 0u), tb1 = dd == 3 ? ki.z : (dd == 4 ? ki.z << 16 : 0u);
                uint32_t tad = xb + (mi == 1 ? 144 : mi == 2 ? 128 : X0_ODD + 128) + 16 * j + 512 * gf - 1024;
                uint32_t ad8 = fa + (mi == 0 ? FB9E : mi == 1 ? FB7O : mi == 2 ? FB9O + 16 : FB7E) + 112 - 16 * j + 512 * gf - 768;
                uint32_t ad4 = fa + ((mi & 1) ? FB3 : FB5) + 240 + 16 * (8 * (mi >> 1) - j) + 1024 * gf - 640;
                const uint32_t p4 = kt + KT_P4 + 16 * (g + t), p8 = kt + KT_P8 + 8 * (g + 2 * t);
#pragma unroll 1
                for (int grp = gf; grp < g1; grp++) {
                    float a[4][4], e[2][4], o[2][4];
#pragma unroll
                    for (int k = 0; k < 4; k++) a[0][k] = a[1][k] = a[2][k] = a[3][k] = e[0][k] = e[1][k] = o[0][k] = o[1][k] = 0.f;
                    {
                        if (!cw && grp == 2) {
                            mbar_wait(S + B_X1 * 8, 0);
#pragma unroll 1
                            for (int rho = 3; rho < 6; rho++) box_round(xb, fa, rho, lane);
                            __syncwarp();
                        }
                        {
                            uint4 A4[10];
#pragma unroll
                            for (int s = 0; s < 10; s++) A4[s] = lds128(p4 + 64 * s);
                            auto s4 = [&](int m) {
                                uint32_t b[4];
                                ldm4t(ad4 - 256 * m, b[0], b[1], b[2], b[3]);
#pragma unroll
                                for (int h = 1; h >= 0; h--)
#pragma unroll
                                    for (int i = 0; i < 4; i++) {
                                        const int s = 2 * m - 2 + 2 * i + (1 - h), k = m + (i & 2);
                                        if (k <= 5 && k >= ((i & 1) ? 0 : 1) && !((i & 1) && k == 5)) mma_h(a[i], A4[s >= 0 && s < 10 ? s : 0].x, A4[s >= 0 && s < 10 ? s : 0].y, A4[s >= 0 && s < 10 ? s : 0].z, A4[s >= 0 && s < 10 ? s : 0].w, b[2 * h], b[2 * h + 1]);
                                    }
                            };
                            auto tap = [&](int i) {
                                uint32_t b[4];
                                ldm4(tad + 128 * i, b[0], b[1], b[2], b[3]);
                                mma_h(a[i], b[0], b[1], b[2], b[3], tb1, tb0);
                            };
                            s4(1); s4(0); s4(2); s4(-1); tap(3); s4(-2);
                            if (grp >= 2) { s4(3); tap(0); s4(4); tap(1); s4(5); tap(2); }
                        }
                        {
                            uint32_t A8[9][4];
#pragma unroll
                            for (int k = 0; k < 9; k++) { A8[k][0] = lds32(p8 + 64 * k); A8[k][1] = lds32(p8 + 64 * k + 64); A8[k][2] = lds32(p8 + 64 * k + 4); A8[k][3] = lds32(p8 + 64 * k + 68); }
                            auto s8 = [&](int m) {
                                uint32_t b[4];
                                ldm4t(ad8 - 128 * m, b[0], b[1], b[2], b[3]);
                                mma_h(e[1], A8[m + 2][0], A8[m + 2][1], A8[m + 2][2], A8[m + 2][3], b[0], b[1]);
                                mma_h(o[1], A8[m + 2][0], A8[m + 2][1], A8[m + 2][2], A8[m + 2][3], b[2], b[3]);
                                if (m >= 0) {
                                    mma_h(e[0], A8[m >= 0 ? m : 0][0], A8[m >= 0 ? m : 0][1], A8[m >= 0 ? m : 0][2], A8[m >= 0 ? m : 0][3], b[0], b[1]);
                                    mma_h(o[0], A8[m >= 0 ? m : 0][0], A8[m >= 0 ? m : 0][1], A8[m >= 0 ? m : 0][2], A8[m >= 0 ? m : 0][3], b[2], b[3]);
                                }
                            };
                            s8(-2);
                            if (grp >= 2) {
                                s8(-1); s8(0); s8(1); s8(2);
                                if (grp >= 3) { s8(3); s8(4); s8(5); s8(6); }
                            }
                        }
                    }
                    tad += 512; ad8 += 512; ad4 += 1024;
#pragma unroll
                    for (int pp = 0; pp < 2; pp++) {
                        if (!cw) {
#pragma unroll 1
                            for (int it = 0; it < SPIN_LIMIT && !__all_sync(~0u, lds32v(park + (2 * pp + 1) * 512) == SLOT_FREE); it++) __nanosleep(32);
                        }
#pragma unroll
                        for (int i = 0; i < 2; i++)
                            sts128(park + (2 * pp + i) * 512, __float_as_uint((a[2 * pp + i][0] + e[pp][2 * i]) * inv), __float_as_uint((a[2 * pp + i][1] + e[pp][2 * i + 1]) * inv),
                                   __float_as_uint((a[2 * pp + i][2] + o[pp][2 * i]) * inv), __float_as_uint((a[2 * pp + i][3] + o[pp][2 * i + 1]) * inv));
                    }
                }
            }
            if ((warp & 12) != 4) {
                uint32_t R[66], x[5];
#pragma unroll
                for (int i = 0; i < 66; i++) R[i] = lds32(kt + 4 * (8 + g - 2 * t) + 32 * i);
                float w[5][4];
#pragma unroll
                for (int i = 0; i < 5; i++) w[i][0] = w[i][1] = w[i][2] = w[i][3] = 0.f;
                uint32_t xa = xb + ((lane & 8) ? X0_ODD + 16 : 16) + 16 * j + 512 * g0;
                uint2* yo = (uint2*)p.s->y + (32 * g0 + g) * 2304 + ch * 4 + t;
                mbar_wait(S + B_X0 * 8, 0);
                const uint32_t ytag = lds32(S + SM_EPOCH);
                if (g0 == 0) {
                    const uint32_t x01 = lds32(xb + 128);
                    const float c0 = lane == 31 ? __uint_as_float(ki.y) * inv * h_lo(x01) : 0.f, c1 = lane == 31 ? c0 + __uint_as_float(ki.y) * inv * h_hi(x01) : 0.f;
                    __syncwarp();
#pragma unroll
                    for (int i = 0; i < 4; i++) sts128(park + i * 512, 0u, 0u, i == 3 ? __float_as_uint(c0) : 0u, i == 3 ? __float_as_uint(c1) : 0u);
                }
                ldm2(xa - 16, x[1], x[0]);
                ldm2(xa, x[1], x[2]);
                ldm2(xa + 16, x[3], x[4]);
                uint32_t zz = z, pk = park;
                float sc = inv;
                const bool direct = g0 == 0;
                uint32_t dir = direct;
                asm volatile("" : "+r"(pk));
#pragma unroll 1
                for (int gq = g0; gq < g1; gq++) {
                    uint32_t pa = pk;
#pragma unroll 1
                    for (int n = 4; n > 0; n--) {
                        asm volatile("" : "+r"(zz), "+f"(sc), "+r"(pa), "+r"(dir));
                        sweep_steps<1, 5>(w, R, xa, x, zz);
                        uint4 v = lds128v(pa | (x[4] & zz));
                        sweep_steps<6, 8>(w, R, xa, x, zz);
                        xa += 128;
                        if (__any_sync(~0u, v.x == SLOT_FREE)) {
#pragma unroll 1
                            for (int it = 0; it < SPIN_LIMIT; it++) {
                                v = lds128v(pa);
                                if (!__any_sync(~0u, v.x == SLOT_FREE)) break;
                            }
                        }
                        const float y0 = fmaf(w[0][0], sc, __uint_as_float(v.x)), y1 = fmaf(w[0][1], sc, __uint_as_float(v.y));
                        const float y2 = fmaf(w[0][2], sc, __uint_as_float(v.z)), y3 = fmaf(w[0][3], sc, __uint_as_float(v.w));
                        if (dir) {
                            *yo = make_uint2((pack_bf(y0, y1) & ~1u) | ytag, pack_bf(y2, y3));
                            sts32(pa, SLOT_FREE);
                        } else {
                            sts128(pa, __float_as_uint(y0), __float_as_uint(y1), __float_as_uint(y2), __float_as_uint(y3));
                        }
                        yo += 18432;
                        pa += 512;
                    }
                    if (direct && lane == 0) red_add(&p.s->cnt[(8 + gq) * 32]);
                }
                __syncwarp();
                if (lane == 0) mbar_arrive(S + (direct ? B_EM : B_SP + g0) * 8);
                if (cw && g0 < 3) {
                    mbar_wait(S + (B_SP + g0 + 1) * 8, 0);
#pragma unroll
                    for (int i = 0; i < 4; i++) {
                        const uint4 v = lds128(park + 2048 + i * 512);
                        yo[i * 18432] = make_uint2((pack_bf(fmaf(w[i + 1][0], inv, __uint_as_float(v.x)), fmaf(w[i + 1][1], inv, __uint_as_float(v.y))) & ~1u) | ytag,
                                                   pack_bf(fmaf(w[i + 1][2], inv, __uint_as_float(v.z)), fmaf(w[i + 1][3], inv, __uint_as_float(v.w))));
                    }
                    if (lane == 0) red_add(&p.s->cnt[(8 + g0 + 1) * 32]);
                }
            }
        }
        if (rowcta && (warp & 12) == 4) {
            bar_sync(10, 128);
            const int i = tid - 128, rb0 = 16 * (bid >> 2), c0 = 144 * (bid & 3);
            if (i == 0) mbar_arrive(S + B_FD * 8);
#pragma unroll 3
            for (int v = i; v < 1152; v += 128) {
                const int row = (v * 3641) >> 16, vv = v - 18 * row;
                cp16(S + SM_ROWS + row * 304 + 16 * vv, (const uint4*)(p.u + (size_t)(512 * (row >> 4) + rb0 + (row & 15)) * D_ + c0) + vv);
            }
            if (i < 64) {
                const uint32_t sw = ld_stat(&p.s->stat[512 * (i >> 4) + rb0 + (i & 15)], lds32(S + SM_EPOCH));
                const float ri = rcpf(bf_hi(sw));
                const uint32_t hi = pack_bf(ri, ri);
                const float rl = ri - bf_lo(hi);
                sts128(S + SM_KT + KT_P4 + 16 * i, prmt(sw, sw, 0x1010), hi, pack_bf(rl, rl), 0u);
            }
            asm volatile("cp.async.wait_all;" ::: "memory");
            __syncwarp();
            if (lane == 0) mbar_arrive(S + B_OUT * 8);
        }
        if (!rowcta) return;

        const int rb0 = 16 * (bid >> 2), c0 = 144 * (bid & 3);
        mbar_wait(S + B_OUT * 8, 0);
        mbar_wait(S + B_XS * 8, 0);
        const uint32_t otag = lds32(S + SM_EPOCH) * 0x00010001u;
        const uint2 skip = lds64(S + SM_SKIP);
        const int pi_g = (g & 1) + 8 * ((g >> 1) & 1) + 2 * (g >> 2), pi_j = (j & 1) + 8 * ((j >> 1) & 1) + 2 * (j >> 2);
#pragma unroll 1
        for (int un = warp; un < 36; un += 12) {
            const int q = (un * 57) >> 9, cu = un - 9 * q;
            const uint32_t rw = S + SM_ROWS + 16 * q * 304 + 32 * cu;
            const uint32_t ad = rw + (pi_j + 4 * (mi & 1)) * 304 + 16 * (mi >> 1);
            const uint32_t dk0 = __ldg((const uint32_t*)p.dskip + (c0 >> 1) + 8 * cu + t), dk1 = __ldg((const uint32_t*)p.dskip + (c0 >> 1) + 8 * cu + 4 + t);
            const uint4 sa = lds128(S + SM_KT + KT_P4 + 16 * (16 * q + pi_g)), sb = lds128(S + SM_KT + KT_P4 + 16 * (16 * q + 4 + pi_g));
            uint32_t x[4], tt[4], gt[4], y[4];
            ldm4(ad, x[0], x[1], x[2], x[3]);
#pragma unroll
            for (int e = 0; e < 4; e++) {
                const uint4 s = (e & 1) ? sb : sa;
                const uint32_t xn = norm2(x[e], s.x, s.y, s.z);
                tt[e] = bmul(xn, e < 2 ? dk0 : dk1);
                gt[e] = pack_bf(silu_f(bf_lo(xn)), silu_f(bf_hi(xn)));
            }
            mbar_wait(S + (B_YIN + q) * 8, 0);
            const uint32_t yb = S + SM_STG + q * 4608 + 512 * cu;
#pragma unroll 1
            for (int it = 0; it < SPIN_LIMIT; it++) {
                ldm4t(yb + (8 * (mi >> 1) + j) * 32 + 16 * (mi & 1), y[0], y[1], y[2], y[3]);
                const uint32_t bad = ((y[0] ^ otag) | (y[1] ^ otag) | (y[2] ^ otag) | (y[3] ^ otag)) & 0x00010001u;
                if (!__any_sync(~0u, (g & 3) == 0 && bad)) break;
                const uint4 v = ld_rlx4((const uint4*)(p.s->y + (32 * q + (bid >> 2)) * 4608 + (bid & 3) * 1152 + 128 * cu) + lane);
                __syncwarp();
                sts128(yb + 16 * lane, v.x, v.y, v.z, v.w);
                __syncwarp();
            }
#pragma unroll
            for (int e = 0; e < 4; e++) y[e] = badd(x[e], bmul(badd(y[e], tt[e]), gt[e]));
            stm4(ad, y[0], y[1], y[2], y[3]);
            __syncwarp();
            const int row = lane >> 1;
            const uint4 o = lds128(rw + row * 304 + 16 * (lane & 1));
            if (!((((q & 2) ? skip.y : skip.x) >> (16 * (q & 1) + row)) & 1))
                *((uint4*)(p.out + (size_t)(512 * q + rb0 + row) * D_ + c0 + 16 * cu) + (lane & 1)) = o;
        }
        return;
    }

    {
        const int fw = warp - 13;
        if (fw < nsl) {
            st_rlx(&p.s->h[tag ^ 1][(32 * (sl0 + fw) + 16 * r) * 4 + lane], 0u);
            st_rlx(&p.s->h[tag ^ 1][(32 * (sl0 + fw) + 16 * r) * 4 + 32 + lane], 0u);
        }
        if (fw == 2) {
            spin_until(t0, p.tn.t_xs);
            uint32_t sv = 0;
#pragma unroll 1
            for (int it = 0; it < SPIN_LIMIT; it++) {
                sv = ld_rlx(&p.s->sel[bid & 3][j]);
                if (__all_sync(~0u, ((sv >> 15) & 1) == tag)) break;
                __nanosleep(40);
            }
            mbar_wait(S + B_KG * 8, 0);
            if (lane == 0) { fence_async(); mbar_expect(S + B_BOX * 8, 8 * 1152); }
            __syncwarp();
            if (lane < 8) bulk_g2s(S + SM_XS + lane * ROW_STRIDE, p.u + (size_t)(sv & 2047) * D_, 1152, S + B_BOX * 8);
            const uint32_t st = ld_stat(&p.s->stat[sv & 2047], tag);
            const float ri = rcpf(bf_hi(st));
            const uint32_t hi = pack_bf(ri, ri);
            const float rl = ri - bf_lo(hi);
            if (lane == 0) sts64(S + SM_SKIP, 0u, 0u);
            __syncwarp();
            if (lane < 8) {
                const int row = sv & 2047;
                if (((row >> 4) & 31) == (bid >> 2)) asm volatile("red.shared.or.b32 [%0], %1;" ::"r"(S + SM_SKIP + 4 * (row >> 10)), "r"(1u << (16 * ((row >> 9) & 1) + (row & 15))) : "memory");
                sts32(S + SM_XS + 8 * ROW_STRIDE + 4 * lane, sv);
                sts128(S + SM_RP + 16 * lane, prmt(st, st, 0x1010), hi, pack_bf(rl, rl), 0u);
            }
        }
        asm volatile("barrier.cluster.wait.aligned;" ::: "memory");
        bar_sync(9, 96);
        mbar_wait(S + B_BOX * 8, 0);
#pragma unroll
        for (int k = 0; k < 6; k++) {
            const int v = tid - 416 + 96 * k, tk = (v * 911) >> 16;
            const uint4 x = lds128(S + SM_XS + 16 * (v + tk)), st = lds128(S + SM_RP + 16 * tk);
            sts128(S + SM_XS + 16 * (v + tk), norm2(x.x, st.x, st.y, st.z), norm2(x.y, st.x, st.y, st.z), norm2(x.z, st.x, st.y, st.z), norm2(x.w, st.x, st.y, st.z));
        }
        bar_sync(9, 96);
        if (tid == 416) mbar_arrive(S + B_XS * 8);
        const uint32_t ob = mapa(S, r ^ 1);
        if (fw == 2) {
            if (elect()) {
#pragma unroll 1
                for (int st = 0; st < (down ? 24 : 6 * nsl); st++) {
                    if (st == 12 && down) break;
                    mbar_wait(S + (B_W + st) * 8, 0);
                    if (st % 3 == 2) mbar_arrive(S + (B_GU + st / 3) * 8);
                }
            }
            __syncwarp();
        }
        if (fw < 2) {
            const uint32_t bad = S + SM_XS + j * ROW_STRIDE + mi * 16;
            uint32_t aad = (SW + (8 * (mi >> 1) + j) * 64 + 16 * ((mi & 1) ^ (j >> 1))) ^ ((r ^ fw) * 32);
            uint32_t b[18][4];
#pragma unroll
            for (int k = 0; k < 18; k++) ldm4(bad + 64 * k, b[k][0], b[k][1], b[k][2], b[k][3]);
#pragma unroll 1
            for (int u = 0; u < nsl; u++) {
                float d[4][4];
#pragma unroll
                for (int i = 0; i < 4; i++) d[i][0] = d[i][1] = d[i][2] = d[i][3] = 0.f;
#pragma unroll
                for (int hf = 0; hf < 2; hf++) {
                    mbar_wait(S + (B_GU + 2 * u + hf) * 8, 0);
#pragma unroll
                    for (int sub = 0; sub < 3; sub++) {
                        uint32_t a[6][4];
#pragma unroll
                        for (int k = 0; k < 6; k++) ldm4t(aad + 1024 * k, a[k][0], a[k][1], a[k][2], a[k][3]);
#pragma unroll
                        for (int k = 0; k < 6; k++) {
                            const int kb = 9 * hf + 3 * sub + (k >> 1);
                            mma_bf(d[k & 3], a[k][0], a[k][1], a[k][2], a[k][3], b[kb][2 * (k & 1)], b[kb][2 * (k & 1) + 1]);
                        }
                        aad += STAGE;
                    }
                }
                const uint32_t k0 = pack_bf((d[0][0] + d[1][0]) + (d[2][0] + d[3][0]), (d[0][1] + d[1][1]) + (d[2][1] + d[3][1]));
                const uint32_t k1 = pack_bf((d[0][2] + d[1][2]) + (d[2][2] + d[3][2]), (d[0][3] + d[1][3]) + (d[2][3] + d[3][3]));
                if (fw == 1) {
                    asm volatile("st.async.shared::cluster.mbarrier::complete_tx::bytes.v2.b32 [%0], {%1, %2}, [%3];" ::"r"(ob + SM_PART + u * 256 + lane * 8), "r"(k0), "r"(k1), "r"(ob + (B_GX + u) * 8) : "memory");
                } else {
                    mbar_wait(S + (B_GX + u) * 8, 0);
                    const uint2 o = lds64(S + SM_PART + u * 256 + lane * 8);
#pragma unroll
                    for (int i = 0; i < 2; i++) {
                        const uint32_t mine = i ? k1 : k0, other = i ? o.y : o.x, gb = r ? other : mine, ub = r ? mine : other;
                        uint32_t hv = bmul(pack_bf(silu_f(bf_lo(gb)), silu_f(bf_hi(gb))), ub);
                        if ((hv & 0xFFFFu) == 0) hv |= 0x8000u;
                        if ((hv >> 16) == 0) hv |= 0x80000000u;
                        st_rlx(&p.s->h[tag][(32 * (sl0 + u) + 16 * r) * 4 + 32 * i + lane], hv);
                    }
                    __syncwarp();
                    if (lane < 8) red_add(&p.s->cnt[lane * 32]);
                }
            }
        }
        if (!down) return;

        const int fi = 32 * fw + lane, tok = 4 * r + ((fi >> 4) & 3), cc = 16 * pr + (fi & 15);
        const uint32_t sel = lds32(S + SM_XS + 8 * ROW_STRIDE + 4 * tok);
        const int row = sel & 2047;
        const uint32_t* ya = p.s->y + (row >> 4) * 4608 + cc * 8 + (row & 6);
        const float xraw = __bfloat162float(p.u[(size_t)row * D_ + cc]), dsk = __bfloat162float(p.dskip[cc]);
        const float xn = bf_lo(lds16(S + SM_XS + tok * ROW_STRIDE + 2 * cc));
        if (fw == 0) {
#pragma unroll 1
            for (int st = 12; st < 24; st++) mbar_wait(S + (B_W + st) * 8, 0);
        }
        if (fw == 2 && elect()) wait_count(&p.s->cnt[(bid & 7) * 32], epoch * 288u);
        bar_sync(9, 96);
        float dn[4][4];
        uint2 yv2 = make_uint2(tag ^ 1, 0u);
#pragma unroll 1
        for (int ph = 0; ph < 64; ph++) {
            if (fw == 2 && elect()) {
                fence_async();
                fence_async_g();
                mbar_expect(S + B_H * 8, 36864);
                bulk_g2s(SW, (const char*)p.s->h[tag] + r * 36864, 36864, S + B_H * 8);
            }
            asm volatile("ld.relaxed.gpu.global.v2.u32 {%0,%1}, [%2];" : "=r"(yv2.x), "=r"(yv2.y) : "l"(ya) : "memory");
            mbar_wait(S + B_H * 8, ph & 1);
#pragma unroll
            for (int i = 0; i < 4; i++) dn[i][0] = dn[i][1] = dn[i][2] = dn[i][3] = 0.f;
            uint32_t bq[4] = {~0u, ~0u, ~0u, ~0u};
            const int fr = j + 8 * (mi >> 1);
            uint32_t wa = SW + 12 * STAGE + fw * 2048 + fr * 32 + (((mi & 1) ^ ((fr >> 2) & 1)) << 4), ha = SW + fw * 1024 + lane * 16;
#pragma unroll 1
            for (int s0 = 0; s0 < 12; s0 += 3) {
                uint32_t a[6][8], b[6][4];
#pragma unroll
                for (int s = 0; s < 3; s++) {
                    if (s == 2 && s0 == 9) wa += S + SM_W_LAST - (SW + 23 * STAGE);
#pragma unroll
                    for (int e = 0; e < 2; e++) {
                        ldm4t(ha + e * 512, b[2 * s + e][0], b[2 * s + e][1], b[2 * s + e][2], b[2 * s + e][3]);
                        ldm4t(wa + e * 1024, a[2 * s + e][0], a[2 * s + e][1], a[2 * s + e][2], a[2 * s + e][3]);
                        ldm4t(wa + e * 1024 + 512, a[2 * s + e][4], a[2 * s + e][5], a[2 * s + e][6], a[2 * s + e][7]);
                    }
                    wa += STAGE; ha += 3072;
                }
#pragma unroll
                for (int k = 0; k < 6; k++) {
                    mma_bf(dn[2 * (k & 1)], a[k][0], a[k][1], a[k][2], a[k][3], b[k][0], b[k][1]);
                    mma_bf(dn[2 * (k & 1) + 1], a[k][4], a[k][5], a[k][6], a[k][7], b[k][2], b[k][3]);
#pragma unroll
                    for (int q = 0; q < 4; q++) bq[q] = __vminu2(bq[q], b[k][q]);
                }
            }
            const uint32_t bm = __vminu2(__vminu2(bq[0], bq[1]), __vminu2(bq[2], bq[3])), bd = (bm - 0x00010001u) & ~bm;
            uint32_t anybad;
            asm volatile("{.reg .pred p, q; setp.ne.u32 p, %1, 0; bar.red.or.pred q, 9, 96, p; selp.u32 %0, 1, 0, q;}" : "=r"(anybad) : "r"(bd & 0x80008000u) : "memory");
            if (!anybad) break;
        }
        float* red = (float*)(smem + SM_RED + fw * 512);
        red[(2 * t) * 16 + g] = (dn[0][0] + dn[1][0]) + (dn[2][0] + dn[3][0]);
        red[(2 * t + 1) * 16 + g] = (dn[0][1] + dn[1][1]) + (dn[2][1] + dn[3][1]);
        red[(2 * t) * 16 + g + 8] = (dn[0][2] + dn[1][2]) + (dn[2][2] + dn[3][2]);
        red[(2 * t + 1) * 16 + g + 8] = (dn[0][3] + dn[1][3]) + (dn[2][3] + dn[3][3]);
        bar_sync(9, 96);
        if (fw < 2) {
            const float* rs = (const float*)(smem + SM_RED);
            const int mine = 64 * r + fi, other = mine ^ 64;
            st_async32(ob + SM_RP + 4 * fi, __float_as_uint(rs[other] + rs[128 + other] + rs[256 + other]), ob + B_RED * 8);
            const float s = rs[mine] + rs[128 + mine] + rs[256 + mine];
#pragma unroll 1
            for (int it = 0; it < SPIN_LIMIT && (yv2.x & 1) != tag; it++)
                asm volatile("ld.relaxed.gpu.global.v2.u32 {%0,%1}, [%2];" : "=r"(yv2.x), "=r"(yv2.y) : "l"(ya) : "memory");
            const uint32_t yw = (row & 8) ? yv2.y : yv2.x;
            const float sg = bf_round(((row & 1) ? bf_hi(yw) : bf_lo(yw)) + bf_round(xn * dsk));
            mbar_wait(S + B_RED * 8, 0);
            const float o = *(const float*)(smem + SM_RP + 4 * fi);
            const float yv = bf_round(bf_round(r == 0 ? s + o : o + s) * bf_hi(sel));
            p.out[(size_t)row * D_ + cc] = __float2bfloat16(xraw + bf_round(sg * bf_round(silu_f(bf_round(xn + yv)))));
            if (bid == 0 && fi == 0) st_rlx(&p.s->cnt[16 * 32], epoch);
        }
    }
}

typedef CUresult (*EncodeFn)(CUtensorMap*, CUtensorMapDataType, cuuint32_t, void*, const cuuint64_t*, const cuuint64_t*, const cuuint32_t*,
                             const cuuint32_t*, CUtensorMapInterleave, CUtensorMapSwizzle, CUtensorMapL2promotion, CUtensorMapFloatOOBfill);

static void make2d(EncodeFn enc, CUtensorMap* m, const void* base, uint64_t cols, uint64_t rows, uint32_t bc, uint32_t br, CUtensorMapSwizzle sw) {
    cuuint64_t gd[2] = {cols, rows};
    cuuint64_t gs[1] = {cols * 2};
    cuuint32_t bd[2] = {bc, br}, es[2] = {1, 1};
    enc(m, CU_TENSOR_MAP_DATA_TYPE_BFLOAT16, 2, const_cast<void*>(base), gd, gs, bd, es, CU_TENSOR_MAP_INTERLEAVE_NONE, sw,
        CU_TENSOR_MAP_L2_PROMOTION_L2_128B, CU_TENSOR_MAP_FLOAT_OOB_FILL_NONE);
}

static Tune g_tune = {2000, 9000, 3, 5, 8, 5000, 7500, 0, 9000, 1, 0, 0};


static void launch(void* const* d_in, void* d_out) {
    static EncodeFn enc = nullptr;
    static Scratch* gs = nullptr;
    if (!enc) {
        void* fn = nullptr;
        cudaDriverEntryPointQueryResult qr;
        cudaGetDriverEntryPoint("cuTensorMapEncodeTiled", &fn, cudaEnableDefault, &qr);
        enc = (EncodeFn)fn;
        cudaFuncSetAttribute(fused_kernel, cudaFuncAttributeMaxDynamicSharedMemorySize, SM_TOTAL);
        cudaGetSymbolAddress((void**)&gs, g_s);
    }
    Hot p;
    Maps m;
    auto in = [&](int i) { return (const __nv_bfloat16*)d_in[i]; };
    p.u = in(0); p.are = in(1); p.aim = in(2); p.bre = in(3); p.bim = in(4); p.cre = in(5); p.cim = in(6);
    p.logdt = in(7); p.dskip = in(8); p.wr = in(10); p.pwg = in(11); p.pwu = in(12); p.pwd = in(13);
    p.out = (__nv_bfloat16*)d_out;
    p.tn = g_tune;
    p.s = gs;
    make2d(enc, &m.wg, p.pwg, F_, D_, 32, 96, CU_TENSOR_MAP_SWIZZLE_64B);
    make2d(enc, &m.wu, p.pwu, F_, D_, 32, 96, CU_TENSOR_MAP_SWIZZLE_64B);
    make2d(enc, &m.wd, p.pwd, D_, F_, 16, 192, CU_TENSOR_MAP_SWIZZLE_32B);
    fused_kernel<<<NCTA, NTHREADS, SM_TOTAL>>>(p, m);
}

}

extern "C" void kernel_launch(void* const* d_in, const int* in_sizes, int n_in, void* d_out, int out_size) {
    static int clusters = -1;
    if (clusters < 0) clusters = v3::max_clusters();
    if (clusters < 15 || !v3::launch(d_in, d_out)) v2::launch(d_in, d_out);
}
```

```cpp
#include <cuda_runtime.h>
#include <cuda_bf16.h>
#include <cuda_fp16.h>
#include <cuda.h>
#include <stdint.h>
#include <stddef.h>
#include <type_traits>


namespace v3 {

template <int N> using Int = std::integral_constant<int, N>;

constexpr int D_ = 576, F_ = 4608;
constexpr int NCTA = 120, NTHREADS = 512;
constexpr int SPIN_LIMIT = 1 << 16;

enum { B_Y = 0, B_X = 8, B_TOP = 10, B_XS = 12, B_UP = 13, B_RAW = 15, B_FULL = 16, B_FIN = 43, B_SEL = 44, B_EMPTY = 38  , B_ROWS = 66, B_WR = 67 };
constexpr int SM_SKIP = 544, SM_SEL = 576;
constexpr int SM_ST = 640;
constexpr int SM_RAW = 2688, PITCH = 80;
constexpr int SM_CH = SM_RAW + 256 * PITCH, CH = 18304;
constexpr int TAB = 0, FT = 3072, XX = 3712, BOX = 8064, YIN = 14208;
constexpr int SM_B = SM_CH + 5 * CH, BP = 1168;
constexpr int SM_CAND = SM_B + 8 * BP, SM_PROG = SM_CAND + 256, SM_DUMP = SM_PROG + 128;
constexpr int NRING = 12, SM_W = SM_B + 10240, SM_FIN = SM_W + NRING * 8192, SM_TOTAL = 232448;
static_assert(SM_W % 1024 == 0 && SM_FIN + 8192 <= SM_TOTAL && SM_TOTAL - 18432 >= SM_W + 10 * 8192, "smem");

struct Tune { int t_tile, stag, late, win5, win4, t_rows, da, t_pf, zero; };

struct Scratch {
    uint32_t h[8 * 2304];
    uint2 stat[2048];
    uint32_t ep[NCTA * 8];
};
__device__ __align__(1024) Scratch g_s;

struct Hot {
    const __nv_bfloat16* u;
    int bre, bim, cre, cim, are, aim, logdt, dskip, wr, ep;
    Scratch* s;
    __nv_bfloat16* out;
    const __nv_bfloat16* wg;
    Tune tn;
};
struct Maps { CUtensorMap w[3], u; };

__device__ __forceinline__ uint32_t smem_u32(const void* p) { return (uint32_t)__cvta_generic_to_shared(p); }
__device__ __forceinline__ void mbar_init(uint32_t b, int c) { asm volatile("mbarrier.init.shared::cta.b64 [%0], %1;" ::"r"(b), "r"(c) : "memory"); }
__device__ __forceinline__ void mbar_expect(uint32_t b, int bytes) { asm volatile("mbarrier.arrive.expect_tx.shared::cta.b64 _, [%0], %1;" ::"r"(b), "r"(bytes) : "memory"); }
__device__ __forceinline__ void mbar_arrive(uint32_t b) { asm volatile("mbarrier.arrive.shared::cta.b64 _, [%0];" ::"r"(b) : "memory"); }
__device__ __forceinline__ bool elect() { uint32_t d; asm volatile("{.reg .pred p; elect.sync _|p, 0xffffffff; selp.u32 %0,1,0,p;}" : "=r"(d)); return d; }
__device__ __forceinline__ void mbar_wait(uint32_t b, int par) {
    asm volatile("{\n.reg .pred p;\nLW:\nmbarrier.try_wait.parity.shared::cta.b64 p, [%0], %1, 2000;\n@!p bra LW;\n}" ::"r"(b), "r"(par) : "memory");
}
__device__ __forceinline__ void mbar_wait_short(uint32_t b) {
    asm volatile("{\n.reg .pred p;\nLW:\nmbarrier.try_wait.parity.shared::cta.b64 p, [%0], 0;\n@!p bra LW;\n}" ::"r"(b) : "memory");
}
__device__ __forceinline__ uint32_t mapa(uint32_t a, uint32_t rank) { uint32_t d; asm("mapa.shared::cluster.u32 %0, %1, %2;" : "=r"(d) : "r"(a), "r"(rank)); return d; }
__device__ __forceinline__ void tma2d(uint32_t dst, const CUtensorMap* m, int c0, int c1, uint32_t bar) {
    asm volatile("cp.async.bulk.tensor.2d.shared::cluster.global.mbarrier::complete_tx::bytes [%0], [%1, {%3, %4}], [%2];" ::"r"(dst), "l"(m), "r"(bar), "r"(c0), "r"(c1) : "memory");
}
__device__ __forceinline__ void bulk_g2s(uint32_t dst, const void* src, int bytes, uint32_t bar) {
    asm volatile("cp.async.bulk.shared::cluster.global.mbarrier::complete_tx::bytes [%0], [%1], %2, [%3];" ::"r"(dst), "l"(src), "r"(bytes), "r"(bar) : "memory");
}
__device__ __forceinline__ void bulk_mc(uint32_t dst, const void* src, int bytes, uint32_t bar) {
    asm volatile("cp.async.bulk.shared::cluster.global.mbarrier::complete_tx::bytes.multicast::cluster [%0], [%1], %2, [%3], %4;"
                 ::"r"(dst), "l"(src), "r"(bytes), "r"(bar), "h"((uint16_t)255) : "memory");
}
__device__ __forceinline__ void bar_sync(int id, int n) { asm volatile("bar.sync %0, %1;" ::"r"(id), "r"(n) : "memory"); }
__device__ __forceinline__ void bar_arrive(int id, int n) { asm volatile("bar.arrive %0, %1;" ::"r"(id), "r"(n) : "memory"); }
__device__ __forceinline__ uint4 ld_rlx4(const void* p) { uint4 v; asm volatile("ld.relaxed.gpu.global.v4.u32 {%0,%1,%2,%3}, [%4];" : "=r"(v.x), "=r"(v.y), "=r"(v.z), "=r"(v.w) : "l"(p) : "memory"); return v; }
__device__ __forceinline__ uint2 ld_rlx2(const void* p) { uint2 v; asm volatile("ld.relaxed.gpu.global.v2.u32 {%0,%1}, [%2];" : "=r"(v.x), "=r"(v.y) : "l"(p) : "memory"); return v; }
__device__ __forceinline__ uint32_t ld_rlx(const void* p) { uint32_t v; asm volatile("ld.relaxed.gpu.global.u32 %0, [%1];" : "=r"(v) : "l"(p) : "memory"); return v; }
__device__ __forceinline__ void st_rlx(void* p, uint32_t v) { asm volatile("st.relaxed.gpu.global.u32 [%0], %1;" ::"l"(p), "r"(v) : "memory"); }
__device__ __forceinline__ void st_rlx2(void* p, uint32_t x, uint32_t y) { asm volatile("st.relaxed.gpu.global.v2.u32 [%0], {%1,%2};" ::"l"(p), "r"(x), "r"(y) : "memory"); }
__device__ __forceinline__ uint4 ldg4(const void* p) { uint4 v; asm volatile("ld.global.nc.v4.u32 {%0,%1,%2,%3}, [%4];" : "=r"(v.x), "=r"(v.y), "=r"(v.z), "=r"(v.w) : "l"(p)); return v; }
__device__ __forceinline__ uint32_t ldg1(const void* p) { uint32_t v; asm volatile("ld.global.nc.u32 %0, [%1];" : "=r"(v) : "l"(p)); return v; }
__device__ __forceinline__ uint32_t ldg16(const void* p) { uint16_t v; asm volatile("ld.global.nc.u16 %0, [%1];" : "=h"(v) : "l"(p)); return v; }
__device__ __forceinline__ const void* at256(const void* b, int o) { const void* r; asm("mad.wide.s32 %0, %1, 256, %2;" : "=l"(r) : "r"(o), "l"(b)); return r; }
__device__ __forceinline__ int laneid() { int v; asm volatile("mov.u32 %0, %%laneid;" : "=r"(v)); return v; }
__device__ __forceinline__ uint32_t keep(uint32_t v) { return __shfl_xor_sync(~0u, v, 0); }
__device__ __forceinline__ int ctaid() { int v; asm volatile("mov.u32 %0, %%ctaid.x;" : "=r"(v)); return v; }
__device__ __forceinline__ uint32_t lds32(uint32_t a) { uint32_t v; asm volatile("ld.shared.u32 %0, [%1];" : "=r"(v) : "r"(a) : "memory"); return v; }
__device__ __forceinline__ uint32_t lds32v(uint32_t a) { uint32_t v; asm volatile("ld.volatile.shared.u32 %0, [%1];" : "=r"(v) : "r"(a) : "memory"); return v; }
__device__ __forceinline__ uint32_t lds16(uint32_t a) { uint16_t v; asm volatile("ld.shared.u16 %0, [%1];" : "=h"(v) : "r"(a) : "memory"); return v; }
__device__ __forceinline__ uint2 lds64(uint32_t a) { uint2 v; asm volatile("ld.shared.v2.u32 {%0,%1}, [%2];" : "=r"(v.x), "=r"(v.y) : "r"(a) : "memory"); return v; }
__device__ __forceinline__ uint4 lds128(uint32_t a) { uint4 v; asm volatile("ld.shared.v4.u32 {%0,%1,%2,%3}, [%4];" : "=r"(v.x), "=r"(v.y), "=r"(v.z), "=r"(v.w) : "r"(a) : "memory"); return v; }
__device__ __forceinline__ void sts16(uint32_t a, uint32_t v) { asm volatile("st.shared.u16 [%0], %1;" ::"r"(a), "h"((uint16_t)v) : "memory"); }
__device__ __forceinline__ void sts32(uint32_t a, uint32_t v) { asm volatile("st.shared.u32 [%0], %1;" ::"r"(a), "r"(v) : "memory"); }
__device__ __forceinline__ void sts32v(uint32_t a, uint32_t v) { asm volatile("st.volatile.shared.u32 [%0], %1;" ::"r"(a), "r"(v) : "memory"); }
__device__ __forceinline__ void sts64(uint32_t a, uint32_t x, uint32_t y) { asm volatile("st.shared.v2.u32 [%0], {%1,%2};" ::"r"(a), "r"(x), "r"(y) : "memory"); }
__device__ __forceinline__ void sts128(uint32_t a, uint32_t x, uint32_t y, uint32_t z, uint32_t w) { asm volatile("st.shared.v4.u32 [%0], {%1,%2,%3,%4};" ::"r"(a), "r"(x), "r"(y), "r"(z), "r"(w) : "memory"); }
__device__ __forceinline__ void sts128v(uint32_t a, uint32_t x, uint32_t y, uint32_t z, uint32_t w) { asm volatile("st.volatile.shared.v4.u32 [%0], {%1,%2,%3,%4};" ::"r"(a), "r"(x), "r"(y), "r"(z), "r"(w) : "memory"); }
__device__ __forceinline__ void sts128f(uint32_t a, float x, float y, float z, float w) { asm volatile("st.shared.v4.f32 [%0], {%1,%2,%3,%4};" ::"r"(a), "f"(x), "f"(y), "f"(z), "f"(w) : "memory"); }
__device__ __forceinline__ void st_async4(uint32_t a, uint32_t x, uint32_t y, uint32_t z, uint32_t w, uint32_t bar) {
    asm volatile("st.async.shared::cluster.mbarrier::complete_tx::bytes.v4.b32 [%0], {%1,%2,%3,%4}, [%5];" ::"r"(a), "r"(x), "r"(y), "r"(z), "r"(w), "r"(bar) : "memory");
}
__device__ __forceinline__ void st_async2(uint32_t a, uint32_t x, uint32_t y, uint32_t bar) {
    asm volatile("st.async.shared::cluster.mbarrier::complete_tx::bytes.v2.b32 [%0], {%1,%2}, [%3];" ::"r"(a), "r"(x), "r"(y), "r"(bar) : "memory");
}
__device__ __forceinline__ void st_async2f(uint32_t a, float x, float y, uint32_t bar) {
    asm volatile("st.async.shared::cluster.mbarrier::complete_tx::bytes.v2.f32 [%0], {%1,%2}, [%3];" ::"r"(a), "f"(x), "f"(y), "r"(bar) : "memory");
}
__device__ __forceinline__ void ldm4(uint32_t a, uint32_t& r0, uint32_t& r1, uint32_t& r2, uint32_t& r3) {
    asm volatile("ldmatrix.sync.aligned.m8n8.x4.shared.b16 {%0,%1,%2,%3}, [%4];" : "=r"(r0), "=r"(r1), "=r"(r2), "=r"(r3) : "r"(a) : "memory");
}
__device__ __forceinline__ void ldm4t(uint32_t a, uint32_t (&r)[4]) {
    asm volatile("ldmatrix.sync.aligned.m8n8.x4.trans.shared.b16 {%0,%1,%2,%3}, [%4];" : "=r"(r[0]), "=r"(r[1]), "=r"(r[2]), "=r"(r[3]) : "r"(a) : "memory");
}
__device__ __forceinline__ void ldm2(uint32_t a, uint32_t& r0, uint32_t& r1) {
    asm volatile("ldmatrix.sync.aligned.m8n8.x2.shared.b16 {%0,%1}, [%2];" : "=r"(r0), "=r"(r1) : "r"(a) : "memory");
}
__device__ __forceinline__ void ldm2t(uint32_t a, uint32_t& r0, uint32_t& r1) {
    asm volatile("ldmatrix.sync.aligned.m8n8.x2.trans.shared.b16 {%0,%1}, [%2];" : "=r"(r0), "=r"(r1) : "r"(a) : "memory");
}
__device__ __forceinline__ void stm4(uint32_t a, uint32_t r0, uint32_t r1, uint32_t r2, uint32_t r3) {
    asm volatile("stmatrix.sync.aligned.m8n8.x4.shared.b16 [%0], {%1,%2,%3,%4};" ::"r"(a), "r"(r0), "r"(r1), "r"(r2), "r"(r3) : "memory");
}
__device__ __forceinline__ void stm4t(uint32_t a, uint32_t r0, uint32_t r1, uint32_t r2, uint32_t r3) {
    asm volatile("stmatrix.sync.aligned.m8n8.x4.trans.shared.b16 [%0], {%1,%2,%3,%4};" ::"r"(a), "r"(r0), "r"(r1), "r"(r2), "r"(r3) : "memory");
}
__device__ __forceinline__ void stm2t(uint32_t a, uint32_t r0, uint32_t r1) {
    asm volatile("stmatrix.sync.aligned.m8n8.x2.trans.shared.b16 [%0], {%1,%2};" ::"r"(a), "r"(r0), "r"(r1) : "memory");
}
__device__ __forceinline__ uint32_t movm(uint32_t a) { uint32_t d; asm volatile("movmatrix.sync.aligned.m8n8.trans.b16 %0, %1;" : "=r"(d) : "r"(a)); return d; }
__device__ __forceinline__ void mma_bf(float (&c)[4], uint32_t a0, uint32_t a1, uint32_t a2, uint32_t a3, uint32_t b0, uint32_t b1) {
    asm volatile("mma.sync.aligned.m16n8k16.row.col.f32.bf16.bf16.f32 {%0,%1,%2,%3},{%4,%5,%6,%7},{%8,%9},{%0,%1,%2,%3};"
                 : "+f"(c[0]), "+f"(c[1]), "+f"(c[2]), "+f"(c[3]) : "r"(a0), "r"(a1), "r"(a2), "r"(a3), "r"(b0), "r"(b1));
}
__device__ __forceinline__ void mma_bf8(float (&c)[4], uint32_t a0, uint32_t a1, uint32_t b0) {
    asm volatile("mma.sync.aligned.m16n8k8.row.col.f32.bf16.bf16.f32 {%0,%1,%2,%3},{%4,%5},{%6},{%0,%1,%2,%3};"
                 : "+f"(c[0]), "+f"(c[1]), "+f"(c[2]), "+f"(c[3]) : "r"(a0), "r"(a1), "r"(b0));
}
__device__ __forceinline__ void mma_h(float (&c)[4], uint32_t a0, uint32_t a1, uint32_t a2, uint32_t a3, uint32_t b0, uint32_t b1) {
    asm volatile("mma.sync.aligned.m16n8k16.row.col.f32.f16.f16.f32 {%0,%1,%2,%3},{%4,%5,%6,%7},{%8,%9},{%0,%1,%2,%3};"
                 : "+f"(c[0]), "+f"(c[1]), "+f"(c[2]), "+f"(c[3]) : "r"(a0), "r"(a1), "r"(a2), "r"(a3), "r"(b0), "r"(b1));
}
__device__ __forceinline__ void mma_h8(float (&c)[4], uint32_t a0, uint32_t a1, uint32_t b0) {
    asm volatile("mma.sync.aligned.m16n8k8.row.col.f32.f16.f16.f32 {%0,%1,%2,%3},{%4,%5},{%6},{%0,%1,%2,%3};"
                 : "+f"(c[0]), "+f"(c[1]), "+f"(c[2]), "+f"(c[3]) : "r"(a0), "r"(a1), "r"(b0));
}
template <int LIM>
__device__ __forceinline__ void mma_hp(int n, float (&d)[4], const float (&c)[4], uint32_t a0, uint32_t a1, uint32_t a2, uint32_t a3, uint32_t b0, uint32_t b1) {
    asm volatile("{.reg .pred p; setp.gt.s32 p, %14, %15;\n"
                 "@p mma.sync.aligned.m16n8k16.row.col.f32.f16.f16.f32 {%0,%1,%2,%3},{%4,%5,%6,%7},{%8,%9},{%10,%11,%12,%13};}"
                 : "+f"(d[0]), "+f"(d[1]), "+f"(d[2]), "+f"(d[3])
                 : "r"(a0), "r"(a1), "r"(a2), "r"(a3), "r"(b0), "r"(b1), "f"(c[0]), "f"(c[1]), "f"(c[2]), "f"(c[3]), "r"(n), "n"(LIM));
}
template <int LIM>
__device__ __forceinline__ void mma_hq(int n, float (&d)[4], uint32_t a0, uint32_t a1, uint32_t a2, uint32_t a3, uint32_t b0, uint32_t b1) {
    asm volatile("{.reg .pred p; setp.gt.s32 p, %10, %11;\n"
                 "@p mma.sync.aligned.m16n8k16.row.col.f32.f16.f16.f32 {%0,%1,%2,%3},{%4,%5,%6,%7},{%8,%9},{%0,%1,%2,%3};}"
                 : "+f"(d[0]), "+f"(d[1]), "+f"(d[2]), "+f"(d[3]) : "r"(a0), "r"(a1), "r"(a2), "r"(a3), "r"(b0), "r"(b1), "r"(n), "n"(LIM));
}
__device__ __forceinline__ void mma_hc(float (&d)[4], const float (&c)[4], uint32_t a0, uint32_t a1, uint32_t a2, uint32_t a3, uint32_t b0, uint32_t b1) {
    asm volatile("mma.sync.aligned.m16n8k16.row.col.f32.f16.f16.f32 {%0,%1,%2,%3},{%4,%5,%6,%7},{%8,%9},{%10,%11,%12,%13};"
                 : "=f"(d[0]), "=f"(d[1]), "=f"(d[2]), "=f"(d[3]) : "r"(a0), "r"(a1), "r"(a2), "r"(a3), "r"(b0), "r"(b1), "f"(c[0]), "f"(c[1]), "f"(c[2]), "f"(c[3]));
}
__device__ __forceinline__ uint32_t pack_bf(float lo, float hi) { uint32_t r; asm("cvt.rn.bf16x2.f32 %0, %1, %2;" : "=r"(r) : "f"(hi), "f"(lo)); return r; }
__device__ __forceinline__ uint32_t pack_h(float lo, float hi) { uint32_t r; asm("cvt.rn.f16x2.f32 %0, %1, %2;" : "=r"(r) : "f"(hi), "f"(lo)); return r; }
__device__ __forceinline__ float bf_lo(uint32_t w) { return __uint_as_float(w << 16); }
__device__ __forceinline__ float bf_hi(uint32_t w) { return __uint_as_float(w & 0xFFFF0000u); }
__device__ __forceinline__ float bf_round(float x) { return __uint_as_float(pack_bf(0.f, x)); }
__device__ __forceinline__ uint32_t badd(uint32_t a, uint32_t b) { uint32_t r; asm("add.rn.bf16x2 %0, %1, %2;" : "=r"(r) : "r"(a), "r"(b)); return r; }
__device__ __forceinline__ uint32_t bsub(uint32_t a, uint32_t b) { uint32_t r; asm("sub.rn.bf16x2 %0, %1, %2;" : "=r"(r) : "r"(a), "r"(b)); return r; }
__device__ __forceinline__ uint32_t bmul(uint32_t a, uint32_t b) { uint32_t r; asm("mul.rn.bf16x2 %0, %1, %2;" : "=r"(r) : "r"(a), "r"(b)); return r; }
__device__ __forceinline__ uint32_t bfma(uint32_t a, uint32_t b, uint32_t c) { uint32_t r; asm("fma.rn.bf16x2 %0, %1, %2, %3;" : "=r"(r) : "r"(a), "r"(b), "r"(c)); return r; }
__device__ __forceinline__ uint32_t hadd(uint32_t a, uint32_t b) { uint32_t r; asm("add.rn.f16x2 %0, %1, %2;" : "=r"(r) : "r"(a), "r"(b)); return r; }
__device__ __forceinline__ uint32_t prmt(uint32_t a, uint32_t b, uint32_t s) { uint32_t r; asm("prmt.b32 %0, %1, %2, %3;" : "=r"(r) : "r"(a), "r"(b), "r"(s)); return r; }
__device__ __forceinline__ uint32_t lop_ne(uint32_t a, uint32_t b, uint32_t c) { uint32_t r; asm("lop3.b32 %0, %1, %2, %3, 0x7E;" : "=r"(r) : "r"(a), "r"(b), "r"(c)); return r; }
__device__ __forceinline__ float ex2f(float x) { float r; asm("ex2.approx.ftz.f32 %0, %1;" : "=f"(r) : "f"(x)); return r; }
__device__ __forceinline__ float rcpf(float x) { float r; asm("rcp.approx.ftz.f32 %0, %1;" : "=f"(r) : "f"(x)); return r; }
__device__ __forceinline__ float sqrt_ap(float x) { float r; asm("sqrt.approx.ftz.f32 %0, %1;" : "=f"(r) : "f"(x)); return r; }
__device__ __forceinline__ float tanh_ap(float x) { float r; asm("tanh.approx.f32 %0, %1;" : "=f"(r) : "f"(x)); return r; }
__device__ __forceinline__ float sigm(float x) { return rcpf(1.f + ex2f(-1.4426950408889634f * x)); }
__device__ __forceinline__ float silu_half(float h) { return fmaf(h, tanh_ap(h), h); }
__device__ __forceinline__ uint32_t clk32() { uint32_t c; asm volatile("mov.u32 %0, %%clock;" : "=r"(c)); return c; }
__device__ __forceinline__ void spin_until(uint32_t t0, int dt) {
#pragma unroll 1
    while ((int)(clk32() - t0) < dt) __nanosleep(32);
}
__device__ __forceinline__ void cp16(uint32_t dst, const void* src) { asm volatile("cp.async.cg.shared.global [%0], [%1], 16;" ::"r"(dst), "l"(src) : "memory"); }

__device__ __forceinline__ uint32_t xslot(int s, int h) { return XX + 32 * (s & ~1) + 16 * ((2 * h + (s & 1)) ^ ((s >> 1) & 2)); }

struct cf { float x, y; };
__device__ __forceinline__ cf cmul(cf a, cf b) { return {a.x * b.x - a.y * b.y, a.x * b.y + a.y * b.x}; }
__device__ __forceinline__ cf csq(cf a) { return {a.x * a.x - a.y * a.y, (a.x + a.x) * a.y}; }
__device__ __forceinline__ cf cpow_direct(float zr2, float zi, float l) {
    const float mag = ex2f(zr2 * l), th = zi * l;
    return {mag * __cosf(th), mag * __sinf(th)};
}
struct hp { uint32_t re, im; };
struct hm { __half2 v; };
__device__ __forceinline__ __half2 as_h2(uint32_t v) { return *reinterpret_cast<__half2*>(&v); }
__device__ __forceinline__ uint32_t as_u32(__half2 v) { return *reinterpret_cast<uint32_t*>(&v); }
__device__ __forceinline__ hp mk2(cf a, cf b) { return {pack_h(a.x, b.x), pack_h(a.y, b.y)}; }
__device__ __forceinline__ hm mk1(cf a) { return {as_h2(pack_h(a.x, a.y))}; }
__device__ __forceinline__ hp his(hp a, hp b) { return {prmt(a.re, b.re, 0x7632), prmt(a.im, b.im, 0x7632)}; }
__device__ __forceinline__ hp operator*(hp a, hm b) {
    const __half2 c = __low2half2(b.v), s = __high2half2(b.v), x = as_h2(a.re), y = as_h2(a.im);
    return {as_u32(__hfma2(x, c, __hneg2(__hmul2_rn(y, s)))), as_u32(__hfma2(x, s, __hmul2_rn(y, c)))};
}
__device__ __forceinline__ hp operator*(hp a, hp b) {
    const __half2 c = as_h2(b.re), s = as_h2(b.im), x = as_h2(a.re), y = as_h2(a.im);
    return {as_u32(__hfma2(x, c, __hneg2(__hmul2_rn(y, s)))), as_u32(__hfma2(x, s, __hmul2_rn(y, c)))};
}
struct KParams { uint32_t are, aim, bre, bim, cre, cim, ldt, dsk, sa, la, lb, sb, sm, lm, l3, l4; };

__device__ __forceinline__ void kgen_addr(KParams& kp, uint32_t scr, int lane) {
    const int g = lane >> 2, t = lane & 3, mi = lane >> 3, j = lane & 7;
    kp.sa = keep(scr + 16 * lane);
    kp.sb = keep(scr + 128 * t + 16 * (g ^ (2 * t)));
    kp.la = keep(scr + 512 * (mi & 1) + 128 * (mi >> 1) + 16 * (j ^ (mi & 2)));
    kp.lb = keep((kp.la ^ 64) + 256);
    kp.sm = keep(scr + 2048 + 144 * mi + 16 * j);
    kp.lm = keep(scr + 2048 + 16 * mi);
    kp.l3 = keep(kp.lm + 144 * (j & 1));
    kp.l4 = keep(kp.lm + 288 - 72 * (j & 2));
}

__device__ __forceinline__ uint32_t kgen(KParams kp, uint32_t scr, uint32_t oth, int bar, int lane, float (&d)[5][4], float& k0, int nc, uint32_t pause, uint32_t zero) {
    const float dt = bf_round(ex2f(bf_lo(kp.ldt) * 1.4426950408889634f));
    cf w = cmul({bf_lo(kp.cre), bf_lo(kp.cim)}, {dt * bf_lo(kp.bre), dt * bf_lo(kp.bim)});
    cf w1 = cmul({bf_hi(kp.cre), bf_hi(kp.cim)}, {dt * bf_hi(kp.bre), dt * bf_hi(kp.bim)});
    const float dk = bf_lo(kp.dsk), dt2 = dt * 1.4426950408889634f;
    uint32_t z = prmt(kp.are, kp.aim, 0x5410), z1 = prmt(kp.are, kp.aim, 0x7632);
    uint32_t eb = __reduce_max_sync(~0u, __float_as_uint(fmaxf(fmaxf(fmaxf(fabsf(w.x), fabsf(w.y)), fmaxf(fabsf(w1.x), fabsf(w1.y))), fabsf(dk) * 0x1p-20f)));
    k0 = w.x + w1.x;
    const uint32_t sa = kp.sa, la = kp.la, lb = kp.lb;
    sts128(oth + 2048 + 16 * lane, __float_as_uint(w1.x), __float_as_uint(w1.y), z1, __float_as_uint(k0));
    sts32(oth + 2560, eb);
    bar_sync(bar, 64);
    const uint4 ov = lds128(sa + 2048);
    eb = min(max(max(eb, lds32(scr + 2560)) & 0x7F800000u, 0x00800000u), 0x7A000000u);
    const float sc = __uint_as_float(0x7B000000u - eb);
    k0 = fmaf(dk, sc, 0x1p-28f * __reduce_add_sync(~0u, __float2int_rn((k0 + __uint_as_float(ov.w)) * sc * 0x1p28f)));
#pragma unroll
    for (int i = 0; i < 5; i++) d[i][0] = d[i][1] = d[i][2] = d[i][3] = 0.f;
    const uint32_t sb = kp.sb, sm = kp.sm, lm = kp.lm, l3 = kp.l3, l4 = kp.l4;
    auto st = [&](int grp, hp a, hp b, hp c, hp e) { sts128v(sb + 1024 * grp, a.re, b.re, c.re, e.re); sts128v(sb + 1024 * grp + 512, a.im, b.im, c.im, e.im); };
#pragma unroll 1
    do {
        const float zr2 = dt2 * bf_lo(z), zi = dt * bf_hi(z);
        const cf ws = {w.x * sc, w.y * sc};
        z = z1; w = w1;
        z1 = ov.z; w1 = {__uint_as_float(ov.x), __uint_as_float(ov.y)};
        const cf a1 = cpow_direct(zr2, zi, 1.f), a256 = cpow_direct(zr2, zi, 256.f), b1 = cpow_direct(-zr2, zi, -16.f);
        const cf b2 = csq(b1), b4 = csq(b2), a2 = csq(a1), a4 = csq(a2), a512 = csq(a256), a514 = cmul(a512, a2), c1 = cmul(ws, a1);
        const hm n4 = mk1(b4), m8 = mk1(csq(a4));
        const hp u0 = mk2({1.f, 0.f}, b1), u1 = u0 * mk1(b2), v0 = mk2(c1, cmul(c1, a2)), v1 = v0 * mk1(a4);
        __syncwarp();
        stm4t(sm, as_u32(mk1(cmul(a514, a256)).v), as_u32(mk1(a512).v), as_u32(mk1(csq(a514)).v), as_u32(mk1(a256).v));
        stm2t(sm + 576, as_u32(mk1(csq(b4)).v), as_u32(mk1(a1).v));
        st(0, u0, u1, u0 * n4, u1 * n4);
        st(1, v0, v1, v0 * m8, v1 * m8);
        __syncwarp();
#pragma unroll
        for (int h = 0; h < 2; h++) {
            if (h && pause) { mbar_wait(pause, 0); pause = 0; }
            uint32_t a[4], b[4], q[5][4];
            ldm4t(h ? lb : la, a);
            ldm4t((h ? lb : la) + 1024, b);
#pragma unroll
            for (int e = 0; e < 5; e++) ldm4((e == 3 ? l3 : (e == 4 ? l4 : lm + (e == 2 ? 432 : 576 + 144 * e))) + 64 * h, q[e][0], q[e][1], q[e][2], q[e][3]);
#pragma unroll
            for (int e = 0; e < 4; e += 2) {
                auto mul = [&](int i) { return hp{q[i][e], q[i][e + 1]}; };
                const hp y0 = {b[e], b[e + 1]}, y1 = y0 * mul(1), y2 = y1 * mul(2), y3 = y1 * mul(3), y4 = y3 * mul(4), x1 = hp{a[e], a[e + 1]} * mul(0);
                const uint32_t a0 = a[e] | zero, a2 = a[e + 1] | zero;
                mma_h(d[0], a0, x1.re, a2, x1.im, y0.re, y0.im);
                mma_h(d[1], a0, x1.re, a2, x1.im, y1.re, y1.im);
                mma_h(d[2], a0, x1.re, a2, x1.im, y2.re, y2.im);
                mma_h(d[3], a0, x1.re, a2, x1.im, y3.re, y3.im);
                mma_h(d[4], a0, x1.re, a2, x1.im, y4.re, y4.im);
            }
        }
    } while (--nc);
    return eb;
}

__device__ __forceinline__ void near_lags(uint32_t S, int k, uint32_t yo, uint32_t eb, const uint32_t (&xa)[8], int late) {
    const int lane = threadIdx.x & 31, g = lane >> 2, t = lane & 3, mi = lane >> 3, j = lane & 7, warp = k;
    const uint32_t cb = S + SM_CH + k * CH;
    uint32_t R[66];
#pragma unroll
    for (int i = 0; i < 66; i++) R[i] = lds32(cb + TAB + 4 * (7 + g - 2 * t) + 32 * i);
    bar_arrive(1 + k, 64);
    float w[5][4];
#pragma unroll
    for (int i = 0; i < 5; i++) w[i][0] = w[i][1] = w[i][2] = w[i][3] = 0.f;
    uint32_t xo = cb;
    uint32_t fa = xa[0], idm = 0;
    uint32_t ya = S + SM_DUMP + 8 * lane, ybar = S + 61 * 8, dy = 0, db = 0;
    const uint32_t sc = prmt(eb + 0x04800000u, 0, 0x3232);
    uint32_t z = lds32(cb + XX + 4 * lane);
    int n = 16;
    mbar_wait(S + B_X * 8, 0);
    uint32_t A[3][4], x[5];
    ldm4(xo + xa[0], x[1], x[2], x[0], x[3]);
    ldm2(xo + xa[1], x[3], x[4]);
    auto send = [&]() { st_async2(ya, bmul(pack_bf(w[0][0], w[0][1]), sc), bmul(pack_bf(w[0][2], w[0][3]), sc), ybar); };
    auto tile = [&](auto nj, auto l4) {
        constexpr int NJ = decltype(nj)::value, L4 = decltype(l4)::value;
        asm volatile("" : "+r"(z), "+r"(xo));
        uint32_t f0, f1;
        if (NJ > 1) ldm2(xo + fa, f0, f1);
        send();
#pragma unroll
        for (int q = 1; q <= 8; q++) {
            const uint32_t ad = xo + xa[(q + 1) & 7] + 32 * ((q + 1) & 8);
            if (!L4) {
                A[0][0] = x[1]; A[0][1] = x[2]; A[0][2] = x[0] | z; A[0][3] = x[1] | z;
                x[0] = x[2]; x[1] = x[3]; x[2] = x[4];
                ldm2(ad, x[3], x[4]);
            } else if (NJ > 1 || q < 7) {
                ldm4(ad, A[2][0], A[2][1], A[2][2], A[2][3]);
            }
            const float zero[4] = {0.f, 0.f, 0.f, 0.f};
#pragma unroll
            for (int i = 0; i < NJ; i++) {
                const int s = 16 * i + 16 - 2 * q, e = NJ == 1 ? 2 * (~q & 1) : i;
                if (q == 1) mma_hc(w[i], w[i + 1], A[0][0], A[0][1], A[0][2], A[0][3], R[s], R[s + 1]);
                else if (NJ == 1 && q == 2) mma_hc(w[2], zero, A[0][0], A[0][1], A[0][2], A[0][3], R[s], R[s + 1]);
                else mma_h(w[e], A[0][0], A[0][1], A[0][2], A[0][3], R[s], R[s + 1]);
            }
            if (q == 4 && NJ > 1) mma_h8(w[1], f0, f1, idm);
            if (q == 7) {
                const uint32_t zz = A[0][0] & z;
                ya += dy + zz; ybar += db + zz; dy = 512 - dy; db = 8 - db;
            }
            if (q == 8 && NJ == 4) mma_hc(w[4], zero, A[0][0], A[0][1], A[0][2], A[0][3], R[64], R[65]);
#pragma unroll
            for (int e = 0; e < 4 * L4; e++) { A[0][e] = A[1][e]; A[1][e] = A[2][e]; }
        }
        xo += 256;
    };
    auto ready = [&]() {
#pragma unroll 1
        while (lds32v(S + SM_PROG + 4 * k) >= n) __nanosleep(40);
    };
    int lim = 15;
#pragma unroll 1
    do {
        n -= lim;
#pragma unroll 1
        do tile(Int<4>(), Int<0>()); while (--n);
        n = lim;
        const int lane = laneid(), g = lane >> 2, t = lane & 3;
        if (n == 15) {
            ybar = mapa(S + B_Y * 8, g >> 1);
            db = dy = mapa(S + B_Y * 8, 4 + (g >> 1)) - ybar;
            ya = ybar - B_Y * 8 + SM_CH + k * CH + YIN + (yo ^ (8 * (lane & 7)));
        }
        if (n == 13) { fa = TAB - 768 + 16 * (lane & 15); idm = g == 2 * t ? 0x3C00u : (g == 2 * t + 1 ? 0x3C000000u : 0u); }
        ready();
        lim = n == 15 ? 13 : n - 4;
    } while (n > late);
    ldm4(xo + xa[0], A[0][0], A[0][1], A[0][2], A[0][3]);
    ldm4(xo + xa[1], A[1][0], A[1][1], A[1][2], A[1][3]);
#pragma unroll 1
    for (;;) {
        lim = max(n - 4, 3);
        n -= lim;
#pragma unroll 1
        do tile(Int<4>(), Int<1>()); while (--n);
        n = lim;
        if (n == 3) break;
        ready();
    }
    tile(Int<3>(), Int<1>());
    tile(Int<2>(), Int<1>());
    tile(Int<1>(), Int<1>());
#pragma unroll
    for (int e = 0; e < 4; e++) w[0][e] += w[2][e];
    send();
}

__global__ void __cluster_dims__(8, 1, 1) __launch_bounds__(NTHREADS, 1) fused_kernel(const __grid_constant__ Hot p, const __grid_constant__ Maps m) {
    extern __shared__ __align__(1024) char smem[];
    const uint32_t t0 = clk32();
    const int tid = threadIdx.x, lane = tid & 31, bx = blockIdx.x;
    {
        const uint32_t a = min(tid >> 5, 5), ln = 10 * bx + lane;
        const void* pa = at256(p.u + ln * 64, (&p.bre)[a]);
        asm volatile("{.reg .pred p; setp.lt.u32 p, %1, 10; setp.lt.and.u32 p, %2, 192, p; setp.lt.and.u32 p, %3, 1152, p;\n@p prefetch.global.L2 [%0];}"
                     ::"l"(pa), "r"(lane), "r"(tid), "r"(ln) : "memory");
    }
    const int g = lane >> 2, t = lane & 3, mi = lane >> 3, j = lane & 7;
    const uint32_t role = __shfl_sync(~0u, (tid >> 5) | ((uint32_t)((bx < 24 ? 0x5776666632103210ull : 0x5436666621043210ull) >> ((tid >> 3) & 60)) & 15) << 8 |
                                               max(4 * (bx >> 3), 5 * (bx >> 3) - 3) << 16 | bx << 24, 0);
    const int warp = role & 255, k = (role >> 8) & 255, cbase = (role >> 13) & 0x7F8, bid = role >> 24, r = bid & 7, cl = role >> 27;
    const int pair = cl > 2, nch = 4 + pair;
    uint32_t S = smem_u32(smem);
    asm volatile("" : "+r"(S));

    const int half = warp >= nch;
    const bool two = cl == 1 || cl == 2, extra = two && k == 7, svcwarp = (warp >> 2) == 2;
    KParams kp;
    uint32_t epoch, pre[8];
    if (k < nch) {
        const uint32_t ch = cbase + 8 * k + r;
        const char* pb = (const char*)p.u + (ch * 256 + half * 128 + lane * 4);
        kp.bre = ldg1(at256(pb, p.bre)); kp.bim = ldg1(at256(pb, p.bim));
        kp.cre = ldg1(at256(pb, p.cre)); kp.cim = ldg1(at256(pb, p.cim));
        kp.ldt = ldg16(at256(p.u + ch, lane & 1 ? p.dskip : p.logdt));
        kp.are = ldg1(at256(pb, p.are)); kp.aim = ldg1(at256(pb, p.aim));
        sts128(S + SM_CH + k * CH + 16 * lane + (half ? FT : (lane < 2 ? TAB : (lane < 8 ? TAB + 2048 : FT + 384))), 0u, 0u, 0u, 0u);
        sts32(S + SM_PROG + 4 * k, 13);
        kgen_addr(kp, S + SM_CH + k * CH + BOX + 3072 * half, lane);
        if (half) {
            const uint32_t a0 = BOX + 16 + 576 * (j & 1) + 16 * (j >> 1);
            pre[0] = keep(a0 + (mi == 1 ? 1152 : (mi == 2 ? 1136 : 0)));
            pre[1] = keep(a0 + 2304 + 1152 * (mi & 1) + 64 * (mi >> 1));
            pre[2] = keep(BOX + 16 + 4608 + 576 * (mi & 1) + 128 * (mi >> 1) + 16 * j);
            pre[3] = keep(BOX + 16 + (lane < 2 ? 1152 + 576 * lane : 2896));
            pre[4] = keep(xslot(8 + lane, 0));
            pre[5] = keep(xslot(7 + lane, 0));
            pre[6] = keep(FT + 504 - 128 * (t & 1) + 4 * g + (t & 2));
            pre[7] = keep(g == 2 * t ? 0x4432 : (g == 2 * t + 1 ? 0x3244 : 0x4444));
        } else {
            const uint32_t v = xslot(lane & 15, lane >> 4);
#pragma unroll
            for (int i = 0; i < 8; i++) pre[i] = __shfl_sync(~0u, v, j + i + (mi == 1 ? 17 : (mi == 2 ? 16 : 1)));
        }
    } else if (warp == 12) {
        if (elect()) {
            mbar_init(S + B_WR * 8, 1);
            mbar_init(S + B_ROWS * 8, 1);
            mbar_expect(S + B_WR * 8, 1152);
            bulk_g2s(S + SM_B + 2048, (const char*)p.u + p.wr * 256ll, 1152, S + B_WR * 8);
            while ((int)(clk32() - t0) < p.tn.t_rows) {}
            mbar_expect(S + B_ROWS * 8, two ? 36864 : 18432);
            const __nv_bfloat16* src = p.u + (8 * (cl & 14) + 2 * r + (cl & 1)) * 9216;
            bulk_g2s(S + SM_TOTAL - 18432, src, 18432, S + B_ROWS * 8);
            if (two) bulk_g2s(S + SM_CH + 4 * CH - 128, p.u + (113 + 2 * r) * 9216, 18432, S + B_ROWS * 8);
        }
    } else if (svcwarp) {
        if (elect()) {
#pragma unroll
            for (int i = 0; i < 16; i++) mbar_init(S + (warp & 3) * 128 + i * 8, warp > (i < 14 ? 10 : 9) ? 4 : 1);
            asm volatile("fence.mbarrier_init.release.cluster;" ::: "memory");
        }
        __syncwarp();
        sts128(S + SM_B + 16 * tid, 0x3F803F80u, 0x3F803F80u, 0x3F803F80u, 0x3F803F80u);
        if (tid < 256 + B_RAW) mbar_expect(S + lane * 8, (uint32_t)(0x0808480101180804ull >> (8 * max(lane - 7, 0)) & 255) * (lane < B_TOP ? 128 * nch : 128));
    }
    if (svcwarp || extra) epoch = ld_rlx(at256(p.u + bid * 16, p.ep));
    __syncthreads();
    asm volatile("barrier.cluster.arrive.relaxed.aligned;" ::: "memory");
    const uint2* sp = &p.s->stat[256 * r + 2 * (tid & 127)];
    uint4 sw;
    if (svcwarp) sw = ld_rlx4(sp);
    if (svcwarp || extra) {
        const uint32_t tag = ~epoch & 1;
        const int tile = extra ? 15 : cl, wj = extra ? warp + 2 * cl - 15 : warp & 3;
        float d2[4] = {0, 0, 0, 0}, d3[4] = {0, 0, 0, 0}, d4[4] = {0, 0, 0, 0}, d5[4] = {0, 0, 0, 0}, d6[4] = {0, 0, 0, 0}, d7[4] = {0, 0, 0, 0};
        const uint32_t xa = S + (extra ? SM_CH + 4 * CH - 128 : SM_TOTAL - 18432) + (8 * (mi >> 1) + 2 * wj + (mi & 1)) * 1152 + 16 * j;
        const uint32_t wa = S + SM_B + 4104 - 2056 * (g & 1) + 64 * (g >> 2) + 16 * t + 2 * (g & 2), ones = 0x3F803F80u;
        uint32_t wv[18];
        mbar_wait_short(S + B_WR * 8);
#pragma unroll
        for (int i = 0; i < 18; i++) wv[i] = lds32(wa + 128 * (i >> 1) + 8 * (i & 1));
#pragma unroll
        for (int i = 0; i < 9; i++) mma_bf(d5, ones, ones, ones, ones, wv[2 * i], wv[2 * i + 1]);
        float wsum = d5[1] + __shfl_xor_sync(~0u, d5[1], 1);
        wsum += __shfl_xor_sync(~0u, wsum, 2);
        mbar_wait_short((S + B_ROWS * 8) | (__float_as_uint(wsum) & p.tn.zero));
        __syncwarp();
#pragma unroll
        for (int i = 0; i < 9; i++) {
            const uint4 x = lds128(xa + 128 * i);
            mma_bf8(d3, x.x, x.y, x.x);
            mma_bf8(d4, x.x, x.y, x.y);
            mma_bf8(d6, x.z, x.w, x.z);
            mma_bf8(d7, x.z, x.w, x.w);
            mma_bf(d2, x.x, x.y, x.z, x.w, wv[2 * i], wv[2 * i + 1]);
        }
        float sx = d2[0] + d2[2], sq = (g & 1) ? (d3[1] + d4[3]) + (d6[1] + d7[3]) : (d3[0] + d4[2]) + (d6[0] + d7[2]);
        float dot = (t & 1) ? d2[3] : d2[1];
        sx += __shfl_xor_sync(~0u, sx, 4);
        sq = __shfl_sync(~0u, sq, 9 * mi) + __shfl_sync(~0u, sq, 9 * mi + 4);
        dot += __shfl_xor_sync(~0u, dot, 1);
        dot += __shfl_xor_sync(~0u, dot, 6);
        const float mean = sx * (1.f / 576.f), var = fmaxf(sq * (1.f / 576.f) - mean * mean, 0.f);
        const float mu = bf_round(mean), sd = bf_round(sqrt_ap(bf_round(bf_round(var) + 1e-5f)));
        const uint32_t idx = 2047 - (128 * (tile & 14) + 32 * r + 16 * (tile & 1) + 8 * (mi >> 1) + 2 * wj + (mi & 1));
        const uint32_t rb = pack_bf(0.f, (dot - mu * wsum) * rcpf(sd));
        uint2 v = make_uint2((__float_as_uint(mu) >> 16) | __float_as_uint(sd), (((rb ^ (((int)rb >> 31) | 0x80000000u)) >> 1) & 0x7FFF8000u) | (tag << 31) | idx);
        uint2* const dst = &p.s->stat[256 * r + 16 * tile];
        if (extra) {
            if (j == 0) st_rlx2(dst + 4 * wj + mi, v.x, v.y);
            bar_arrive(13, 224);
        } else {
        const uint32_t ga = S + SM_B + 3200 + 32 * wj;
        if (j == 0) sts64(ga + 8 * mi, v.x, v.y);
        bar_sync(15, 128);
        if (tid < 272) {
            v = lds64(ga + 8 * lane);
            st_rlx2(dst + lane, v.x, v.y);
        }
        if (lane == 0) mbar_arrive(S + (B_EMPTY + 10) * 8);
        }
    }

    if (k < nch) {
        const uint32_t cb = S + SM_CH + k * CH, scr = cb + BOX + 3072 * half, oth = cb + BOX + 3072 - 3072 * half;
        float d[5][4], k0;
        kp.dsk = __shfl_sync(~0u, kp.ldt, 1);
        kp.ldt = __shfl_sync(~0u, kp.ldt, 0);
        const uint32_t eb = kgen(kp, scr, oth, 1 + k, lane, d, k0, k > 7 - nch ? 3 - 2 * half : 2, ((p.tn.stag >> warp) & 1) ? S + (B_EMPTY + 10) * 8 : 0, p.tn.zero);
        __syncwarp();
#pragma unroll
        for (int i = 0; i < 5; i++)
            if (half == (i < 3)) sts128f(kp.sa + i * 512, d[i][0], d[i][1], d[i][2], d[i][3]);
        bar_sync(1 + k, 64);
        auto both = [&](int i) {
            const uint4 v = lds128(oth + i * 512 + lane * 16);
            d[i][0] += __uint_as_float(v.x); d[i][1] += __uint_as_float(v.y); d[i][2] += __uint_as_float(v.z); d[i][3] += __uint_as_float(v.w);
        };
        if (half) {
            both(3); both(4);
            const uint32_t o = cb + FT + 56 + 2 * lane, q = cb + pre[6];
#pragma unroll
            for (int e = 0; e < 2; e++) {
                const uint32_t a = pack_h(d[3][e], d[3][2 + e]), b = pack_h(d[4][e], d[4][2 + e]);
                sts16(o + 128 - 128 * e, a); sts16(o + 192 - 128 * e, a >> 16);
                sts16(q + 64 - 64 * e, b); sts16(q + 96 - 64 * e, b >> 16);
            }
            bar_sync(1 + k, 64);
        } else {
            {
                both(0); both(1); both(2);
                const uint32_t a[2] = {pack_h(d[0][0], d[1][0]), pack_h(d[0][2], d[1][2])}, b[2] = {pack_h(d[0][1], d[1][1]), pack_h(d[0][3], d[1][3])};
                const uint32_t c[2] = {pack_h(d[2][0], d[2][1]), pack_h(d[2][2], d[2][3])};
                uint32_t last = pack_h(k0, k0);
                const uint32_t o = cb + TAB + 32 + 16 * lane;
                sts16(cb + TAB + 28, last);
#pragma unroll
                for (int h = 0; h < 4; h++) {
                    const uint32_t e = h < 2 ? b[h] : c[h - 2], pv = __shfl_sync(~0u, lane == 31 ? last : e, lane - 1);
                    if (h < 2) sts128(o + 512 * h, prmt(a[h], pv, 0x7610), prmt(a[h], 0, 0x1032), prmt(e, a[h], 0x7610), prmt(e, 0, 0x1032));
                    else sts128(o + 512 * h, prmt(pv, 0, 0x3232), prmt(e, pv, 0x7610), prmt(e, 0, 0x1032), prmt(e, 0, 0x3232));
                    last = e;
                }
                if (lane == 31) sts128(o + 1552, prmt(last, 0, 0x3232), prmt(last, 0, 0x3232), last & 0xFFFF0000u, 0u);
                __syncwarp();
            }
            near_lags(S, k, 64 * r + 16 * ((2 * k + (cbase >> 2) + (r >> 2)) & 3), eb, pre, (p.tn.late >> (5 * k)) & 31);
            return;
        }
    }

    const int ph0 = pair & ~r, f0 = pair ? 32 * (bid & ~1) + 768 : 64 * bid;
    if (k == 7) {
        spin_until(t0, p.tn.t_pf);
#pragma unroll 1
        for (int e = tid - 224; e < 576; e += 64) {
            asm volatile("prefetch.global.L2 [%0];" ::"l"(p.wg + e * F_ + f0) : "memory");
            __nanosleep(100);
        }
        return;
    }
    if (warp == 12) {
        if (elect()) {
            asm volatile("prefetch.tensormap [%0];" ::"l"(m.w + ph0) : "memory");
            asm volatile("prefetch.tensormap [%0];" ::"l"(&m.u) : "memory");
            spin_until(t0, p.tn.t_tile);
            auto raw = [&]() {
                mbar_expect(S + B_RAW * 8, 256 * PITCH);
                asm volatile("cp.async.bulk.tensor.5d.shared::cluster.global.mbarrier::complete_tx::bytes [%0], [%1, {%3, 0, %4, 0, 0}], [%2];"
                             ::"r"(S + SM_RAW), "l"(&m.u), "r"(S + B_RAW * 8), "r"(cbase), "r"(4 * r) : "memory");
            };
            raw();
            uint32_t bar = S + B_FULL * 8, dst = S + SM_W, em = 0x1249400u, wm = pair ? p.tn.win5 : p.tn.win4, wb = bar;
#pragma unroll 1
            for (int ph = ph0; ph < 3; ph += 1 + (pair & r)) {
                const int c0 = ph < 2 ? f0 : cbase, c1 = ph < 2 ? 0 : 576 * r;
#pragma unroll 1
                for (int n = 0; n < 576; n += 64) {
                    if (wm & 3) { wb += 8 * (wm & 3); mbar_wait(wb - 8, 0); }
                    if (em & 1) mbar_wait(bar + 8 * (B_EMPTY - B_FULL), 0);
                    mbar_expect(bar, ph < 2 ? 8192 : 128 * 40);
                    tma2d(dst, m.w + ph, c0, c1 + n, bar);
                    bar += 8; em >>= 1; wm = wm >> 2 | 0x40000000u;
                    dst = dst == S + SM_W + (NRING - 1) * 8192 ? S + SM_W : dst + 8192;
                }
            }
        }
        return;
    }

    if (warp == 15) {
        asm volatile("barrier.cluster.wait.aligned;" ::: "memory");
        sts32(S + SM_SKIP + 4 * j, 0u);
        const uint32_t ob = mapa(S, g);
        bar_sync(13, two ? 224 : 160);
        const uint4 ka = lds128(S + SM_B + 256 + 16 * lane), kb = lds128(S + SM_B + 768 + 16 * lane);
        uint32_t k0 = ka.x, k1 = ka.y, mine = 0, c = 0;
        int rank = lane;
#pragma unroll 1
        for (int pass = 0;; pass++) {
#pragma unroll 1
            for (int n = 0; n < (pass < 2 ? 4 : 8); n++) {
                const uint32_t a = __viaddmin_u32(k0, c, __viaddmin_u32(k1, c, ka.z + c)), b = __viaddmin_u32(ka.w, c, __viaddmin_u32(kb.x, c, kb.y + c));
                c += ~__reduce_min_sync(~0u, __vimin3_u32(a, b, __viaddmin_u32(kb.z, c, kb.w + c)));
                if ((pass < 2 ? t : j) == n) mine = c;
            }
            if (pass == 2) break;
            asm volatile("st.async.shared::cluster.mbarrier::complete_tx::bytes.b32 [%0], %1, [%2];" ::"r"(ob + SM_CAND + 128 * pass + 16 * r + 4 * t), "r"(~mine), "r"(ob + (B_TOP + pass) * 8) : "memory");
            mbar_wait_short(S + (B_TOP + pass) * 8);
            const uint32_t v = lds32(S + SM_CAND + 4 * lane);
            if (pass) {
                k0 = v; k1 = lds32(S + SM_CAND + 128 + 4 * lane); c = 0;
            } else {
                uint32_t cn[4] = {0, 0, 0, 0};
#pragma unroll 4
                for (int e = 0; e < 128; e += 16) {
                    const uint4 o = lds128(S + SM_CAND + e);
                    cn[0] += (o.x - v) >> 31; cn[1] += (o.y - v) >> 31; cn[2] += (o.z - v) >> 31; cn[3] += (o.w - v) >> 31;
                }
                const int rk = (cn[0] + cn[1]) + (cn[2] + cn[3]);
                if (!__any_sync(~0u, t == 3 && rk < 8)) { rank = rk; mine = ~v; break; }
            }
        }
        const uint32_t row = ~mine & 2047, ix = (row & 0xE0) * 8 + ((row >> 3) & 0xE0) + (row & 0x11) + ((row >> 2) & 2) + (row & 6) * 2;
        const uint32_t mr = __reduce_or_sync(~0u, rank == r ? row : 0u);
        if (elect()) {
            bulk_mc(S + SM_B + BP * r, p.u + mr * D_, 1152, S + B_XS * 8);
        }
        const bool own = rank < 8 && (ix >> 8) == r;
        const uint32_t m2 = 2 * mine, rb = (m2 ^ ((~(int)m2 >> 31) | 0x80000000u)) & 0xFFFF0000u;
        if (rank < 8) sts64(S + SM_SEL + 8 * rank, ix | rb, row | ((row & 0x700) + 32 * (row & 6) + 2 * (row & 24) + 8 * (row & 1)) << 16);
        if (own) asm volatile("red.shared.or.b32 [%0], %1;" ::"r"(S + SM_SKIP + 4 * (ix & 7)), "r"(1u << ((ix >> 3) & 31)) : "memory");
        const int no = __popc(__ballot_sync(~0u, own));
        if (lane < 2) mbar_expect(S + (B_FIN + lane) * 8, lane ? 0 : no * (nch - 2) * 256);
        __syncwarp();
        const uint2 sv = lds64(S + SM_SEL + 8 * j);
        float sa, sb;
        asm volatile("ld.shared::cluster.v2.f32 {%0, %1}, [%2];" : "=f"(sa), "=f"(sb) : "r"(mapa(S + SM_ST + (sv.y >> 16), (sv.x >> 8) & 7)) : "memory");
        const float m1 = -sb * rcpf(sa);
        const uint32_t mu = pack_bf(m1, m1), bw = S + SM_B + BP * j + 16 * mi;
        sts32(S + SM_PROG + 32 + 4 * j, __float_as_uint(sa + sa));
        mbar_wait_short(S + B_XS * 8);
#pragma unroll 1
        for (int n = 0; n < 1152; n += 576) {
            uint4 v[9];
#pragma unroll
            for (int e = 0; e < 9; e++) v[e] = lds128(bw + n + 64 * e);
#pragma unroll
            for (int e = 0; e < 9; e++) sts128(bw + n + 64 * e, bsub(v[e].x, mu), bsub(v[e].y, mu), bsub(v[e].z, mu), bsub(v[e].w, mu));
        }
        bar_arrive(14, 160);
    }

    if (svcwarp) {
        const uint32_t tag = ~epoch & 1;
        const int fw = warp & 3, i = tid & 127;
        uint32_t xbar = mapa(S + B_X * 8, g), xd = keep(xbar - B_X * 8 + SM_CH + xslot(8 + 2 * r + (t >> 1), t & 1) + 256 * (fw & 2));
        uint32_t ra = keep(S + SM_RAW + (64 * mi + j + 4 * (fw & 2)) * PITCH), sa = keep(S + SM_ST + 16 * t + 128 * (fw & 2));
        const uint32_t ta = keep(S + SM_ST + 16 * (i & 0x71) + 32 * (i & 6) + 4 * (i & 8));
        asm volatile("barrier.cluster.wait.aligned;" ::: "memory");
        mbar_wait_short(S + B_RAW * 8);
#pragma unroll 1
        for (int it = 0; it < SPIN_LIMIT && (int)((sw.y ^ -tag) | (sw.w ^ -tag)) < 0; it++) sw = ld_rlx4(sp);
        sts64(S + SM_B + 256 + 8 * i, ~sw.y, ~sw.w);
        {
            const float r0 = 0.5f * rcpf(bf_hi(sw.x)), r1 = 0.5f * rcpf(bf_hi(sw.z));
            sts128f(ta, r0, -bf_lo(sw.x) * r0, r1, -bf_lo(sw.z) * r1);
        }
        bar_sync(13, two ? 224 : 160);
        if (i == 0) st_rlx(&p.s->ep[bid * 8], epoch + 1);
        {
#pragma unroll 1
            for (int u = fw; u < fw + 4; u++) {
                uint4 s[4];
#pragma unroll
                for (int e = 0; e < 4; e++) s[e] = lds128(sa + 64 * e);
#pragma unroll 1
                for (int n = u & 1; n < nch; n += 2) {
                    uint32_t a[4];
                    ldm4t(ra + 16 * n, a);
#pragma unroll
                    for (int e = 0; e < 4; e++)
                        a[e] = pack_h(fmaf(bf_lo(a[e]), __uint_as_float(s[e].x), __uint_as_float(s[e].y)), fmaf(bf_hi(a[e]), __uint_as_float(s[e].z), __uint_as_float(s[e].w)));
                    st_async4(xd + n * CH, a[0], a[1], a[2], a[3], xbar);
                }
                xd += 1024; ra += 16 * PITCH; sa += 512; xbar |= 8;
            }
        }
        const int mt = (fw + 3) & 3;
        const uint32_t bw = keep(S + SM_B + BP * j + 16 * (i >> 3)), ba = keep(S + SM_B + BP * j + 16 * mi);
        const uint32_t aa = keep(S + SM_W + (8 * (mi >> 1) + j) * 128 + (((2 * mt + (mi & 1)) ^ j) << 4));
        uint32_t bar = S + B_FULL * 8, of = 0;
        bar_sync(14, 160);
        const uint2 sv = lds64(S + SM_SEL + 8 * j), ri = lds64(S + SM_PROG + 32 + 8 * t);
        float r0 = __uint_as_float(ri.x), r1 = __uint_as_float(ri.y);
        const uint32_t tx = clk32();
        float d[4][4];
#pragma unroll 1
        for (int ph = ph0;; ph++) {
            if (ph == 2) {
                bar_sync(15, 128);
                spin_until(tx, p.tn.da);
                r0 = r1 = 1.f;
                const uint32_t* const hp = p.s->h + 2304 * r + 4 * i;
                uint4 v[5];
                const uint32_t tm = -tag;
#pragma unroll 1
                for (int it = 0; it < SPIN_LIMIT; it++) {
                    uint32_t bad = 0;
#pragma unroll
                    for (int n = 0; n < 5; n++) v[n] = ld_rlx4(hp + (n < 4 ? 512 * n : 1792));
#pragma unroll
                    for (int n = 0; n < 5; n++) bad |= lop_ne(v[n].x, v[n].z, tm);
                    if (!(bad & 1)) break;
                }
#pragma unroll
                for (int n = 0; n < 5; n++) sts128(bw + (n < 4 ? 256 * n : 896), v[n].x, v[n].y, v[n].z, v[n].w);
                bar_sync(15, 128);
            }
            if (ph == 2 && mt >= nch - 2) break;
#pragma unroll
            for (int e = 0; e < 4; e++) d[0][e] = d[1][e] = d[2][e] = d[3][e] = 0.f;
#pragma unroll 1
            for (int n = 0; n < 1152; n += 384) {
                uint32_t a[12][4], b[24];
                mbar_wait(bar + 8 * min(lane, 2), 0);
                __syncwarp();
#pragma unroll
                for (int e = 0; e < 12; e++) {
                    if (!(e & 1)) ldm4(ba + n + 32 * e, b[2 * e], b[2 * e + 1], b[2 * e + 2], b[2 * e + 3]);
                    ldm4t(aa + of + 2048 * e, a[e]);
                }

#pragma unroll
                for (int e = 0; e < 12; e++) mma_bf(d[e & 3], a[e][0], a[e][1], a[e][2], a[e][3], b[2 * e], b[2 * e + 1]);
                if (lane == 0) mbar_arrive(min(bar + (B_EMPTY + NRING - B_FULL) * 8, S + 63 * 8));
                bar += 24;
                of = of == 8192 * (NRING - 3) ? 0 : of + 24576;
            }
#pragma unroll
            for (int e = 0; e < 4; e++) d[0][e] = (d[0][e] + d[1][e]) + (d[2][e] + d[3][e]);
            uint32_t k0 = pack_bf(d[0][0] * r0, d[0][1] * r1), k1 = pack_bf(d[0][2] * r0, d[0][3] * r1);
            const uint32_t ea = SM_FIN + 6144 + 8 * i, eb = B_UP * 8;
            if (ph == 0) {
                const uint32_t ob = mapa(S, r & ~pair);
                st_async2(ob + ea, k0, k1, ob + eb);
                ph += pair;
                continue;
            }
            if (ph == 1) {
                k0 = pack_bf(silu_half(0.5f * bf_lo(k0)), silu_half(0.5f * bf_hi(k0))); k1 = pack_bf(silu_half(0.5f * bf_lo(k1)), silu_half(0.5f * bf_hi(k1)));
                mbar_wait_short((S + eb) | (k0 & k1 & p.tn.zero));
                const uint2 v = lds64(S + ea);
                k0 = bmul(k0, v.x); k1 = bmul(k1, v.y);
                __syncwarp();
            }
            k0 = movm(k0); k1 = movm(k1);
            if (ph == 2) {
                const uint32_t ob = mapa(S, (__shfl_sync(~0u, sv.x, g) >> 8) & 7);
                st_async2(ob + SM_FIN + 768 * g + 96 * r + 32 * mt + 8 * t, k0, k1, ob + B_FIN * 8);
                break;
            }
            const uint32_t o = __shfl_xor_sync(~0u, (lane & 1) ? k0 : k1, 1);
            st_rlx2(p.s->h + 4 * f0 + 64 * mt + 31 * (lane & 1) + lane, (((lane & 1) ? o : k0) & ~1u) | tag, (lane & 1) ? k1 : o);
        }
        const int l = min(lane, 4 * nch - 1);
        int n = fw;
#pragma unroll 1
        for (uint32_t own = __ballot_sync(~0u, ((sv.x >> 8) & 7) == r) & 255; own; own &= own - 1) {
            if (n-- & 3) continue;
            const int tk = __ffs(own) - 1;
            const uint2 e = lds64(S + SM_SEL + 8 * tk), st = lds64(S + SM_ST + (e.y >> 16));
            const uint32_t ix = e.x, x = lds32(S + SM_RAW + (16 * (ix & 12) + ((ix >> 2) & 60) + (ix & 3)) * PITCH + 4 * l);
            const uint32_t yb = S + SM_CH + YIN + (l >> 2) * CH + 16 * (ix & 0xE0) + 128 * (l & 3) + 16 * (((ix >> 3) ^ ((l >> 1) + (cbase >> 2))) & 3) + 2 * (ix & 7);
            const float sg = 0.5f * sigm(bf_hi(ix));
            const uint32_t hx = pack_bf(fmaf(bf_lo(x), __uint_as_float(st.x), __uint_as_float(st.y)), fmaf(bf_hi(x), __uint_as_float(st.x), __uint_as_float(st.y))), sg2 = pack_bf(sg, sg);
            mbar_wait((S + B_FIN * 8) | (hx & sg2 & p.tn.zero), 0);
            float a[2] = {0.f, 0.f}, b[2] = {0.f, 0.f};
#pragma unroll
            for (int q = 0; q < 8; q++) {
                const uint32_t v = lds32(S + SM_FIN + 768 * tk + 96 * q + 4 * (l & 24) + 8 * (l & 3) + (l & 4));
                a[q & 1] += bf_lo(v); b[q & 1] += bf_hi(v);
            }
            const uint32_t hv = badd(hx, bmul(pack_bf(a[0] + a[1], b[0] + b[1]), sg2)), gt = pack_bf(silu_half(bf_lo(hv)), silu_half(bf_hi(hv)));
            mbar_wait((S + B_Y * 8 + ((ix >> 2) & 56)) | (gt & p.tn.zero), 0);
            *(uint32_t*)(p.out + (e.y & 2047) * D_ + cbase + 2 * l) = bfma(lds16(yb) | (lds16(yb + 64) << 16), gt, x);
        }
        return;
    }

    mbar_wait(S + B_X * 8, 0);
    if (k < nch) {
        const uint32_t cb = S + SM_CH + k * CH, bx = cb + BOX + 16;
        float u[4][4], v[4][4], w[4][4];
#pragma unroll
        for (int i = 0; i < 4; i++) v[i][0] = v[i][1] = v[i][2] = v[i][3] = w[i][0] = w[i][1] = w[i][2] = w[i][3] = 0.f;
        uint2 T4[10];
        const uint32_t ta = cb + FT + 4 * (g - t);
#pragma unroll
        for (int e = 0; e < 10; e++) T4[e] = lds64(ta + 24 + 32 * e + 4 * (g - t));
        const uint32_t tb = prmt(lds32(cb + FT + 308), 0, pre[7]);
        const uint32_t a4 = cb + pre[0], a8 = cb + pre[1], at = cb + pre[2], hb = cb + pre[3], o = bx + 16 * lane;
        uint32_t xi = cb + pre[4], xp = cb + pre[5], hs = cb + XX;
#pragma unroll 1
        for (int n = 9; n > 0; n -= 4) {
            {
                const uint4 hv = lds128(hs);
                hs = hb + 496;
                const uint2 v0 = lds64(xp + 8);
                const uint4 v1 = lds128(xp ^ 32), v2 = lds128(xi), v3 = lds128(xi ^ 32);
                xi += 1024; xp += 1024;
                __syncwarp();
                if (lane < 3) sts128(hb - 16, hv.x, hv.y, hv.z, hv.w);
                const uint32_t P[13] = {v0.x, v0.y, v1.x, v1.y, v1.z, v1.w, v2.x, v2.y, v2.z, v2.w, v3.x, v3.y, v3.z};
                uint32_t Q[12], s2[12], s4[10], b3[11], b5[9];
#pragma unroll
                for (int e = 0; e < 12; e++) { Q[e] = prmt(P[e], P[e + 1], 0x5432); s2[e] = hadd(P[e], Q[e]); }
#pragma unroll
                for (int e = 0; e < 11; e++) b3[e] = hadd(Q[e], s2[e + 1]);
#pragma unroll
                for (int e = 0; e < 10; e++) s4[e] = hadd(s2[e], s2[e + 1]);
#pragma unroll
                for (int e = 0; e < 9; e++) b5[e] = hadd(s4[e + 1], P[e + 3]);
                sts128(o, b3[3], b3[4], b3[5], b3[6]);
                sts128(o + 1152, b3[7], b3[8], b3[9], b3[10]);
                sts128(o + 576, b5[0], b5[1], b5[2], b5[3]);
                sts128(o + 1728, b5[4], b5[5], b5[6], b5[7]);
                if (n > 4) {
                    sts128(o + 4608, s2[4], s2[5], s2[6], s2[7]);
                    sts128(o + 5184, s2[8], s2[9], s2[10], s2[11]);
                    sts128(o + 2304, hadd(b3[0], s4[2]), hadd(b3[1], s4[3]), hadd(b3[2], s4[4]), hadd(b3[3], s4[5]));
                    sts128(o + 3456, hadd(b3[4], s4[6]), hadd(b3[5], s4[7]), hadd(b3[6], s4[8]), hadd(b3[7], s4[9]));
                    sts128(o + 4032, hadd(s4[0], b5[1]), hadd(s4[1], b5[2]), hadd(s4[2], b5[3]), hadd(s4[3], b5[4]));
                    sts128(o + 2896, hadd(s4[4], b5[5]), hadd(s4[5], b5[6]), hadd(s4[6], b5[7]), hadd(s4[7], b5[8]));
                }
                __syncwarp();
            }
            uint32_t A[8][4];
#pragma unroll
            for (int e = 0; e < 8; e++) ldm4t(a4 + 64 * e, A[e]);
#pragma unroll
            for (int e = 0; e < 8; e++)
#pragma unroll
                for (int b = 3; b >= e / 2; b--) {
                    const uint2 T = T4[2 * (b - e / 2) + 1 - (e & 1)];
                    if (e == 0) mma_hc(u[b], v[b], A[e][0], A[e][1], A[e][2], A[e][3], T.x, T.y);
                    else mma_h(u[b], A[e][0], A[e][1], A[e][2], A[e][3], T.x, T.y);
                }
            if (n == 9) mbar_wait_short(S + (B_X + 1) * 8);
#pragma unroll
            for (int e = 0; e < 2; e++)
                stm4t(cb + TAB + 2304 - 256 * n + 512 * e + 16 * lane, pack_h(u[2 * e][0], u[2 * e][1]), pack_h(u[2 * e][2], u[2 * e][3]),
                      pack_h(u[2 * e + 1][0], u[2 * e + 1][1]), pack_h(u[2 * e + 1][2], u[2 * e + 1][3]));
            __syncwarp();
            sts32v(S + SM_PROG + 4 * k, n);
            if (n == 1) break;
            uint32_t C[4][4], E[2][4], T8[16];
#pragma unroll
            for (int e = 0; e < 4; e++) ldm4t(a8 + 128 * e, C[e]);
#pragma unroll
            for (int e = 0; e < 2; e++) ldm4t(at + 256 * e, E[e]);
#pragma unroll
            for (int e = 0; e < 8; e++) T8[e] = lds32(ta + 376 + 32 * (e >> 1) - 16 * (e & 1));
#pragma unroll
            for (int e = 7; e >= 0; e--)
#pragma unroll
                for (int b = 0; b <= e / 2; b++) {
                    const uint2 T = T4[2 * (4 + b - e / 2) + 1 - (e & 1)];
                    if (e == 7) mma_hc(v[b], w[b], A[e][0], A[e][1], A[e][2], A[e][3], T.x, T.y);
                    else mma_h(v[b], A[e][0], A[e][1], A[e][2], A[e][3], T.x, T.y);
                }
#pragma unroll
            for (int e = 3; e >= 0; e--) {
                mma_h8(v[e], E[e >> 1][2 * (e & 1)], E[e >> 1][2 * (e & 1) + 1], tb);
#pragma unroll
                for (int b = 3; b >= e; b--) mma_h(v[b], C[e][0], C[e][1], C[e][2], C[e][3], T8[2 * (b - e)], T8[2 * (b - e) + 1]);
            }
            if (n == 9) {
#pragma unroll
                for (int e = 8; e < 16; e++) T8[e] = lds32(ta + 376 + 32 * (e >> 1) - 16 * (e & 1));
#pragma unroll
                for (int e = 3; e >= 0; e--)
#pragma unroll
                    for (int b = 0; b < 4; b++) mma_h(w[b], C[e][0], C[e][1], C[e][2], C[e][3], T8[2 * (4 + b - e)], T8[2 * (4 + b - e) + 1]);
            }
        }
    }

  {
    int lane;
    asm volatile("mov.u32 %0, %%laneid;" : "=r"(lane));
    const int g = lane >> 2, t = lane & 3, mi = lane >> 3, j = lane & 7, sh = (cbase >> 3) & 1;
    mbar_wait_short(S + B_SEL * 8);
    if (k < nch - 2 || k == 5) {
        const int one = k == 2, st = k == 5 ? 1 : 2, kk = one ? 4 - 4 * sh : sh + 2 * st - 2;
        const int q0 = k == 1, qx = q0 + (one & (t >> 1)), cx = 16 * kk + 8 * (one ? t & 1 : t);
        uint32_t xa = S + SM_RAW + (16 * (g & 4) + (g & 3) + 8 * qx) * PITCH + cx, sa = S + SM_ST + 16 * (g & 4) + 8 * (g & 3) + 256 * qx, bar = S + (B_Y + qx) * 8;
        uint32_t ya = S + SM_CH + YIN + kk * CH + (j >> 2) * (one ? 512 : CH) + 128 * (j & 2) + 128 * (mi & 1) + 64 * (j & 1) + 512 * q0 +
                      16 * ((mi >> 1) ^ (one ? 2 * sh + ((j >> 1) & 1) : j >> 1));
        uint32_t sk = lds32(S + SM_SKIP + 4 * g) >> (4 * qx);
        char* o = (char*)p.out + ((256 * qx + 32 * r + 4 * (g & 2) + 2 * (g >> 2) + (g & 1)) * D_ + cbase) * 2 + cx;
#pragma unroll 1
        for (int n = 0; n < 8; n += st) {
            uint2 x[4];
            uint32_t gt[8], y[2][4];
#pragma unroll
            for (int e = 0; e < 4; e++) {
                x[e] = lds64(xa + (128 * (e & 1) + 2 * (e & 2)) * PITCH);
                const uint2 s = lds64(sa + 128 * (e & 1) + 16 * (e & 2));
                const float a = __uint_as_float(s.x), b = __uint_as_float(s.y);
                gt[2 * e] = pack_bf(silu_half(fmaf(bf_lo(x[e].x), a, b)), silu_half(fmaf(bf_hi(x[e].x), a, b)));
                gt[2 * e + 1] = pack_bf(silu_half(fmaf(bf_lo(x[e].y), a, b)), silu_half(fmaf(bf_hi(x[e].y), a, b)));
            }
            mbar_wait(bar | (((gt[0] | gt[1] | gt[2]) | (gt[3] | gt[4] | gt[5]) | (gt[6] | gt[7])) & p.tn.zero), 0);
            __syncwarp();
            ldm4t(ya, y[0]);
            ldm4t(ya ^ 32, y[1]);
#pragma unroll
            for (int e = 0; e < 4; e++)
                asm volatile("{.reg .pred p; setp.eq.u32 p, %3, 0;\n@p st.global.v2.u32 [%0], {%1, %2};}" ::"l"(o + (8 * (e & 1) + 16 * (e & 2)) * D_),
                             "r"(bfma(y[e >> 1][2 * (e & 1)], gt[2 * e], x[e].x)), "r"(bfma(y[e >> 1][2 * (e & 1) + 1], gt[2 * e + 1], x[e].y)), "r"(sk & (1 << e)) : "memory");
            xa += 8 * PITCH * st; sa += 256 * st; ya += 512 * st; bar += 8 * st; sk >>= 4 * st; o += 512 * D_ * st;
        }
    }
  }
}

typedef CUresult (*EncodeFn)(CUtensorMap*, CUtensorMapDataType, cuuint32_t, void*, const cuuint64_t*, const cuuint64_t*, const cuuint32_t*,
                             const cuuint32_t*, CUtensorMapInterleave, CUtensorMapSwizzle, CUtensorMapL2promotion, CUtensorMapFloatOOBfill);

static void make2d(EncodeFn enc, CUtensorMap* m, const void* base, uint64_t cols, uint64_t rows, uint32_t bc = 64) {
    cuuint64_t gd[2] = {cols, rows};
    cuuint64_t gs[1] = {cols * 2};
    cuuint32_t bd[2] = {bc, 64}, es[2] = {1, 1};
    enc(m, CU_TENSOR_MAP_DATA_TYPE_BFLOAT16, 2, const_cast<void*>(base), gd, gs, bd, es, CU_TENSOR_MAP_INTERLEAVE_NONE, CU_TENSOR_MAP_SWIZZLE_128B,
        CU_TENSOR_MAP_L2_PROMOTION_L2_128B, CU_TENSOR_MAP_FLOAT_OOB_FILL_NONE);
}

static void make5d(EncodeFn enc, CUtensorMap* m, const void* base, uint32_t cols, CUtensorMapSwizzle sw) {
    cuuint64_t gd[5] = {D_, 2, 32, 8, 4};
    cuuint64_t gs[4] = {D_ * 2, D_ * 16, D_ * 512, D_ * 4};
    cuuint32_t bd[5] = {cols, 2, 4, 8, 4}, es[5] = {1, 1, 1, 1, 1};
    enc(m, CU_TENSOR_MAP_DATA_TYPE_BFLOAT16, 5, const_cast<void*>(base), gd, gs, bd, es, CU_TENSOR_MAP_INTERLEAVE_NONE, sw,
        CU_TENSOR_MAP_L2_PROMOTION_NONE, CU_TENSOR_MAP_FLOAT_OOB_FILL_NONE);
}

static Tune g_tune = {2000, 24807, 5412005, 1431655504, 1431635200, 800, 5000, 6500, 0};

static int max_clusters() {
    cudaFuncSetAttribute(fused_kernel, cudaFuncAttributeMaxDynamicSharedMemorySize, SM_TOTAL);
    cudaLaunchConfig_t cfg = {};
    cudaLaunchAttribute at[1];
    at[0].id = cudaLaunchAttributeClusterDimension;
    at[0].val.clusterDim.x = 8; at[0].val.clusterDim.y = 1; at[0].val.clusterDim.z = 1;
    cfg.gridDim = dim3(NCTA); cfg.blockDim = dim3(NTHREADS); cfg.dynamicSmemBytes = SM_TOTAL; cfg.attrs = at; cfg.numAttrs = 1;
    int n = 0;
    if (cudaOccupancyMaxActiveClusters(&n, fused_kernel, &cfg) != cudaSuccess) { cudaGetLastError(); n = 0; }
    return n;
}

static bool launch(void* const* d_in, void* d_out) {
    static EncodeFn enc = nullptr;
    static Scratch* gs = nullptr;
    if (!enc) {
        void* fn = nullptr;
        cudaDriverEntryPointQueryResult qr;
        cudaGetDriverEntryPoint("cuTensorMapEncodeTiled", &fn, cudaEnableDefault, &qr);
        enc = (EncodeFn)fn;
        cudaFuncSetAttribute(fused_kernel, cudaFuncAttributeMaxDynamicSharedMemorySize, SM_TOTAL);
        cudaGetSymbolAddress((void**)&gs, g_s);
    }
    Hot p;
    Maps m;
    auto in = [&](int i) { return (const __nv_bfloat16*)d_in[i]; };
    bool ok = true;
    auto off = [&](const void* q) {
        const long long d = (const char*)q - (const char*)d_in[0];
        ok = ok && d / 256 * 256 == d && (int)(d / 256) == d / 256;
        return (int)(d / 256);
    };
    p.u = in(0); p.are = off(in(1)); p.aim = off(in(2)); p.bre = off(in(3)); p.bim = off(in(4)); p.cre = off(in(5)); p.cim = off(in(6));
    p.logdt = off(in(7)); p.dskip = off(in(8)); p.wr = off(in(10)); p.ep = off(gs->ep);
    if (!ok) return false;
    p.out = (__nv_bfloat16*)d_out;
    p.wg = in(11);
    p.tn = g_tune;
    p.s = gs;
    make2d(enc, &m.w[0], in(12), F_, D_);
    make2d(enc, &m.w[1], in(11), F_, D_);
    make2d(enc, &m.w[2], in(13), D_, F_, 40);
    make5d(enc, &m.u, in(0), 40, CU_TENSOR_MAP_SWIZZLE_NONE);
    fused_kernel<<<NCTA, NTHREADS, SM_TOTAL>>>(p, m);
    return true;
}

}

namespace v2 {

constexpr int L_ = 2048, D_ = 576, F_ = 4608;
constexpr int NDOWN = 72, NMAIN = 128, NCTA = 132, NTHREADS = 512;
constexpr int SPIN_LIMIT = 1 << 16;
constexpr uint32_t SLOT_FREE = 0x7FFFABCDu;

constexpr int SM_PART = 544;
constexpr int SM_RED = SM_PART;
constexpr int SM_STA = 2080;
constexpr int SM_ONES = 2176;
constexpr int SM_KINF = 2192;
constexpr int SM_RP = 2272;
constexpr int SM_XS = 2704;
constexpr int KR_STRIDE = 1296;
constexpr int SM_X0 = 12080, X0_STRIDE = 4512, X0_ODD = 2240;
constexpr int SM_KT = 30128, KT_STRIDE = 3584, KT_P4 = 2144, KT_P8 = 2896;
constexpr int SM_FAR = 44544, FAR_STRIDE = 11328;
constexpr int FB5 = 0, FB3 = 3328, FB9E = 6656, FB9O = 7824, FB7E = 8992, FB7O = 10160;
constexpr int SM_ROWS = SM_FAR, ROW_STRIDE = 1168;
constexpr int SM_STG = SM_FAR + 19968;
constexpr int KG_SCR = 3072;
constexpr int SM_EX = 89856;
constexpr int EX_KT = SM_EX + X0_STRIDE, EX_FAR = EX_KT + KT_STRIDE, EX_HAND = 109312;
constexpr int SM_W_DOWN = 90112, SM_W_BIG = 121856, STAGE = 6144;
constexpr int SM_W_LAST = 12288;
constexpr int SM_TOTAL = 232448;
constexpr int SM_EPOCH = 2528, SM_SKIP = 2536;
static_assert(SM_STG + 8 * KG_SCR <= SM_EX && SM_STG % 128 == 0 && EX_HAND % 128 == 0 && EX_FAR + FAR_STRIDE <= EX_HAND && EX_HAND + 12288 <= SM_W_BIG, "scratch");

enum { B_ROWS = 0, B_KG, B_X0, B_X1, B_BOX  , B_TAB, B_EM = 6, B_SP = 10, B_OUT = 14, B_H = 15, B_RED = 16, B_TAB1 = 17, B_XS = 18, B_GX = 19, B_YIN = 22, B_P1 = 26, B_FD, B_GU = 28, B_W = 34, B_COUNT = 58 };

struct Tune { short f_start, f_t3, w2, w2b, w3, t_xs, t_svc, t_marg, f_t2, w1, zero, pad; };

struct Scratch {
    uint32_t x[144 * 4096];
    uint32_t y[128 * 4608];
    uint32_t h[2][F_ * 4];
    uint32_t key[L_];
    uint32_t stat[L_];
    uint32_t sel[4][32];
    uint32_t cnt[17 * 32];
};
__device__ __align__(1024) Scratch g_s;

struct Hot {
    const __nv_bfloat16* u;
    Scratch* s;
    const __nv_bfloat16 *wr, *are, *aim, *bre, *bim, *cre, *cim, *logdt;
    Tune tn;
    const __nv_bfloat16 *dskip, *pwg, *pwu, *pwd;
    __nv_bfloat16* out;
};
struct Maps { CUtensorMap wg, wu, wd; };

__device__ __forceinline__ uint32_t smem_u32(const void* p) { return (uint32_t)__cvta_generic_to_shared(p); }
__device__ __forceinline__ void mbar_init(uint32_t b, int c) { asm volatile("mbarrier.init.shared::cta.b64 [%0], %1;" ::"r"(b), "r"(c) : "memory"); }
__device__ __forceinline__ void mbar_expect(uint32_t b, int bytes) { asm volatile("mbarrier.arrive.expect_tx.shared::cta.b64 _, [%0], %1;" ::"r"(b), "r"(bytes) : "memory"); }
__device__ __forceinline__ void mbar_arrive(uint32_t b) { asm volatile("mbarrier.arrive.shared::cta.b64 _, [%0];" ::"r"(b) : "memory"); }
__device__ __forceinline__ bool elect() { uint32_t d; asm volatile("{.reg .pred p; elect.sync _|p, 0xffffffff; selp.u32 %0,1,0,p;}" : "=r"(d)); return d; }
__device__ __forceinline__ bool mbar_test(uint32_t b, int par) {
    uint32_t d;
    asm volatile("{.reg .pred p; mbarrier.test_wait.parity.shared::cta.b64 p, [%1], %2; selp.u32 %0,1,0,p;}" : "=r"(d) : "r"(b), "r"(par) : "memory");
    return d;
}
#define WAIT_LOOP(ins) "{\n.reg .pred p;\n.reg .u32 n;\nmov.u32 n, 0;\nLW:\n" ins " p, [%0], %1;\n@p bra LD;\nadd.u32 n, n, 1;\nsetp.lt.u32 p, n, 16384;\n@p bra LW;\nLD:\n}"
__device__ __forceinline__ void mbar_wait(uint32_t b, int par) { asm volatile(WAIT_LOOP("mbarrier.try_wait.parity.shared::cta.b64")::"r"(b), "r"(par) : "memory"); }
__device__ __forceinline__ uint32_t mapa(uint32_t a, uint32_t rank) { uint32_t d; asm("mapa.shared::cluster.u32 %0, %1, %2;" : "=r"(d) : "r"(a), "r"(rank)); return d; }
__device__ __forceinline__ void bulk_g2s(uint32_t dst, const void* src, int bytes, uint32_t bar) {
    asm volatile("cp.async.bulk.shared::cluster.global.mbarrier::complete_tx::bytes [%0], [%1], %2, [%3];" ::"r"(dst), "l"(src), "r"(bytes), "r"(bar) : "memory");
}
__device__ __forceinline__ void tma2d(uint32_t dst, const CUtensorMap* m, int c0, int c1, uint32_t bar) {
    asm volatile("cp.async.bulk.tensor.2d.shared::cluster.global.mbarrier::complete_tx::bytes [%0], [%1, {%3, %4}], [%2];" ::"r"(dst), "l"(m), "r"(bar), "r"(c0), "r"(c1) : "memory");
}
__device__ __forceinline__ void pf_tmap(const CUtensorMap* m) { asm volatile("prefetch.tensormap [%0];" ::"l"(m) : "memory"); }
__device__ __forceinline__ void bar_sync(int id, int n) { asm volatile("bar.sync %0, %1;" ::"r"(id), "r"(n) : "memory"); }
__device__ __forceinline__ uint4 ld_rlx4(const void* p) { uint4 v; asm volatile("ld.relaxed.gpu.global.v4.u32 {%0,%1,%2,%3}, [%4];" : "=r"(v.x), "=r"(v.y), "=r"(v.z), "=r"(v.w) : "l"(p) : "memory"); return v; }
__device__ __forceinline__ uint32_t ld_rlx(const void* p) { uint32_t v; asm volatile("ld.relaxed.gpu.global.u32 %0, [%1];" : "=r"(v) : "l"(p) : "memory"); return v; }
__device__ __forceinline__ void st_rlx(void* p, uint32_t v) { asm volatile("st.relaxed.gpu.global.u32 [%0], %1;" ::"l"(p), "r"(v) : "memory"); }
__device__ __forceinline__ uint32_t lds32(uint32_t a) { uint32_t v; asm volatile("ld.shared.u32 %0, [%1];" : "=r"(v) : "r"(a) : "memory"); return v; }
__device__ __forceinline__ uint32_t lds32v(uint32_t a) { uint32_t v; asm volatile("ld.volatile.shared.u32 %0, [%1];" : "=r"(v) : "r"(a) : "memory"); return v; }
__device__ __forceinline__ uint4 lds128v(uint32_t a) { uint4 v; asm volatile("ld.volatile.shared.v4.u32 {%0,%1,%2,%3}, [%4];" : "=r"(v.x), "=r"(v.y), "=r"(v.z), "=r"(v.w) : "r"(a) : "memory"); return v; }
__device__ __forceinline__ uint32_t lds16(uint32_t a) { uint16_t v; asm volatile("ld.shared.u16 %0, [%1];" : "=h"(v) : "r"(a) : "memory"); return v; }
__device__ __forceinline__ uint2 lds64(uint32_t a) { uint2 v; asm volatile("ld.shared.v2.u32 {%0,%1}, [%2];" : "=r"(v.x), "=r"(v.y) : "r"(a) : "memory"); return v; }
__device__ __forceinline__ uint4 lds128(uint32_t a) { uint4 v; asm volatile("ld.shared.v4.u32 {%0,%1,%2,%3}, [%4];" : "=r"(v.x), "=r"(v.y), "=r"(v.z), "=r"(v.w) : "r"(a) : "memory"); return v; }
__device__ __forceinline__ void sts16(uint32_t a, uint32_t v) { asm volatile("st.shared.u16 [%0], %1;" ::"r"(a), "h"((uint16_t)v) : "memory"); }
__device__ __forceinline__ void sts32(uint32_t a, uint32_t v) { asm volatile("st.shared.u32 [%0], %1;" ::"r"(a), "r"(v) : "memory"); }
__device__ __forceinline__ void sts64(uint32_t a, uint32_t x, uint32_t y) { asm volatile("st.shared.v2.u32 [%0], {%1,%2};" ::"r"(a), "r"(x), "r"(y) : "memory"); }
__device__ __forceinline__ void sts128(uint32_t a, uint32_t x, uint32_t y, uint32_t z, uint32_t w) { asm volatile("st.shared.v4.u32 [%0], {%1,%2,%3,%4};" ::"r"(a), "r"(x), "r"(y), "r"(z), "r"(w) : "memory"); }
__device__ __forceinline__ void st_async32(uint32_t a, uint32_t v, uint32_t bar) {
    asm volatile("st.async.shared::cluster.mbarrier::complete_tx::bytes.b32 [%0], %1, [%2];" ::"r"(a), "r"(v), "r"(bar) : "memory");
}
__device__ __forceinline__ void ldm4(uint32_t a, uint32_t& r0, uint32_t& r1, uint32_t& r2, uint32_t& r3) {
    asm volatile("ldmatrix.sync.aligned.m8n8.x4.shared.b16 {%0,%1,%2,%3}, [%4];" : "=r"(r0), "=r"(r1), "=r"(r2), "=r"(r3) : "r"(a) : "memory");
}
__device__ __forceinline__ void ldm4t(uint32_t a, uint32_t& r0, uint32_t& r1, uint32_t& r2, uint32_t& r3) {
    asm volatile("ldmatrix.sync.aligned.m8n8.x4.trans.shared.b16 {%0,%1,%2,%3}, [%4];" : "=r"(r0), "=r"(r1), "=r"(r2), "=r"(r3) : "r"(a) : "memory");
}
__device__ __forceinline__ void ldm2(uint32_t a, uint32_t& r0, uint32_t& r1) {
    asm volatile("ldmatrix.sync.aligned.m8n8.x2.shared.b16 {%0,%1}, [%2];" : "=r"(r0), "=r"(r1) : "r"(a) : "memory");
}
__device__ __forceinline__ void stm4(uint32_t a, uint32_t r0, uint32_t r1, uint32_t r2, uint32_t r3) {
    asm volatile("stmatrix.sync.aligned.m8n8.x4.shared.b16 [%0], {%1,%2,%3,%4};" ::"r"(a), "r"(r0), "r"(r1), "r"(r2), "r"(r3) : "memory");
}
__device__ __forceinline__ void mma_bf(float& c0, float& c1, float& c2, float& c3, uint32_t a0, uint32_t a1, uint32_t a2, uint32_t a3, uint32_t b0, uint32_t b1) {
    asm volatile("mma.sync.aligned.m16n8k16.row.col.f32.bf16.bf16.f32 {%0,%1,%2,%3},{%4,%5,%6,%7},{%8,%9},{%0,%1,%2,%3};"
                 : "+f"(c0), "+f"(c1), "+f"(c2), "+f"(c3) : "r"(a0), "r"(a1), "r"(a2), "r"(a3), "r"(b0), "r"(b1));
}
__device__ __forceinline__ void mma_bf(float (&c)[4], uint32_t a0, uint32_t a1, uint32_t a2, uint32_t a3, uint32_t b0, uint32_t b1) { mma_bf(c[0], c[1], c[2], c[3], a0, a1, a2, a3, b0, b1); }
__device__ __forceinline__ void mma_h(float (&c)[4], uint32_t a0, uint32_t a1, uint32_t a2, uint32_t a3, uint32_t b0, uint32_t b1) {
    asm volatile("mma.sync.aligned.m16n8k16.row.col.f32.f16.f16.f32 {%0,%1,%2,%3},{%4,%5,%6,%7},{%8,%9},{%0,%1,%2,%3};"
                 : "+f"(c[0]), "+f"(c[1]), "+f"(c[2]), "+f"(c[3]) : "r"(a0), "r"(a1), "r"(a2), "r"(a3), "r"(b0), "r"(b1));
}
__device__ __forceinline__ void mma_bf8(float (&c)[4], uint32_t a0, uint32_t a1, uint32_t b0) {
    asm volatile("mma.sync.aligned.m16n8k8.row.col.f32.bf16.bf16.f32 {%0,%1,%2,%3},{%4,%5},{%6},{%0,%1,%2,%3};"
                 : "+f"(c[0]), "+f"(c[1]), "+f"(c[2]), "+f"(c[3]) : "r"(a0), "r"(a1), "r"(b0));
}
__device__ __forceinline__ uint32_t pack_bf(float lo, float hi) { uint32_t r; asm("cvt.rn.bf16x2.f32 %0, %1, %2;" : "=r"(r) : "f"(hi), "f"(lo)); return r; }
__device__ __forceinline__ uint32_t pack_h(float lo, float hi) { uint32_t r; asm("cvt.rn.f16x2.f32 %0, %1, %2;" : "=r"(r) : "f"(hi), "f"(lo)); return r; }
__device__ __forceinline__ float bf_lo(uint32_t w) { return __uint_as_float(w << 16); }
__device__ __forceinline__ float bf_hi(uint32_t w) { return __uint_as_float(w & 0xFFFF0000u); }
__device__ __forceinline__ float bf_round(float x) { return bf_lo(pack_bf(x, 0.f)); }
__device__ __forceinline__ uint32_t badd(uint32_t a, uint32_t b) { uint32_t r; asm("add.rn.bf16x2 %0, %1, %2;" : "=r"(r) : "r"(a), "r"(b)); return r; }
__device__ __forceinline__ uint32_t bsub(uint32_t a, uint32_t b) { uint32_t r; asm("sub.rn.bf16x2 %0, %1, %2;" : "=r"(r) : "r"(a), "r"(b)); return r; }
__device__ __forceinline__ uint32_t bmul(uint32_t a, uint32_t b) { uint32_t r; asm("mul.rn.bf16x2 %0, %1, %2;" : "=r"(r) : "r"(a), "r"(b)); return r; }
__device__ __forceinline__ uint32_t bfma(uint32_t a, uint32_t b, uint32_t c) { uint32_t r; asm("fma.rn.bf16x2 %0, %1, %2, %3;" : "=r"(r) : "r"(a), "r"(b), "r"(c)); return r; }
__device__ __forceinline__ uint32_t prmt(uint32_t a, uint32_t b, uint32_t s) { uint32_t r; asm("prmt.b32 %0, %1, %2, %3;" : "=r"(r) : "r"(a), "r"(b), "r"(s)); return r; }
__device__ __forceinline__ float ex2f(float x) { float r; asm("ex2.approx.ftz.f32 %0, %1;" : "=f"(r) : "f"(x)); return r; }
__device__ __forceinline__ float rcpf(float x) { float r; asm("rcp.approx.ftz.f32 %0, %1;" : "=f"(r) : "f"(x)); return r; }
__device__ __forceinline__ float silu_f(float x) { return x * rcpf(1.f + ex2f(-1.4426950408889634f * x)); }
__device__ __forceinline__ uint32_t norm2(uint32_t x, uint32_t m, uint32_t hi, uint32_t lo) { uint32_t d = bsub(x, m); return bfma(d, hi, bmul(d, lo)); }
__device__ __forceinline__ uint32_t clk32() { uint32_t c; asm volatile("mov.u32 %0, %%clock;" : "=r"(c)); return c; }
__device__ __forceinline__ void spin_until(uint32_t t0, int dt) {
#pragma unroll 1
    while ((int)(clk32() - t0) < dt) __nanosleep(32);
}
__device__ __forceinline__ float sqrt_ap(float x) { float r; asm("sqrt.approx.ftz.f32 %0, %1;" : "=f"(r) : "f"(x)); return r; }

__device__ __forceinline__ void cp16(uint32_t dst, const void* src) { asm volatile("cp.async.cg.shared.global [%0], [%1], 16;" ::"r"(dst), "l"(src) : "memory"); }
__device__ __forceinline__ void pf_l2(const void* p) { asm volatile("cp.async.bulk.prefetch.L2.global [%0], 16;" ::"l"(p) : "memory"); }
__device__ __forceinline__ void bulk_s2g(void* dst, uint32_t src, int bytes) {
    asm volatile("cp.async.bulk.global.shared::cta.bulk_group [%0], [%1], %2;" ::"l"(dst), "r"(src), "r"(bytes) : "memory");
}
__device__ __forceinline__ uint32_t ld_acq(const void* p) { uint32_t v; asm volatile("ld.acquire.gpu.global.u32 %0, [%1];" : "=r"(v) : "l"(p) : "memory"); return v; }
__device__ __forceinline__ void red_add(void* p) { asm volatile("red.relaxed.gpu.global.add.u32 [%0], 1;" ::"l"(p) : "memory"); }
__device__ __forceinline__ void fence_async() { asm volatile("fence.proxy.async.shared::cta;" ::: "memory"); }
__device__ __forceinline__ void fence_async_g() { asm volatile("fence.proxy.async.global;" ::: "memory"); }
__device__ __forceinline__ void red_rel(void* p) { asm volatile("red.release.gpu.global.add.u32 [%0], 1;" ::"l"(p) : "memory"); }
__device__ __forceinline__ void wait_count(const uint32_t* p, uint32_t want) {
#pragma unroll 1
    for (int it = 0; it < SPIN_LIMIT && ld_rlx(p) != want; it++) __nanosleep(20);
}
__device__ __forceinline__ uint32_t ld_stat(const uint32_t* p, uint32_t tag) {
    uint32_t v = 0;
#pragma unroll 1
    for (int it = 0; it < SPIN_LIMIT; it++) {
        v = ld_rlx(p);
        if ((v >> 31) == tag) break;
    }
    return v & 0x7FFFFFFFu;
}
__device__ __forceinline__ uint32_t hadd(uint32_t a, uint32_t b) { uint32_t r; asm("add.rn.f16x2 %0, %1, %2;" : "=r"(r) : "r"(a), "r"(b)); return r; }
__device__ __forceinline__ float h_lo(uint32_t w) { return __half2float(__ushort_as_half((unsigned short)w)); }
__device__ __forceinline__ float h_hi(uint32_t w) { return __half2float(__ushort_as_half((unsigned short)(w >> 16))); }
__device__ __forceinline__ uint32_t x0_chunk(uint32_t xb, int c) { return xb + ((c & 1) ? X0_ODD + 120 : 128) + 8 * c; }

struct cf { float x, y; };
__device__ __forceinline__ cf cmul(cf a, cf b) { return {a.x * b.x - a.y * b.y, a.x * b.y + a.y * b.x}; }
__device__ __forceinline__ cf csq(cf a) { return {a.x * a.x - a.y * a.y, (a.x + a.x) * a.y}; }
__device__ __forceinline__ cf cpow_direct(float zr2, float zi, float l) {
    const float mag = ex2f(zr2 * l), th = zi * l;
    return {mag * __cosf(th), mag * __sinf(th)};
}
__device__ __forceinline__ __half2 as_h2(uint32_t v) { return *reinterpret_cast<__half2*>(&v); }
__device__ __forceinline__ uint32_t as_u32(__half2 v) { return *reinterpret_cast<uint32_t*>(&v); }
struct hm { uint32_t v, s; };
__device__ __forceinline__ hm mk_hm(cf a) {
    const uint32_t v = pack_h(a.x, a.y);
    return {v, prmt(v, v, 0x1032) ^ 0x8000u};
}
__device__ __forceinline__ uint32_t hcmul(uint32_t x, hm y) {
    const __half2 xx = as_h2(x);
    return as_u32(__hfma2(__high2half2(xx), as_h2(y.s), __hmul2(__low2half2(xx), as_h2(y.v))));
}

struct KParams { uint32_t are, aim, bre, bim, cre, cim, ldt; };
__device__ __forceinline__ KParams kgen_load(const Hot& p, int ch, int half, int lane) {
    const uint32_t po = ch * 64 + half * 32 + lane;
    KParams k;
    k.are = __ldg((const uint32_t*)p.are + po); k.aim = __ldg((const uint32_t*)p.aim + po);
    k.bre = __ldg((const uint32_t*)p.bre + po); k.bim = __ldg((const uint32_t*)p.bim + po);
    k.cre = __ldg((const uint32_t*)p.cre + po); k.cim = __ldg((const uint32_t*)p.cim + po);
    k.ldt = __ldg((const uint16_t*)p.logdt + ch + (lane & p.tn.zero));
    return k;
}

__device__ __forceinline__ void kgen(KParams kp, uint32_t scr, uint32_t os, int c0, int c1, uint32_t pause) {
    const int lane = threadIdx.x & 31;
    const float dt = bf_round(ex2f(bf_lo(kp.ldt) * 1.4426950408889634f));
    const cf w0 = cmul({bf_lo(kp.cre), bf_lo(kp.cim)}, {dt * bf_lo(kp.bre), dt * bf_lo(kp.bim)});
    const cf w1 = cmul({bf_hi(kp.cre), bf_hi(kp.cim)}, {dt * bf_hi(kp.bre), dt * bf_hi(kp.bim)});
    uint32_t eb = __reduce_max_sync(~0u, __float_as_uint(fmaxf(fmaxf(fabsf(w0.x), fabsf(w0.y)), fmaxf(fabsf(w1.x), fabsf(w1.y))))) & 0x7F800000u;
    eb = min(max(eb, 0x00800000u), 0x7E800000u);
    const float sc = __uint_as_float(0x7F000000u - eb);
    float k0 = c0 ? 0.f : w0.x + w1.x;
#pragma unroll
    for (int o = 16; o > 0; o >>= 1) k0 += __shfl_xor_sync(~0u, k0, o);
    float d[5][4];
#pragma unroll
    for (int i = 0; i < 5; i++) d[i][0] = d[i][1] = d[i][2] = d[i][3] = 0.f;
    const int mi = lane >> 3, j = lane & 7;
    const uint32_t st0 = scr + mi * 128 + ((j ^ mi) << 4), st1 = st0 ^ 64;
    const uint32_t la = scr + (lane & 15) * 128 + (((lane >> 4) ^ j) << 4), lb = scr + j * 128 + ((mi ^ j) << 4);
    auto st = [&](int row, uint32_t a, uint32_t b, uint32_t c, uint32_t e) { stm4(((row & 4) ? st1 : st0) + row * 128, a, b, c, e); };
#pragma unroll 1
    for (int c = c0; c < c1; c++) {
        if (c > c0 && pause) mbar_wait(pause, 0);
        const float zr2 = dt * (c ? bf_hi(kp.are) : bf_lo(kp.are)) * 1.4426950408889634f;
        const float zi = dt * (c ? bf_hi(kp.aim) : bf_lo(kp.aim));
        const cf w = {(c ? w1.x : w0.x) * sc, (c ? w1.y : w0.y) * sc};
        const cf a1 = cpow_direct(zr2, zi, 1.f), a256 = cpow_direct(zr2, zi, 256.f);
        uint32_t a[4][4];
        {
            const cf a16 = cpow_direct(-zr2, zi, -16.f);
            const cf a32 = csq(a16), a48 = cmul(a32, a16), a64 = csq(a32), a128 = csq(a64), a192 = cmul(a128, a64);
            const uint32_t p1 = pack_h(a16.x, a16.y), p2 = pack_h(a32.x, a32.y), p3 = pack_h(a48.x, a48.y);
            const hm q1 = mk_hm(a64), q2 = mk_hm(a128), q3 = mk_hm(a192);
            __syncwarp();
            st(0, 0x00003C00u, p1, p2, p3);
            st(4, q1.v, hcmul(p1, q1), hcmul(p2, q1), hcmul(p3, q1));
            st(8, q2.v, hcmul(p1, q2), hcmul(p2, q2), hcmul(p3, q2));
            st(12, q3.v, hcmul(p1, q3), hcmul(p2, q3), hcmul(p3, q3));
            __syncwarp();
#pragma unroll
            for (int k = 0; k < 4; k++) ldm4(la ^ (k * 32), a[k][0], a[k][1], a[k][2], a[k][3]);
        }
        auto tile = [&](int T, int row) {
#pragma unroll
            for (int kp2 = 0; kp2 < 2; kp2++) {
                uint32_t b0, b1, b2, b3;
                ldm4((lb ^ (kp2 * 64)) + row * 128, b0, b1, b2, b3);
                mma_h(d[T], a[2 * kp2][0], a[2 * kp2][1], a[2 * kp2][2], a[2 * kp2][3], b0, b1);
                mma_h(d[T], a[2 * kp2 + 1][0], a[2 * kp2 + 1][1], a[2 * kp2 + 1][2], a[2 * kp2 + 1][3], b2, b3);
            }
        };
        const cf a2 = csq(a1), a4 = csq(a2), a8 = csq(a4), a12 = cmul(a8, a4);
        const cf u1 = cmul(w, a1), u2 = cmul(w, a2), u3 = cmul(u2, a1), u4 = cmul(w, a4);
        uint32_t v[16];
        v[0] = pack_h(u1.x, u1.y); v[1] = pack_h(u2.x, u2.y); v[2] = pack_h(u3.x, u3.y); v[3] = pack_h(u4.x, u4.y);
        const hm m4 = mk_hm(a4), m8 = mk_hm(a8), m12 = mk_hm(a12);
#pragma unroll
        for (int i = 0; i < 4; i++) { v[4 + i] = hcmul(v[i], m4); v[8 + i] = hcmul(v[i], m8); v[12 + i] = hcmul(v[i], m12); }
        const hm m256 = mk_hm(a256);
        __syncwarp();
#pragma unroll
        for (int i = 0; i < 4; i++) st(4 * i, v[4 * i], v[4 * i + 1], v[4 * i + 2], v[4 * i + 3]);
        st(16, hcmul(v[1], m256), hcmul(v[3], m256), hcmul(v[5], m256), hcmul(v[7], m256));
        st(20, hcmul(v[9], m256), hcmul(v[11], m256), hcmul(v[13], m256), hcmul(v[15], m256));
        __syncwarp();
        tile(0, 0); tile(1, 8); tile(2, 16);
        const cf a512 = csq(a256), a768 = cmul(a512, a256), a1024 = csq(a512);
        const cf a1280 = cmul(a1024, a256), a1536 = csq(a768), a1792 = cmul(a1024, a768);
        const hm m512 = mk_hm(a512), m768 = mk_hm(a768);
        const hm n0 = mk_hm(a1024), n1 = mk_hm(a1280), n2 = mk_hm(a1536), n3 = mk_hm(a1792);
        __syncwarp();
        st(0, hcmul(v[3], m512), hcmul(v[7], m512), hcmul(v[11], m512), hcmul(v[15], m512));
        st(4, hcmul(v[3], m768), hcmul(v[7], m768), hcmul(v[11], m768), hcmul(v[15], m768));
        st(8, hcmul(v[7], n0), hcmul(v[15], n0), hcmul(v[7], n1), hcmul(v[15], n1));
        st(12, hcmul(v[7], n2), hcmul(v[15], n2), hcmul(v[7], n3), hcmul(v[15], n3));
        __syncwarp();
        tile(3, 0); tile(4, 8);
    }
    __syncwarp();
#pragma unroll
    for (int i = 0; i < 5; i++) sts128(os + i * 512 + lane * 16, __float_as_uint(d[i][0]), __float_as_uint(d[i][1]), __float_as_uint(d[i][2]), __float_as_uint(d[i][3]));
    sts64(os + 2560, eb, __float_as_uint(k0));
}

__device__ __forceinline__ void ktables(uint32_t os, int ostep, int np, uint32_t kr, uint32_t kt, uint32_t kinf, int part) {
    const int lane = threadIdx.x & 31, g = lane >> 2, t = lane & 3;
    uint32_t eb = 0;
    float k0 = 0.f, f[4];
#pragma unroll
    for (int q = 0; q < 4; q++) {
        uint2 v = make_uint2(0u, 0u);
        if (q < np) v = lds64(os + q * ostep + 2560);
        eb = max(eb, v.x);
        k0 += __uint_as_float(v.y);
        f[q] = __uint_as_float(v.x);
    }
    const float rs = __uint_as_float(0x7F000000u - eb);
#pragma unroll
    for (int q = 0; q < 4; q++) f[q] *= rs;
#pragma unroll 1
    for (int i = (part & 1) ? 0 : 2; i < ((part & 2) ? 5 : 3); i++) {
        float a0 = 0.f, a1 = 0.f, a2 = 0.f, a3 = 0.f;
        uint4 v[4];
#pragma unroll
        for (int q = 0; q < 4; q++) {
            v[q] = make_uint4(0u, 0u, 0u, 0u);
            if (q < np) v[q] = lds128(os + q * ostep + i * 512 + lane * 16);
        }
#pragma unroll
        for (int q = 0; q < 4; q++) { a0 += __uint_as_float(v[q].x) * f[q]; a1 += __uint_as_float(v[q].y) * f[q]; a2 += __uint_as_float(v[q].z) * f[q]; a3 += __uint_as_float(v[q].w) * f[q]; }
        const int sg = 32 >> max(i - 1, 0);
        const uint32_t o = kr + 4 + (i < 2 ? 16 * i : 256 * i) + sg * g + (i < 3 ? 8 : 128) * (t >> 1) + (i < 4 ? 4 : 64) * (t & 1);
        sts32(o, pack_h(a0, a1));
        sts32(o + 8 * sg, pack_h(a2, a3));
    }
    sts32(kr, pack_h(0.f, k0 * rs));
    __syncwarp();
    if (part & 1) {
        uint32_t w0[4], w1[4], a[2], b[2];
#pragma unroll
        for (int r = 0; r < 4; r++) { w0[r] = lds32(kr + 4 * lane + 128 * r); w1[r] = lds32(kr + 4 * lane + 128 * r + 4); }
#pragma unroll
        for (int r = 0; r < 2; r++) { a[r] = lds32(kr + 512 + 4 * lane + 128 * r); b[r] = lds32(kr + 516 + 4 * lane + 128 * r); }
#pragma unroll
        for (int r = 0; r < 4; r++) sts64(kt + 8 * lane + 256 * r + 32, prmt(w0[r], w0[r], 0x1032), prmt(w0[r], w1[r], 0x3254));
        if (lane == 31) b[1] = pack_h(h_lo(b[1]) - h_hi(b[1]), 0.f);
#pragma unroll
        for (int r = 0; r < 2; r++)
            sts128(kt + 4 * 264 + 16 * lane + 512 * r, prmt(a[r], a[r], (r == 0 && lane == 0) ? 0x1032 : 0x3232), prmt(a[r], a[r], 0x3232), prmt(a[r], b[r], 0x3254), prmt(b[r], b[r], 0x1032));
        if (lane < 24) sts32(kt + 4 * (lane < 8 ? lane : 512 + lane), 0u);
    }
    if (part & 2) {
        const uint32_t k512 = lds16(kr + 2 * 385), k1024 = lds16(kr + 2 * 513);
        if (lane == 0) {
            sts128(kinf, eb, __float_as_uint(h_lo(k512)), k1024, 0u);
            sts16(kr + 2 * 512, pack_h(h_lo(lds16(kr + 2 * 512)) - h_lo(k1024), 0.f));
        }
#pragma unroll
        for (int r = 0; r < 3; r++)
            if (r < 2 || lane < 26) sts128(kt + KT_P4 + 16 * lane + 512 * r, 0u, 0u, 0u, 0u);
        __syncwarp();
        uint32_t x0[5], x1[5], y0[5], y1[5];
#pragma unroll
        for (int r = 0; r < 5; r++) {
            const int m = min(126 + lane + 32 * r, 256);
            x0[r] = lds16(kr + 2 * (257 + m)); x1[r] = lds16(kr + 2 * (259 + m)); y0[r] = lds16(kr + 2 * (385 + m)); y1[r] = lds16(kr + 2 * (387 + m));
        }
#pragma unroll
        for (int r = 0; r < 5; r++) {
            const int m = 126 + lane + 32 * r;
            if (m < 128) x0[r] = y0[r] = 0;
            if (m > 253) x1[r] = 0;
            if (m > 254) y1[r] = 0;
            if (m < 256) sts32(kt + KT_P4 + 4 * (((m - 96) & ~3) | ((m & 1) << 1) | ((m >> 1) & 1)), x0[r] | (x1[r] << 16));
            if (m < 257) sts32(kt + KT_P8 + 4 * (m - 96), y0[r] | (y1[r] << 16));
        }
    }
    __syncwarp();
}

__device__ __forceinline__ void mma_hc(float (&d)[4], const float (&c)[4], uint32_t a0, uint32_t a1, uint32_t a2, uint32_t a3, uint32_t b0, uint32_t b1) {
    asm volatile("mma.sync.aligned.m16n8k16.row.col.f32.f16.f16.f32 {%0,%1,%2,%3},{%4,%5,%6,%7},{%8,%9},{%10,%11,%12,%13};"
                 : "=f"(d[0]), "=f"(d[1]), "=f"(d[2]), "=f"(d[3]) : "r"(a0), "r"(a1), "r"(a2), "r"(a3), "r"(b0), "r"(b1), "f"(c[0]), "f"(c[1]), "f"(c[2]), "f"(c[3]));
}
template <int Q0, int Q1>
__device__ __forceinline__ void sweep_steps(float (&w)[5][4], const uint32_t (&R)[66], uint32_t xa, uint32_t (&x)[5], uint32_t z) {
#pragma unroll
    for (int q = Q0; q <= Q1; q++) {
        uint32_t n0, n1;
        ldm2(xa + 16 * (q + 1), n0, n1);
        const uint32_t a2 = x[0] | z, a3 = x[1] | z;
#pragma unroll
        for (int j = 0; j < 4; j++) {
            const int s = 8 * j + 8 - q;
            if (q == 1) mma_hc(w[j], w[j + 1], x[1], x[2], a2, a3, R[2 * s], R[2 * s + 1]);
            else mma_h(w[j], x[1], x[2], a2, a3, R[2 * s], R[2 * s + 1]);
        }
        if (q == 8) {
            const float zero[4] = {0.f, 0.f, 0.f, 0.f};
            mma_hc(w[4], zero, x[1], x[2], a2, a3, R[64], R[65]);
        }
        x[0] = x[2]; x[1] = x[3]; x[2] = x[4]; x[3] = n0; x[4] = n1;
    }
}

__device__ __forceinline__ void box_round(uint32_t xb, uint32_t fa, int rho, int lane) {
    if (rho == 6) {
        const int a = lane >> 3, j = lane & 7;
        sts128(fa + 3328 * (lane >> 4) + 16 * ((lane & 15) < 15 ? (lane & 15) : 207), 0u, 0u, 0u, 0u);
        sts128(fa + FB9E + 1168 * a + 16 * (j < 7 ? j : 71 + (a & 1)), 0u, 0u, 0u, 0u);
        __syncwarp();
    }
    const int c = rho < 6 ? 32 * rho + lane : -1;
    const uint4 pv = lds128(x0_chunk(xb, c - 1)), ow = lds128(x0_chunk(xb, c));
    const uint2 nx = lds64(x0_chunk(xb, c + 1));
    const uint32_t P[9] = {pv.y, pv.z, pv.w, ow.x, ow.y, ow.z, ow.w, nx.x, nx.y};
    uint32_t Q[8], b3[6], b5[4];
#pragma unroll
    for (int k = 0; k < 8; k++) Q[k] = prmt(P[k], P[k + 1], 0x5432);
#pragma unroll
    for (int k = 0; k < 6; k++) b3[k] = hadd(hadd(Q[k], Q[k + 1]), P[k + 1]);
#pragma unroll
    for (int k = 0; k < 4; k++) b5[k] = hadd(b3[k + 2], hadd(P[k + 2], P[k + 4]));
    sts128(fa + FB5 + 240 + 16 * c, b5[0], b5[1], b5[2], b5[3]);
    sts128(fa + FB3 + 240 + 16 * c, b3[0], b3[1], b3[2], b3[3]);
    if (rho < 4 || rho == 6) {
        uint32_t b7[4], b9[4];
#pragma unroll
        for (int k = 0; k < 4; k++) {
            b7[k] = hadd(b5[k], hadd(Q[k + 1], Q[k + 4]));
            b9[k] = hadd(b7[k], hadd(P[k + 1], P[k + 5]));
        }
        const uint32_t ad = fa + ((c & 1) ? FB9O + 120 : FB9E + 112) + 8 * c;
        sts128(ad, b9[0], b9[1], b9[2], b9[3]);
        sts128(ad + (FB7E - FB9E), b7[0], b7[1], b7[2], b7[3]);
    }
}

__global__ void __cluster_dims__(2, 1, 1) __launch_bounds__(NTHREADS, 1) fused_kernel(const Hot p, const __grid_constant__ Maps m) {
    extern __shared__ __align__(1024) char smem[];
    const uint32_t t0 = clk32();
    const int tid = (threadIdx.x + 32 * 0) & (NTHREADS - 1), lane = tid & 31, warp = __shfl_sync(~0u, tid >> 5, 0), bid = blockIdx.x;
    const uint32_t S = smem_u32(smem), z = (uint32_t)p.tn.zero;
    const bool down = bid < NDOWN, rowcta = bid < NMAIN, big = rowcta && !down;
    const int xd = rowcta ? bid : 142 + ((bid - NMAIN) >> 1);
    const int slot = warp < 8 ? (warp & 3) : 4;
    const bool has = warp < 8 ? (rowcta || (slot >> 1) == (bid & 1)) : (big && warp < 12);
    const int ch = slot < 4 ? 4 * xd + slot : 512 + bid - NDOWN;
    KParams kp;
    if (has) kp = kgen_load(p, ch, warp < 8 ? warp >> 2 : (warp >> 1) & 1, lane);
    if (elect()) {
#pragma unroll 1
        for (int i = warp; i < B_COUNT; i += 16) {
            const uint32_t c = i < 16 ? (uint32_t)((big ? 0x1411115555412290ull : 0x1411114444412290ull) >> (4 * i)) & 15 : 1;
            mbar_init(S + i * 8, c ? c : NTHREADS);
        }
        asm volatile("fence.mbarrier_init.release.cluster;" ::: "memory");
    }
    if (rowcta) {
#pragma unroll 1
        for (int i = tid; i < 1224; i += NTHREADS)
            cp16(S + SM_ROWS + 16 * (i + min((i * 911) >> 16, 16)), i < 1152 ? (const uint4*)p.u + bid * 1152 + i : (const uint4*)p.wr + (i - 1152));
    }
    if (tid >= 256 && tid < 336) {
        const int i = tid - 256;
        if (i < 64 || big) sts128(S + (i < 64 ? SM_X0 + (i >> 4) * X0_STRIDE : SM_EX) + ((i & 8) ? X0_ODD : 0) + 16 * (i & 7), 0u, 0u, 0u, 0u);
    }
    if (tid == 447) sts128(S + SM_ONES, 0x3F803F80u, 0x3F803F80u, 0x3F803F80u, 0x3F803F80u);
    __syncthreads();
    if (rowcta) asm volatile("cp.async.mbarrier.arrive.noinc.shared::cta.b64 [%0];" ::"r"(S + B_ROWS * 8) : "memory");
    if (warp == 15 && lane < 4) mbar_expect(S + (lane < 3 ? B_GX + lane : B_RED) * 8, 256);
    asm volatile("barrier.cluster.arrive.relaxed.aligned;" ::: "memory");
    const int g = lane >> 2, t = lane & 3, mi = lane >> 3, j = lane & 7;
    const uint32_t SW = S + (down ? SM_W_DOWN : SM_W_BIG);
    const int pr = bid >> 1, r = bid & 1, nsl = pr >= 54 ? 3 : 2, sl0 = pr < 54 ? 2 * pr : 3 * pr - 54;

    if (warp == 12) {
        if (elect()) {
            const int ng = 6 * nsl, ns = down ? 24 : ng;
            const CUtensorMap* mg = r ? &m.wu : &m.wg;
            pf_tmap(mg);
            if (down) pf_tmap(&m.wd);
            const uint32_t epoch = ld_rlx(&p.s->cnt[16 * 32]) + 1;
            spin_until(t0, p.tn.f_start);
            int done = 0;
#pragma unroll 1
            for (int s = 0; s < ns; s++) {
                if (s == ng) spin_until(t0, p.tn.f_t3);
                #pragma unroll 1
                for (int it = 0; it < SPIN_LIMIT; it++) {
                    const int w = s >= ng ? p.tn.w3 : ((int)(clk32() - t0) < p.tn.f_t2 ? p.tn.w1 : (nsl == 3 ? p.tn.w2b : p.tn.w2));
                    if (s - done < w) break;
                    if (mbar_test(S + (B_W + done) * 8, 0)) done++;
                    else __nanosleep(32);
                }
                const uint32_t bar = S + (B_W + s) * 8;
                uint32_t dst = SW + s * STAGE;
                if (s == 23) { mbar_wait(S + B_EM * 8, 0); fence_async(); dst = S + SM_W_LAST; }
                mbar_expect(bar, STAGE);
                const int u = (s * 43) >> 8;
                if (s < ng) tma2d(dst, mg, 32 * (sl0 + u), 96 * (s - 6 * u), bar);
                else tma2d(dst, &m.wd, 16 * pr, r * 2304 + 192 * (s - 12), bar);
            }
            if (rowcta) {
                mbar_wait(S + B_FD * 8, 0);
                fence_async();
#pragma unroll 1
                for (int q = 0; q < 4; q++) {
                    wait_count(&p.s->cnt[(8 + q) * 32], epoch * (uint32_t)D_);
                    fence_async_g();
                    mbar_expect(S + (B_YIN + q) * 8, 4608);
                    bulk_g2s(S + SM_STG + q * 4608, p.s->y + (32 * q + (bid >> 2)) * 4608 + (bid & 3) * 1152, 4608, S + (B_YIN + q) * 8);
                }
            }
        }
        return;
    }

    uint32_t epoch = 0;
    if (warp >= 8 || !rowcta) epoch = ld_rlx(&p.s->cnt[16 * 32] + (lane & z)) + 1;
    const uint32_t tag = epoch & 1;
    const int hw = warp < 12 ? warp - 8 : warp - 9;

    if (rowcta && warp >= 8 && warp < 15) {
        const uint32_t ad = S + SM_ROWS + (lane & 15) * ROW_STRIDE + 192 * hw + 16 * (lane >> 4);
        uint32_t wd = j ? S + SM_ROWS + 16 * ROW_STRIDE + 192 * hw + 16 * mi : S + SM_ONES;
        const uint32_t wstep = j ? 64 : 0, ones = 0x3F803F80u | z;
        float d1[4] = {0, 0, 0, 0}, d2[4] = {0, 0, 0, 0}, d3[4] = {0, 0, 0, 0}, d4[4] = {0, 0, 0, 0};
        mbar_wait(S + B_ROWS * 8, 0);
#pragma unroll
        for (int kk = 0; kk < 3; kk++) {
            uint32_t w[4];
            ldm4(wd, w[0], w[1], w[2], w[3]);
            wd += wstep;
#pragma unroll
            for (int e = 0; e < 2; e++) {
                uint32_t a0, a1, a2, a3;
                ldm4(ad + 64 * kk + 32 * e, a0, a1, a2, a3);
                mma_bf(d1, a0, a1, a2, a3, w[2 * e], w[2 * e + 1]);
                mma_bf(d2, a0, a1, a2, a3, a0, a2);
                mma_bf(d3, a0, a1, a2, a3, a1, a3);
                mma_bf(d4, ones, ones ^ z, ones + z, ones - z, w[2 * e], w[2 * e + 1]);
            }
        }
        float* part = (float*)(smem + SM_PART + hw * 256) + g * 4;
        if (t == 0) {
            *(float2*)part = make_float2(d1[0], d1[1]);
            *(float2*)(part + 32) = make_float2(d1[2], d1[3]);
            part[3] = d4[1];
            part[35] = d4[1];
        }
        if (t == (g >> 1)) {
            part[2] = (g & 1) ? d2[1] : d2[0];
            part[34] = (g & 1) ? d3[3] : d3[2];
        }
        bar_sync(1, 192);
        if (hw == 0 && lane < 16) {
            float4 s = *(const float4*)(smem + SM_PART + lane * 16);
#pragma unroll
            for (int w = 1; w < 6; w++) {
                const float4 v = *(const float4*)(smem + SM_PART + w * 256 + lane * 16);
                s.x += v.x; s.y += v.y; s.z += v.z; s.w += v.w;
            }
            const float mean = s.x * (1.f / 576.f);
            const float var = fmaxf(s.z * (1.f / 576.f) - mean * mean, 0.f);
            const uint32_t mm = pack_bf(mean, mean);
            const float mu = bf_lo(mm), sd = bf_round(sqrt_ap(bf_round(bf_round(var) + 1e-5f))), ri = rcpf(sd);
            const uint32_t hi = pack_bf(ri, ri);
            const float rl = ri - bf_lo(hi);
            sts16(S + SM_STA + 2 * lane, mm); sts16(S + SM_STA + 32 + 2 * lane, hi); sts16(S + SM_STA + 64 + 2 * lane, pack_bf(rl, rl));
            const uint32_t rb = pack_bf(0.f, (s.y - mu * s.w) * ri);
            const int row = bid * 16 + lane;
            p.s->stat[row] = (mm & 0xFFFFu) | __float_as_uint(sd) | (tag << 31);
            p.s->key[row] = ((rb ^ (((int)rb >> 31) | 0x80000000u)) & 0xFFFF0000u) | (tag << 15) | (2047 - row);
        }
        bar_sync(1, 192);
        if (tid == 256) mbar_arrive(S + B_P1 * 8);
        {
            const uint2 sm = lds64(S + SM_STA + 8 * t), sh = lds64(S + SM_STA + 32 + 8 * t), sl = lds64(S + SM_STA + 64 + 8 * t);
            const uint32_t at = S + SM_ROWS + (4 * (j >> 1) + (j & 1) + 2 * (mi & 1)) * ROW_STRIDE + 32 * hw + 16 * (mi >> 1);
            uint2* dst = (uint2*)p.s->x + (4 * hw + (g >> 2)) * 2048 + bid * 16 + (g & 3) * 4 + t;
            uint32_t r4[6][4];
#pragma unroll
            for (int n = 5; n >= 0; n--) ldm4t(at + 192 * n, r4[n][0], r4[n][1], r4[n][2], r4[n][3]);
#pragma unroll
            for (int n = 5; n >= 0; n--) {
                uint32_t o[4];
#pragma unroll
                for (int e = 0; e < 4; e++) {
                    const uint32_t v = (e & 1) ? norm2(r4[n][e], sm.y, sh.y, sl.y) : norm2(r4[n][e], sm.x, sh.x, sl.x);
                    o[e] = pack_h(bf_lo(v), bf_hi(v));
                }
                dst[n * 49152] = make_uint2((o[0] & ~1u) | tag, o[1]);
                dst[n * 49152 + 4096] = make_uint2((o[2] & ~1u) | tag, o[3]);
            }
        }
        bar_sync(1, 192);
    }

    if (has) {
        asm volatile("" : "+r"(kp.ldt), "+r"(kp.are), "+r"(kp.aim), "+r"(kp.bre), "+r"(kp.bim), "+r"(kp.cre), "+r"(kp.cim));

        const uint32_t scr = warp < 8 ? S + SM_STG + warp * KG_SCR : S + EX_HAND + hw * KG_SCR;
        kgen(kp, scr, warp < 8 ? scr : S + EX_FAR + hw * 2576, warp < 8 ? 0 : warp & 1, warp < 8 ? 2 : (warp & 1) + 1, rowcta ? S + B_P1 * 8 : 0);
        if (warp >= 8) { __syncwarp(); if (lane == 0) mbar_arrive(S + B_TAB * 8); }
    }
    if (warp < 8 || warp == 15) {
        if (warp < 8 ? has : big) {
            if (warp < 8) bar_sync(4 + slot, 64); else mbar_wait(S + B_TAB * 8, 0);
            ktables(warp < 8 ? S + SM_STG + slot * KG_SCR : S + EX_FAR, warp < 8 ? 4 * KG_SCR : 2576, warp < 8 ? 2 : 4, S + SM_XS + slot * KR_STRIDE,
                    S + (warp < 8 ? SM_KT + slot * KT_STRIDE : EX_KT), S + SM_KINF + slot * 16, warp < 8 ? 1 + (warp >> 2) : 3);
        }
        if (lane == 0) { mbar_arrive(S + B_KG * 8); if (warp == 15) mbar_arrive(S + B_TAB1 * 8); }
    }

    if (!rowcta && warp < 8 && !has) {
        const int w4 = (warp >> 2) * 2 + (warp & 1), i = 32 * w4 + lane;
#pragma unroll 1
        for (int pass = 1; pass < 2; pass++) {
        uint4 k[4];
        if (pass) spin_until(t0, p.tn.t_svc - 1500);
#pragma unroll 1
        for (int it = 0; it < SPIN_LIMIT; it++) {
            if (!pass) {
#pragma unroll
                for (int q = 0; q < 4; q++) k[q] = make_uint4(16 * i + 4 * q, 16 * i + 4 * q + 1, 16 * i + 4 * q + 2, 16 * i + 4 * q + 3);
                break;
            }
            uint32_t bad = 0;
#pragma unroll
            for (int q = 0; q < 4; q++) k[q] = ld_rlx4(&p.s->key[4 * i + 512 * q]);
#pragma unroll
            for (int q = 0; q < 4; q++) bad |= tag ? ~(k[q].x & k[q].y & k[q].z & k[q].w) : (k[q].x | k[q].y | k[q].z | k[q].w);
            if (!(bad & 0x8000u)) break;
            __nanosleep(100);
        }
        const uint32_t sc = S + SM_XS + ((bid & 1) ? 0 : 2) * KR_STRIDE;
        auto pk = [](uint32_t v) { return ((v >> 16) << 11) | (v & 2047u); };
        auto gt = [](uint32_t a, uint32_t b) { return (b - a) >> 31; };
        uint32_t mx = 0;
#pragma unroll
        for (int q = 0; q < 4; q++) {
            k[q] = make_uint4(pk(k[q].x), pk(k[q].y), pk(k[q].z), pk(k[q].w));
            mx = max(max(mx, max(k[q].x, k[q].y)), max(k[q].z, k[q].w));
        }
        bar_sync(1, 128);
        sts32(sc + 4 * i, mx);
        if (i == 0) sts32(sc + 1024, 0u);
        bar_sync(1, 128);
        int rank;
        {
            int c[8] = {0, 0, 0, 0, 0, 0, 0, 0};
#pragma unroll 1
            for (int q = 0; q < 32; q += 4) {
                uint4 v[4];
#pragma unroll
                for (int e = 0; e < 4; e++) v[e] = lds128(sc + 16 * (q + e));
#pragma unroll
                for (int e = 0; e < 4; e++) {
                    c[(2 * e) & 7] += gt(v[e].x, mx); c[(2 * e + 1) & 7] += gt(v[e].y, mx);
                    c[(2 * e + 4) & 7] += gt(v[e].z, mx); c[(2 * e + 5) & 7] += gt(v[e].w, mx);
                }
            }
            rank = ((c[0] + c[1]) + (c[2] + c[3])) + ((c[4] + c[5]) + (c[6] + c[7]));
        }
        if (rank == 7) sts32(sc + 1028, mx);
        bar_sync(1, 128);
        if (rank < 8) {
            const uint32_t lb = lds32(sc + 1028);
            int cq[4];
#pragma unroll
            for (int q = 0; q < 4; q++) cq[q] = (gt(lb, k[q].x) + gt(lb, k[q].y)) + (gt(lb, k[q].z) + gt(lb, k[q].w));
            const int c = 16 - ((cq[0] + cq[1]) + (cq[2] + cq[3]));
            uint32_t pos;
            asm volatile("atom.shared.add.u32 %0, [%1], %2;" : "=r"(pos) : "r"(sc + 1024), "r"(c) : "memory");
            pos = sc + 512 + 4 * pos;
#pragma unroll
            for (int q = 0; q < 4; q++) {
                if (k[q].x >= lb) { sts32(pos, k[q].x); pos += 4; }
                if (k[q].y >= lb) { sts32(pos, k[q].y); pos += 4; }
                if (k[q].z >= lb) { sts32(pos, k[q].z); pos += 4; }
                if (k[q].w >= lb) { sts32(pos, k[q].w); pos += 4; }
            }
        }
        bar_sync(1, 128);
        const int n = lds32(sc + 1024);
        if (i < n) {
            const uint32_t mine = lds32(sc + 512 + 4 * i);
            rank = 0;
#pragma unroll 1
            for (int q = 0; q < n; q += 4) {
                const uint4 v = lds128(sc + 512 + 4 * q);
                rank += ((v.x > mine) + (q + 1 < n && v.y > mine)) + ((q + 2 < n && v.z > mine) + (q + 3 < n && v.w > mine));
            }
            const uint32_t k32 = (mine >> 11) << 16, rb = (k32 ^ ((~(int)k32 >> 31) | 0x80000000u)) & 0xFFFF0000u;
            if (rank < 8 && pass) st_rlx(&p.s->sel[bid - NMAIN][rank], (2047 - (mine & 2047)) | (tag << 15) | (pack_bf(rcpf(1.f + ex2f(-1.4426950408889634f * __uint_as_float(rb))), 0.f) << 16));
        }
        }
    }

    if (warp == 13 || warp == 14) {
        const int i = tid - 416;
        if (i == 0) sts32(S + SM_EPOCH, tag);
        if (rowcta) {
            if (p.tn.t_marg <= 600) {
                const uint32_t back = ld_rlx(p.s->x + 2 * ((4 * hw + 2 + (g >> 2)) * 2048 + bid * 16 + (g & 3) * 4 + t));
                if (back == 0xFFFFFFFFu) __nanosleep(20);
            }
            spin_until(clk32(), p.tn.t_marg);
        } else {
            spin_until(t0, p.tn.t_svc);
        }
        const uint4* xa = (const uint4*)p.s->x + xd * 1024 + i;
        const int e = bid - NDOWN;
        const uint4* xe = (const uint4*)p.s->x + (128 + (e >> 2)) * 1024 + (i >> 1) * 8 + (e & 3) * 2 + (i & 1);
        const uint32_t da = S + SM_X0 + ((i >> 1) & 3) * X0_STRIDE + ((i & 1) ? X0_ODD : 0) + 128 + 16 * (i >> 3);
        const uint32_t de = S + SM_EX + ((i & 1) ? X0_ODD : 0) + 128 + 16 * (i >> 1);
        uint4 v[2][10];
        auto fetch = [&](int half) {
#pragma unroll
            for (int k = 0; k < 10; k++) {
                v[half][k].x = v[half][k].z = tag;
                if (k < 8 || big) v[half][k] = ld_rlx4(k < 8 ? xa + 512 * half + 64 * k : xe + 512 * half + 256 * (k - 8));
            }
        };
        fetch(0); fetch(1);
#pragma unroll
        for (int half = 0; half < 2; half++) {
#pragma unroll 1
            for (int it = 0; it < SPIN_LIMIT; it++) {
                uint32_t bad = 0;
#pragma unroll
                for (int k = 0; k < 10; k++) bad |= (v[half][k].x ^ tag) | (v[half][k].z ^ tag);
                if (!(bad & 1)) break;
                __nanosleep(60);
                fetch(half);
            }
#pragma unroll
            for (int k = 0; k < 10; k++)
                if (k < 8 || big) sts128(k < 8 ? da + 1024 * half + 128 * k : de + 1024 * half + 512 * (k - 8), v[half][k].x & ~1u, v[half][k].y, v[half][k].z & ~1u, v[half][k].w);
            __syncwarp();
            if (lane == 0) mbar_arrive(S + (B_X0 + half) * 8);
        }
    }

    if (warp < 12) {
        const bool cw = warp >= 8;
        if (has) {
            const uint32_t xb = S + (cw ? SM_EX : SM_X0 + slot * X0_STRIDE), kt = S + (cw ? EX_KT : SM_KT + slot * KT_STRIDE);
            const int g0 = cw ? warp - 8 : 0, g1 = cw ? warp - 7 : 4;
            const uint32_t park = (cw ? S + EX_HAND + g0 * 2048 : kt) + lane * 16;
            if (cw) mbar_wait(S + B_TAB1 * 8, 0);
            const uint4 ki = lds128(S + SM_KINF + slot * 16);
            const float inv = __uint_as_float(ki.x);
            if (warp >= 4) {
                const uint32_t fa = S + (cw ? EX_FAR : SM_FAR + slot * FAR_STRIDE);
                mbar_wait(S + (cw ? B_X1 : B_X0) * 8, 0);
                mbar_wait(S + B_KG * 8, 0);
#pragma unroll 1
                for (int rho = cw ? g0 : 0; rho < (cw ? 7 : 4); rho += cw ? 4 : 1) box_round(xb, fa, (!cw && rho == 3) ? 6 : rho, lane);
                if (cw) bar_sync(2, 128); else __syncwarp();
                const int dd = g - 2 * t, gf = g0 ? g0 : 1;
                const uint32_t tb0 = dd == -5 ? ki.z : (dd == -4 ? ki.z << 16 : 0u), tb1 = dd == 3 ? ki.z : (dd == 4 ? ki.z << 16 : 0u);
                uint32_t tad = xb + (mi == 1 ? 144 : mi == 2 ? 128 : X0_ODD + 128) + 16 * j + 512 * gf - 1024;
                uint32_t ad8 = fa + (mi == 0 ? FB9E : mi == 1 ? FB7O : mi == 2 ? FB9O + 16 : FB7E) + 112 - 16 * j + 512 * gf - 768;
                uint32_t ad4 = fa + ((mi & 1) ? FB3 : FB5) + 240 + 16 * (8 * (mi >> 1) - j) + 1024 * gf - 640;
                const uint32_t p4 = kt + KT_P4 + 16 * (g + t), p8 = kt + KT_P8 + 8 * (g + 2 * t);
#pragma unroll 1
                for (int grp = gf; grp < g1; grp++) {
                    float a[4][4], e[2][4], o[2][4];
#pragma unroll
                    for (int k = 0; k < 4; k++) a[0][k] = a[1][k] = a[2][k] = a[3][k] = e[0][k] = e[1][k] = o[0][k] = o[1][k] = 0.f;
                    {
                        if (!cw && grp == 2) {
                            mbar_wait(S + B_X1 * 8, 0);
#pragma unroll 1
                            for (int rho = 3; rho < 6; rho++) box_round(xb, fa, rho, lane);
                            __syncwarp();
                        }
                        {
                            uint4 A4[10];
#pragma unroll
                            for (int s = 0; s < 10; s++) A4[s] = lds128(p4 + 64 * s);
                            auto s4 = [&](int m) {
                                uint32_t b[4];
                                ldm4t(ad4 - 256 * m, b[0], b[1], b[2], b[3]);
#pragma unroll
                                for (int h = 1; h >= 0; h--)
#pragma unroll
                                    for (int i = 0; i < 4; i++) {
                                        const int s = 2 * m - 2 + 2 * i + (1 - h), k = m + (i & 2);
                                        if (k <= 5 && k >= ((i & 1) ? 0 : 1) && !((i & 1) && k == 5)) mma_h(a[i], A4[s >= 0 && s < 10 ? s : 0].x, A4[s >= 0 && s < 10 ? s : 0].y, A4[s >= 0 && s < 10 ? s : 0].z, A4[s >= 0 && s < 10 ? s : 0].w, b[2 * h], b[2 * h + 1]);
                                    }
                            };
                            auto tap = [&](int i) {
                                uint32_t b[4];
                                ldm4(tad + 128 * i, b[0], b[1], b[2], b[3]);
                                mma_h(a[i], b[0], b[1], b[2], b[3], tb1, tb0);
                            };
                            s4(1); s4(0); s4(2); s4(-1); tap(3); s4(-2);
                            if (grp >= 2) { s4(3); tap(0); s4(4); tap(1); s4(5); tap(2); }
                        }
                        {
                            uint32_t A8[9][4];
#pragma unroll
                            for (int k = 0; k < 9; k++) { A8[k][0] = lds32(p8 + 64 * k); A8[k][1] = lds32(p8 + 64 * k + 64); A8[k][2] = lds32(p8 + 64 * k + 4); A8[k][3] = lds32(p8 + 64 * k + 68); }
                            auto s8 = [&](int m) {
                                uint32_t b[4];
                                ldm4t(ad8 - 128 * m, b[0], b[1], b[2], b[3]);
                                mma_h(e[1], A8[m + 2][0], A8[m + 2][1], A8[m + 2][2], A8[m + 2][3], b[0], b[1]);
                                mma_h(o[1], A8[m + 2][0], A8[m + 2][1], A8[m + 2][2], A8[m + 2][3], b[2], b[3]);
                                if (m >= 0) {
                                    mma_h(e[0], A8[m >= 0 ? m : 0][0], A8[m >= 0 ? m : 0][1], A8[m >= 0 ? m : 0][2], A8[m >= 0 ? m : 0][3], b[0], b[1]);
                                    mma_h(o[0], A8[m >= 0 ? m : 0][0], A8[m >= 0 ? m : 0][1], A8[m >= 0 ? m : 0][2], A8[m >= 0 ? m : 0][3], b[2], b[3]);
                                }
                            };
                            s8(-2);
                            if (grp >= 2) {
                                s8(-1); s8(0); s8(1); s8(2);
                                if (grp >= 3) { s8(3); s8(4); s8(5); s8(6); }
                            }
                        }
                    }
                    tad += 512; ad8 += 512; ad4 += 1024;
#pragma unroll
                    for (int pp = 0; pp < 2; pp++) {
                        if (!cw) {
#pragma unroll 1
                            for (int it = 0; it < SPIN_LIMIT && !__all_sync(~0u, lds32v(park + (2 * pp + 1) * 512) == SLOT_FREE); it++) __nanosleep(32);
                        }
#pragma unroll
                        for (int i = 0; i < 2; i++)
                            sts128(park + (2 * pp + i) * 512, __float_as_uint((a[2 * pp + i][0] + e[pp][2 * i]) * inv), __float_as_uint((a[2 * pp + i][1] + e[pp][2 * i + 1]) * inv),
                                   __float_as_uint((a[2 * pp + i][2] + o[pp][2 * i]) * inv), __float_as_uint((a[2 * pp + i][3] + o[pp][2 * i + 1]) * inv));
                    }
                }
            }
            if ((warp & 12) != 4) {
                uint32_t R[66], x[5];
#pragma unroll
                for (int i = 0; i < 66; i++) R[i] = lds32(kt + 4 * (8 + g - 2 * t) + 32 * i);
                float w[5][4];
#pragma unroll
                for (int i = 0; i < 5; i++) w[i][0] = w[i][1] = w[i][2] = w[i][3] = 0.f;
                uint32_t xa = xb + ((lane & 8) ? X0_ODD + 16 : 16) + 16 * j + 512 * g0;
                uint2* yo = (uint2*)p.s->y + (32 * g0 + g) * 2304 + ch * 4 + t;
                mbar_wait(S + B_X0 * 8, 0);
                const uint32_t ytag = lds32(S + SM_EPOCH);
                if (g0 == 0) {
                    const uint32_t x01 = lds32(xb + 128);
                    const float c0 = lane == 31 ? __uint_as_float(ki.y) * inv * h_lo(x01) : 0.f, c1 = lane == 31 ? c0 + __uint_as_float(ki.y) * inv * h_hi(x01) : 0.f;
                    __syncwarp();
#pragma unroll
                    for (int i = 0; i < 4; i++) sts128(park + i * 512, 0u, 0u, i == 3 ? __float_as_uint(c0) : 0u, i == 3 ? __float_as_uint(c1) : 0u);
                }
                ldm2(xa - 16, x[1], x[0]);
                ldm2(xa, x[1], x[2]);
                ldm2(xa + 16, x[3], x[4]);
                uint32_t zz = z, pk = park;
                float sc = inv;
                const bool direct = g0 == 0;
                uint32_t dir = direct;
                asm volatile("" : "+r"(pk));
#pragma unroll 1
                for (int gq = g0; gq < g1; gq++) {
                    uint32_t pa = pk;
#pragma unroll 1
                    for (int n = 4; n > 0; n--) {
                        asm volatile("" : "+r"(zz), "+f"(sc), "+r"(pa), "+r"(dir));
                        sweep_steps<1, 5>(w, R, xa, x, zz);
                        uint4 v = lds128v(pa | (x[4] & zz));
                        sweep_steps<6, 8>(w, R, xa, x, zz);
                        xa += 128;
                        if (__any_sync(~0u, v.x == SLOT_FREE)) {
#pragma unroll 1
                            for (int it = 0; it < SPIN_LIMIT; it++) {
                                v = lds128v(pa);
                                if (!__any_sync(~0u, v.x == SLOT_FREE)) break;
                            }
                        }
                        const float y0 = fmaf(w[0][0], sc, __uint_as_float(v.x)), y1 = fmaf(w[0][1], sc, __uint_as_float(v.y));
                        const float y2 = fmaf(w[0][2], sc, __uint_as_float(v.z)), y3 = fmaf(w[0][3], sc, __uint_as_float(v.w));
                        if (dir) {
                            *yo = make_uint2((pack_bf(y0, y1) & ~1u) | ytag, pack_bf(y2, y3));
                            sts32(pa, SLOT_FREE);
                        } else {
                            sts128(pa, __float_as_uint(y0), __float_as_uint(y1), __float_as_uint(y2), __float_as_uint(y3));
                        }
                        yo += 18432;
                        pa += 512;
                    }
                    if (direct && lane == 0) red_add(&p.s->cnt[(8 + gq) * 32]);
                }
                __syncwarp();
                if (lane == 0) mbar_arrive(S + (direct ? B_EM : B_SP + g0) * 8);
                if (cw && g0 < 3) {
                    mbar_wait(S + (B_SP + g0 + 1) * 8, 0);
#pragma unroll
                    for (int i = 0; i < 4; i++) {
                        const uint4 v = lds128(park + 2048 + i * 512);
                        yo[i * 18432] = make_uint2((pack_bf(fmaf(w[i + 1][0], inv, __uint_as_float(v.x)), fmaf(w[i + 1][1], inv, __uint_as_float(v.y))) & ~1u) | ytag,
                                                   pack_bf(fmaf(w[i + 1][2], inv, __uint_as_float(v.z)), fmaf(w[i + 1][3], inv, __uint_as_float(v.w))));
                    }
                    if (lane == 0) red_add(&p.s->cnt[(8 + g0 + 1) * 32]);
                }
            }
        }
        if (rowcta && (warp & 12) == 4) {
            bar_sync(10, 128);
            const int i = tid - 128, rb0 = 16 * (bid >> 2), c0 = 144 * (bid & 3);
            if (i == 0) mbar_arrive(S + B_FD * 8);
#pragma unroll 3
            for (int v = i; v < 1152; v += 128) {
                const int row = (v * 3641) >> 16, vv = v - 18 * row;
                cp16(S + SM_ROWS + row * 304 + 16 * vv, (const uint4*)(p.u + (size_t)(512 * (row >> 4) + rb0 + (row & 15)) * D_ + c0) + vv);
            }
            if (i < 64) {
                const uint32_t sw = ld_stat(&p.s->stat[512 * (i >> 4) + rb0 + (i & 15)], lds32(S + SM_EPOCH));
                const float ri = rcpf(bf_hi(sw));
                const uint32_t hi = pack_bf(ri, ri);
                const float rl = ri - bf_lo(hi);
                sts128(S + SM_KT + KT_P4 + 16 * i, prmt(sw, sw, 0x1010), hi, pack_bf(rl, rl), 0u);
            }
            asm volatile("cp.async.wait_all;" ::: "memory");
            __syncwarp();
            if (lane == 0) mbar_arrive(S + B_OUT * 8);
        }
        if (!rowcta) return;

        const int rb0 = 16 * (bid >> 2), c0 = 144 * (bid & 3);
        mbar_wait(S + B_OUT * 8, 0);
        mbar_wait(S + B_XS * 8, 0);
        const uint32_t otag = lds32(S + SM_EPOCH) * 0x00010001u;
        const uint2 skip = lds64(S + SM_SKIP);
        const int pi_g = (g & 1) + 8 * ((g >> 1) & 1) + 2 * (g >> 2), pi_j = (j & 1) + 8 * ((j >> 1) & 1) + 2 * (j >> 2);
#pragma unroll 1
        for (int un = warp; un < 36; un += 12) {
            const int q = (un * 57) >> 9, cu = un - 9 * q;
            const uint32_t rw = S + SM_ROWS + 16 * q * 304 + 32 * cu;
            const uint32_t ad = rw + (pi_j + 4 * (mi & 1)) * 304 + 16 * (mi >> 1);
            const uint32_t dk0 = __ldg((const uint32_t*)p.dskip + (c0 >> 1) + 8 * cu + t), dk1 = __ldg((const uint32_t*)p.dskip + (c0 >> 1) + 8 * cu + 4 + t);
            const uint4 sa = lds128(S + SM_KT + KT_P4 + 16 * (16 * q + pi_g)), sb = lds128(S + SM_KT + KT_P4 + 16 * (16 * q + 4 + pi_g));
            uint32_t x[4], tt[4], gt[4], y[4];
            ldm4(ad, x[0], x[1], x[2], x[3]);
#pragma unroll
            for (int e = 0; e < 4; e++) {
                const uint4 s = (e & 1) ? sb : sa;
                const uint32_t xn = norm2(x[e], s.x, s.y, s.z);
                tt[e] = bmul(xn, e < 2 ? dk0 : dk1);
                gt[e] = pack_bf(silu_f(bf_lo(xn)), silu_f(bf_hi(xn)));
            }
            mbar_wait(S + (B_YIN + q) * 8, 0);
            const uint32_t yb = S + SM_STG + q * 4608 + 512 * cu;
#pragma unroll 1
            for (int it = 0; it < SPIN_LIMIT; it++) {
                ldm4t(yb + (8 * (mi >> 1) + j) * 32 + 16 * (mi & 1), y[0], y[1], y[2], y[3]);
                const uint32_t bad = ((y[0] ^ otag) | (y[1] ^ otag) | (y[2] ^ otag) | (y[3] ^ otag)) & 0x00010001u;
                if (!__any_sync(~0u, (g & 3) == 0 && bad)) break;
                const uint4 v = ld_rlx4((const uint4*)(p.s->y + (32 * q + (bid >> 2)) * 4608 + (bid & 3) * 1152 + 128 * cu) + lane);
                __syncwarp();
                sts128(yb + 16 * lane, v.x, v.y, v.z, v.w);
                __syncwarp();
            }
#pragma unroll
            for (int e = 0; e < 4; e++) y[e] = badd(x[e], bmul(badd(y[e], tt[e]), gt[e]));
            stm4(ad, y[0], y[1], y[2], y[3]);
            __syncwarp();
            const int row = lane >> 1;
            const uint4 o = lds128(rw + row * 304 + 16 * (lane & 1));
            if (!((((q & 2) ? skip.y : skip.x) >> (16 * (q & 1) + row)) & 1))
                *((uint4*)(p.out + (size_t)(512 * q + rb0 + row) * D_ + c0 + 16 * cu) + (lane & 1)) = o;
        }
        return;
    }

    {
        const int fw = warp - 13;
        if (fw < nsl) {
            st_rlx(&p.s->h[tag ^ 1][(32 * (sl0 + fw) + 16 * r) * 4 + lane], 0u);
            st_rlx(&p.s->h[tag ^ 1][(32 * (sl0 + fw) + 16 * r) * 4 + 32 + lane], 0u);
        }
        if (fw == 2) {
            spin_until(t0, p.tn.t_xs);
            uint32_t sv = 0;
#pragma unroll 1
            for (int it = 0; it < SPIN_LIMIT; it++) {
                sv = ld_rlx(&p.s->sel[bid & 3][j]);
                if (__all_sync(~0u, ((sv >> 15) & 1) == tag)) break;
                __nanosleep(40);
            }
            mbar_wait(S + B_KG * 8, 0);
            if (lane == 0) { fence_async(); mbar_expect(S + B_BOX * 8, 8 * 1152); }
            __syncwarp();
            if (lane < 8) bulk_g2s(S + SM_XS + lane * ROW_STRIDE, p.u + (size_t)(sv & 2047) * D_, 1152, S + B_BOX * 8);
            const uint32_t st = ld_stat(&p.s->stat[sv & 2047], tag);
            const float ri = rcpf(bf_hi(st));
            const uint32_t hi = pack_bf(ri, ri);
            const float rl = ri - bf_lo(hi);
            if (lane == 0) sts64(S + SM_SKIP, 0u, 0u);
            __syncwarp();
            if (lane < 8) {
                const int row = sv & 2047;
                if (((row >> 4) & 31) == (bid >> 2)) asm volatile("red.shared.or.b32 [%0], %1;" ::"r"(S + SM_SKIP + 4 * (row >> 10)), "r"(1u << (16 * ((row >> 9) & 1) + (row & 15))) : "memory");
                sts32(S + SM_XS + 8 * ROW_STRIDE + 4 * lane, sv);
                sts128(S + SM_RP + 16 * lane, prmt(st, st, 0x1010), hi, pack_bf(rl, rl), 0u);
            }
        }
        asm volatile("barrier.cluster.wait.aligned;" ::: "memory");
        bar_sync(9, 96);
        mbar_wait(S + B_BOX * 8, 0);
#pragma unroll
        for (int k = 0; k < 6; k++) {
            const int v = tid - 416 + 96 * k, tk = (v * 911) >> 16;
            const uint4 x = lds128(S + SM_XS + 16 * (v + tk)), st = lds128(S + SM_RP + 16 * tk);
            sts128(S + SM_XS + 16 * (v + tk), norm2(x.x, st.x, st.y, st.z), norm2(x.y, st.x, st.y, st.z), norm2(x.z, st.x, st.y, st.z), norm2(x.w, st.x, st.y, st.z));
        }
        bar_sync(9, 96);
        if (tid == 416) mbar_arrive(S + B_XS * 8);
        const uint32_t ob = mapa(S, r ^ 1);
        if (fw == 2) {
            if (elect()) {
#pragma unroll 1
                for (int st = 0; st < (down ? 24 : 6 * nsl); st++) {
                    if (st == 12 && down) break;
                    mbar_wait(S + (B_W + st) * 8, 0);
                    if (st % 3 == 2) mbar_arrive(S + (B_GU + st / 3) * 8);
                }
            }
            __syncwarp();
        }
        if (fw < 2) {
            const uint32_t bad = S + SM_XS + j * ROW_STRIDE + mi * 16;
            uint32_t aad = (SW + (8 * (mi >> 1) + j) * 64 + 16 * ((mi & 1) ^ (j >> 1))) ^ ((r ^ fw) * 32);
            uint32_t b[18][4];
#pragma unroll
            for (int k = 0; k < 18; k++) ldm4(bad + 64 * k, b[k][0], b[k][1], b[k][2], b[k][3]);
#pragma unroll 1
            for (int u = 0; u < nsl; u++) {
                float d[4][4];
#pragma unroll
                for (int i = 0; i < 4; i++) d[i][0] = d[i][1] = d[i][2] = d[i][3] = 0.f;
#pragma unroll
                for (int hf = 0; hf < 2; hf++) {
                    mbar_wait(S + (B_GU + 2 * u + hf) * 8, 0);
#pragma unroll
                    for (int sub = 0; sub < 3; sub++) {
                        uint32_t a[6][4];
#pragma unroll
                        for (int k = 0; k < 6; k++) ldm4t(aad + 1024 * k, a[k][0], a[k][1], a[k][2], a[k][3]);
#pragma unroll
                        for (int k = 0; k < 6; k++) {
                            const int kb = 9 * hf + 3 * sub + (k >> 1);
                            mma_bf(d[k & 3], a[k][0], a[k][1], a[k][2], a[k][3], b[kb][2 * (k & 1)], b[kb][2 * (k & 1) + 1]);
                        }
                        aad += STAGE;
                    }
                }
                const uint32_t k0 = pack_bf((d[0][0] + d[1][0]) + (d[2][0] + d[3][0]), (d[0][1] + d[1][1]) + (d[2][1] + d[3][1]));
                const uint32_t k1 = pack_bf((d[0][2] + d[1][2]) + (d[2][2] + d[3][2]), (d[0][3] + d[1][3]) + (d[2][3] + d[3][3]));
                if (fw == 1) {
                    asm volatile("st.async.shared::cluster.mbarrier::complete_tx::bytes.v2.b32 [%0], {%1, %2}, [%3];" ::"r"(ob + SM_PART + u * 256 + lane * 8), "r"(k0), "r"(k1), "r"(ob + (B_GX + u) * 8) : "memory");
                } else {
                    mbar_wait(S + (B_GX + u) * 8, 0);
                    const uint2 o = lds64(S + SM_PART + u * 256 + lane * 8);
#pragma unroll
                    for (int i = 0; i < 2; i++) {
                        const uint32_t mine = i ? k1 : k0, other = i ? o.y : o.x, gb = r ? other : mine, ub = r ? mine : other;
                        uint32_t hv = bmul(pack_bf(silu_f(bf_lo(gb)), silu_f(bf_hi(gb))), ub);
                        if ((hv & 0xFFFFu) == 0) hv |= 0x8000u;
                        if ((hv >> 16) == 0) hv |= 0x80000000u;
                        st_rlx(&p.s->h[tag][(32 * (sl0 + u) + 16 * r) * 4 + 32 * i + lane], hv);
                    }
                    __syncwarp();
                    if (lane < 8) red_add(&p.s->cnt[lane * 32]);
                }
            }
        }
        if (!down) return;

        const int fi = 32 * fw + lane, tok = 4 * r + ((fi >> 4) & 3), cc = 16 * pr + (fi & 15);
        const uint32_t sel = lds32(S + SM_XS + 8 * ROW_STRIDE + 4 * tok);
        const int row = sel & 2047;
        const uint32_t* ya = p.s->y + (row >> 4) * 4608 + cc * 8 + (row & 6);
        const float xraw = __bfloat162float(p.u[(size_t)row * D_ + cc]), dsk = __bfloat162float(p.dskip[cc]);
        const float xn = bf_lo(lds16(S + SM_XS + tok * ROW_STRIDE + 2 * cc));
        if (fw == 0) {
#pragma unroll 1
            for (int st = 12; st < 24; st++) mbar_wait(S + (B_W + st) * 8, 0);
        }
        if (fw == 2 && elect()) wait_count(&p.s->cnt[(bid & 7) * 32], epoch * 288u);
        bar_sync(9, 96);
        float dn[4][4];
        uint2 yv2 = make_uint2(tag ^ 1, 0u);
#pragma unroll 1
        for (int ph = 0; ph < 64; ph++) {
            if (fw == 2 && elect()) {
                fence_async();
                fence_async_g();
                mbar_expect(S + B_H * 8, 36864);
                bulk_g2s(SW, (const char*)p.s->h[tag] + r * 36864, 36864, S + B_H * 8);
            }
            asm volatile("ld.relaxed.gpu.global.v2.u32 {%0,%1}, [%2];" : "=r"(yv2.x), "=r"(yv2.y) : "l"(ya) : "memory");
            mbar_wait(S + B_H * 8, ph & 1);
#pragma unroll
            for (int i = 0; i < 4; i++) dn[i][0] = dn[i][1] = dn[i][2] = dn[i][3] = 0.f;
            uint32_t bq[4] = {~0u, ~0u, ~0u, ~0u};
            const int fr = j + 8 * (mi >> 1);
            uint32_t wa = SW + 12 * STAGE + fw * 2048 + fr * 32 + (((mi & 1) ^ ((fr >> 2) & 1)) << 4), ha = SW + fw * 1024 + lane * 16;
#pragma unroll 1
            for (int s0 = 0; s0 < 12; s0 += 3) {
                uint32_t a[6][8], b[6][4];
#pragma unroll
                for (int s = 0; s < 3; s++) {
                    if (s == 2 && s0 == 9) wa += S + SM_W_LAST - (SW + 23 * STAGE);
#pragma unroll
                    for (int e = 0; e < 2; e++) {
                        ldm4t(ha + e * 512, b[2 * s + e][0], b[2 * s + e][1], b[2 * s + e][2], b[2 * s + e][3]);
                        ldm4t(wa + e * 1024, a[2 * s + e][0], a[2 * s + e][1], a[2 * s + e][2], a[2 * s + e][3]);
                        ldm4t(wa + e * 1024 + 512, a[2 * s + e][4], a[2 * s + e][5], a[2 * s + e][6], a[2 * s + e][7]);
                    }
                    wa += STAGE; ha += 3072;
                }
#pragma unroll
                for (int k = 0; k < 6; k++) {
                    mma_bf(dn[2 * (k & 1)], a[k][0], a[k][1], a[k][2], a[k][3], b[k][0], b[k][1]);
                    mma_bf(dn[2 * (k & 1) + 1], a[k][4], a[k][5], a[k][6], a[k][7], b[k][2], b[k][3]);
#pragma unroll
                    for (int q = 0; q < 4; q++) bq[q] = __vminu2(bq[q], b[k][q]);
                }
            }
            const uint32_t bm = __vminu2(__vminu2(bq[0], bq[1]), __vminu2(bq[2], bq[3])), bd = (bm - 0x00010001u) & ~bm;
            uint32_t anybad;
            asm volatile("{.reg .pred p, q; setp.ne.u32 p, %1, 0; bar.red.or.pred q, 9, 96, p; selp.u32 %0, 1, 0, q;}" : "=r"(anybad) : "r"(bd & 0x80008000u) : "memory");
            if (!anybad) break;
        }
        float* red = (float*)(smem + SM_RED + fw * 512);
        red[(2 * t) * 16 + g] = (dn[0][0] + dn[1][0]) + (dn[2][0] + dn[3][0]);
        red[(2 * t + 1) * 16 + g] = (dn[0][1] + dn[1][1]) + (dn[2][1] + dn[3][1]);
        red[(2 * t) * 16 + g + 8] = (dn[0][2] + dn[1][2]) + (dn[2][2] + dn[3][2]);
        red[(2 * t + 1) * 16 + g + 8] = (dn[0][3] + dn[1][3]) + (dn[2][3] + dn[3][3]);
        bar_sync(9, 96);
        if (fw < 2) {
            const float* rs = (const float*)(smem + SM_RED);
            const int mine = 64 * r + fi, other = mine ^ 64;
            st_async32(ob + SM_RP + 4 * fi, __float_as_uint(rs[other] + rs[128 + other] + rs[256 + other]), ob + B_RED * 8);
            const float s = rs[mine] + rs[128 + mine] + rs[256 + mine];
#pragma unroll 1
            for (int it = 0; it < SPIN_LIMIT && (yv2.x & 1) != tag; it++)
                asm volatile("ld.relaxed.gpu.global.v2.u32 {%0,%1}, [%2];" : "=r"(yv2.x), "=r"(yv2.y) : "l"(ya) : "memory");
            const uint32_t yw = (row & 8) ? yv2.y : yv2.x;
            const float sg = bf_round(((row & 1) ? bf_hi(yw) : bf_lo(yw)) + bf_round(xn * dsk));
            mbar_wait(S + B_RED * 8, 0);
            const float o = *(const float*)(smem + SM_RP + 4 * fi);
            const float yv = bf_round(bf_round(r == 0 ? s + o : o + s) * bf_hi(sel));
            p.out[(size_t)row * D_ + cc] = __float2bfloat16(xraw + bf_round(sg * bf_round(silu_f(bf_round(xn + yv)))));
            if (bid == 0 && fi == 0) st_rlx(&p.s->cnt[16 * 32], epoch);
        }
    }
}

typedef CUresult (*EncodeFn)(CUtensorMap*, CUtensorMapDataType, cuuint32_t, void*, const cuuint64_t*, const cuuint64_t*, const cuuint32_t*,
                             const cuuint32_t*, CUtensorMapInterleave, CUtensorMapSwizzle, CUtensorMapL2promotion, CUtensorMapFloatOOBfill);

static void make2d(EncodeFn enc, CUtensorMap* m, const void* base, uint64_t cols, uint64_t rows, uint32_t bc, uint32_t br, CUtensorMapSwizzle sw) {
    cuuint64_t gd[2] = {cols, rows};
    cuuint64_t gs[1] = {cols * 2};
    cuuint32_t bd[2] = {bc, br}, es[2] = {1, 1};
    enc(m, CU_TENSOR_MAP_DATA_TYPE_BFLOAT16, 2, const_cast<void*>(base), gd, gs, bd, es, CU_TENSOR_MAP_INTERLEAVE_NONE, sw,
        CU_TENSOR_MAP_L2_PROMOTION_L2_128B, CU_TENSOR_MAP_FLOAT_OOB_FILL_NONE);
}

static Tune g_tune = {2000, 9000, 3, 5, 8, 5000, 7500, 0, 9000, 1, 0, 0};


static void launch(void* const* d_in, void* d_out) {
    static EncodeFn enc = nullptr;
    static Scratch* gs = nullptr;
    if (!enc) {
        void* fn = nullptr;
        cudaDriverEntryPointQueryResult qr;
        cudaGetDriverEntryPoint("cuTensorMapEncodeTiled", &fn, cudaEnableDefault, &qr);
        enc = (EncodeFn)fn;
        cudaFuncSetAttribute(fused_kernel, cudaFuncAttributeMaxDynamicSharedMemorySize, SM_TOTAL);
        cudaGetSymbolAddress((void**)&gs, g_s);
    }
    Hot p;
    Maps m;
    auto in = [&](int i) { return (const __nv_bfloat16*)d_in[i]; };
    p.u = in(0); p.are = in(1); p.aim = in(2); p.bre = in(3); p.bim = in(4); p.cre = in(5); p.cim = in(6);
    p.logdt = in(7); p.dskip = in(8); p.wr = in(10); p.pwg = in(11); p.pwu = in(12); p.pwd = in(13);
    p.out = (__nv_bfloat16*)d_out;
    p.tn = g_tune;
    p.s = gs;
    make2d(enc, &m.wg, p.pwg, F_, D_, 32, 96, CU_TENSOR_MAP_SWIZZLE_64B);
    make2d(enc, &m.wu, p.pwu, F_, D_, 32, 96, CU_TENSOR_MAP_SWIZZLE_64B);
    make2d(enc, &m.wd, p.pwd, D_, F_, 16, 192, CU_TENSOR_MAP_SWIZZLE_32B);
    fused_kernel<<<NCTA, NTHREADS, SM_TOTAL>>>(p, m);
}

}

extern "C" void kernel_launch(void* const* d_in, const int* in_sizes, int n_in, void* d_out, int out_size) {
    static int clusters = -1;
    if (clusters < 0) clusters = v3::max_clusters();
    if (clusters < 15 || !v3::launch(d_in, d_out)) v2::launch(d_in, d_out);
}
```

```cpp
#include <cuda_runtime.h>
#include <cuda_bf16.h>
#include <cuda_fp16.h>
#include <cuda.h>
#include <stdint.h>
#include <stddef.h>
#include <type_traits>


namespace v3 {

template <int N> using Int = std::integral_constant<int, N>;

constexpr int D_ = 576, F_ = 4608;
constexpr int NCTA = 120, NTHREADS = 512;
constexpr int SPIN_LIMIT = 1 << 16;

enum { B_Y = 0, B_X = 8, B_TOP = 10, B_XS = 12, B_UP = 13, B_RAW = 15, B_FULL = 16, B_FIN = 43, B_SEL = 44, B_EMPTY = 38  , B_ROWS = 66, B_WR = 67 };
constexpr int SM_SKIP = 544, SM_SEL = 576;
constexpr int SM_ST = 640;
constexpr int SM_RAW = 2688, PITCH = 80;
constexpr int SM_CH = SM_RAW + 256 * PITCH, CH = 18304;
constexpr int TAB = 0, FT = 3072, XX = 3712, BOX = 8064, YIN = 14208;
constexpr int SM_B = SM_CH + 5 * CH, BP = 1168;
constexpr int SM_CAND = SM_B + 8 * BP, SM_PROG = SM_CAND + 256, SM_DUMP = SM_PROG + 128;
constexpr int NRING = 12, SM_W = SM_B + 10240, SM_FIN = SM_W + NRING * 8192, SM_TOTAL = 232448;
static_assert(SM_W % 1024 == 0 && SM_FIN + 8192 <= SM_TOTAL && SM_TOTAL - 18432 >= SM_W + 10 * 8192, "smem");

struct Tune { int t_tile, stag, c256, win5, win4, t_rows, da, t_pf, zero; };

struct Scratch {
    uint32_t h[8 * 2304];
    uint2 stat[2048];
    uint32_t ep[NCTA * 8];
};
__device__ __align__(1024) Scratch g_s;

struct Hot {
    const __nv_bfloat16* u;
    int bre, bim, cre, cim, are, aim, logdt, dskip, wr, ep;
    Scratch* s;
    __nv_bfloat16* out;
    const __nv_bfloat16* wg;
    Tune tn;
};
struct Maps { CUtensorMap w[3], u; };

__device__ __forceinline__ uint32_t smem_u32(const void* p) { return (uint32_t)__cvta_generic_to_shared(p); }
__device__ __forceinline__ void mbar_init(uint32_t b, int c) { asm volatile("mbarrier.init.shared::cta.b64 [%0], %1;" ::"r"(b), "r"(c) : "memory"); }
__device__ __forceinline__ void mbar_expect(uint32_t b, int bytes) { asm volatile("mbarrier.arrive.expect_tx.shared::cta.b64 _, [%0], %1;" ::"r"(b), "r"(bytes) : "memory"); }
__device__ __forceinline__ void mbar_arrive(uint32_t b) { asm volatile("mbarrier.arrive.shared::cta.b64 _, [%0];" ::"r"(b) : "memory"); }
__device__ __forceinline__ bool elect() { uint32_t d; asm volatile("{.reg .pred p; elect.sync _|p, 0xffffffff; selp.u32 %0,1,0,p;}" : "=r"(d)); return d; }
__device__ __forceinline__ void mbar_wait(uint32_t b, int par) {
    asm volatile("{\n.reg .pred p;\nLW:\nmbarrier.try_wait.parity.shared::cta.b64 p, [%0], %1, 2000;\n@!p bra LW;\n}" ::"r"(b), "r"(par) : "memory");
}
__device__ __forceinline__ void mbar_wait_short(uint32_t b) {
    asm volatile("{\n.reg .pred p;\nLW:\nmbarrier.try_wait.parity.shared::cta.b64 p, [%0], 0;\n@!p bra LW;\n}" ::"r"(b) : "memory");
}
__device__ __forceinline__ uint32_t mapa(uint32_t a, uint32_t rank) { uint32_t d; asm("mapa.shared::cluster.u32 %0, %1, %2;" : "=r"(d) : "r"(a), "r"(rank)); return d; }
__device__ __forceinline__ void tma2d(uint32_t dst, const CUtensorMap* m, int c0, int c1, uint32_t bar) {
    asm volatile("cp.async.bulk.tensor.2d.shared::cluster.global.mbarrier::complete_tx::bytes [%0], [%1, {%3, %4}], [%2];" ::"r"(dst), "l"(m), "r"(bar), "r"(c0), "r"(c1) : "memory");
}
__device__ __forceinline__ void bulk_g2s(uint32_t dst, const void* src, int bytes, uint32_t bar) {
    asm volatile("cp.async.bulk.shared::cluster.global.mbarrier::complete_tx::bytes [%0], [%1], %2, [%3];" ::"r"(dst), "l"(src), "r"(bytes), "r"(bar) : "memory");
}
__device__ __forceinline__ void bulk_mc(uint32_t dst, const void* src, int bytes, uint32_t bar) {
    asm volatile("cp.async.bulk.shared::cluster.global.mbarrier::complete_tx::bytes.multicast::cluster [%0], [%1], %2, [%3], %4;"
                 ::"r"(dst), "l"(src), "r"(bytes), "r"(bar), "h"((uint16_t)255) : "memory");
}
__device__ __forceinline__ void bar_sync(int id, int n) { asm volatile("bar.sync %0, %1;" ::"r"(id), "r"(n) : "memory"); }
__device__ __forceinline__ void bar_arrive(int id, int n) { asm volatile("bar.arrive %0, %1;" ::"r"(id), "r"(n) : "memory"); }
__device__ __forceinline__ uint4 ld_rlx4(const void* p) { uint4 v; asm volatile("ld.relaxed.gpu.global.v4.u32 {%0,%1,%2,%3}, [%4];" : "=r"(v.x), "=r"(v.y), "=r"(v.z), "=r"(v.w) : "l"(p) : "memory"); return v; }
__device__ __forceinline__ uint2 ld_rlx2(const void* p) { uint2 v; asm volatile("ld.relaxed.gpu.global.v2.u32 {%0,%1}, [%2];" : "=r"(v.x), "=r"(v.y) : "l"(p) : "memory"); return v; }
__device__ __forceinline__ uint32_t ld_rlx(const void* p) { uint32_t v; asm volatile("ld.relaxed.gpu.global.u32 %0, [%1];" : "=r"(v) : "l"(p) : "memory"); return v; }
__device__ __forceinline__ void st_rlx(void* p, uint32_t v) { asm volatile("st.relaxed.gpu.global.u32 [%0], %1;" ::"l"(p), "r"(v) : "memory"); }
__device__ __forceinline__ void st_rlx2(void* p, uint32_t x, uint32_t y) { asm volatile("st.relaxed.gpu.global.v2.u32 [%0], {%1,%2};" ::"l"(p), "r"(x), "r"(y) : "memory"); }
__device__ __forceinline__ uint4 ldg4(const void* p) { uint4 v; asm volatile("ld.global.nc.v4.u32 {%0,%1,%2,%3}, [%4];" : "=r"(v.x), "=r"(v.y), "=r"(v.z), "=r"(v.w) : "l"(p)); return v; }
__device__ __forceinline__ uint32_t ldg1(const void* p) { uint32_t v; asm volatile("ld.global.nc.u32 %0, [%1];" : "=r"(v) : "l"(p)); return v; }
__device__ __forceinline__ uint32_t ldg16(const void* p) { uint16_t v; asm volatile("ld.global.nc.u16 %0, [%1];" : "=h"(v) : "l"(p)); return v; }
__device__ __forceinline__ const void* at256(const void* b, int o) { const void* r; asm("mad.wide.s32 %0, %1, 256, %2;" : "=l"(r) : "r"(o), "l"(b)); return r; }
__device__ __forceinline__ int laneid() { int v; asm volatile("mov.u32 %0, %%laneid;" : "=r"(v)); return v; }
__device__ __forceinline__ uint32_t keep(uint32_t v) { return __shfl_xor_sync(~0u, v, 0); }
__device__ __forceinline__ int ctaid() { int v; asm volatile("mov.u32 %0, %%ctaid.x;" : "=r"(v)); return v; }
__device__ __forceinline__ uint32_t lds32(uint32_t a) { uint32_t v; asm volatile("ld.shared.u32 %0, [%1];" : "=r"(v) : "r"(a) : "memory"); return v; }
__device__ __forceinline__ uint32_t lds32v(uint32_t a) { uint32_t v; asm volatile("ld.volatile.shared.u32 %0, [%1];" : "=r"(v) : "r"(a) : "memory"); return v; }
__device__ __forceinline__ uint32_t lds16(uint32_t a) { uint16_t v; asm volatile("ld.shared.u16 %0, [%1];" : "=h"(v) : "r"(a) : "memory"); return v; }
__device__ __forceinline__ uint2 lds64(uint32_t a) { uint2 v; asm volatile("ld.shared.v2.u32 {%0,%1}, [%2];" : "=r"(v.x), "=r"(v.y) : "r"(a) : "memory"); return v; }
__device__ __forceinline__ uint4 lds128(uint32_t a) { uint4 v; asm volatile("ld.shared.v4.u32 {%0,%1,%2,%3}, [%4];" : "=r"(v.x), "=r"(v.y), "=r"(v.z), "=r"(v.w) : "r"(a) : "memory"); return v; }
__device__ __forceinline__ void sts16(uint32_t a, uint32_t v) { asm volatile("st.shared.u16 [%0], %1;" ::"r"(a), "h"((uint16_t)v) : "memory"); }
__device__ __forceinline__ void sts32(uint32_t a, uint32_t v) { asm volatile("st.shared.u32 [%0], %1;" ::"r"(a), "r"(v) : "memory"); }
__device__ __forceinline__ void sts32v(uint32_t a, uint32_t v) { asm volatile("st.volatile.shared.u32 [%0], %1;" ::"r"(a), "r"(v) : "memory"); }
__device__ __forceinline__ void sts64(uint32_t a, uint32_t x, uint32_t y) { asm volatile("st.shared.v2.u32 [%0], {%1,%2};" ::"r"(a), "r"(x), "r"(y) : "memory"); }
__device__ __forceinline__ void sts128(uint32_t a, uint32_t x, uint32_t y, uint32_t z, uint32_t w) { asm volatile("st.shared.v4.u32 [%0], {%1,%2,%3,%4};" ::"r"(a), "r"(x), "r"(y), "r"(z), "r"(w) : "memory"); }
__device__ __forceinline__ void sts128v(uint32_t a, uint32_t x, uint32_t y, uint32_t z, uint32_t w) { asm volatile("st.volatile.shared.v4.u32 [%0], {%1,%2,%3,%4};" ::"r"(a), "r"(x), "r"(y), "r"(z), "r"(w) : "memory"); }
__device__ __forceinline__ void sts128f(uint32_t a, float x, float y, float z, float w) { asm volatile("st.shared.v4.f32 [%0], {%1,%2,%3,%4};" ::"r"(a), "f"(x), "f"(y), "f"(z), "f"(w) : "memory"); }
__device__ __forceinline__ void st_async4(uint32_t a, uint32_t x, uint32_t y, uint32_t z, uint32_t w, uint32_t bar) {
    asm volatile("st.async.shared::cluster.mbarrier::complete_tx::bytes.v4.b32 [%0], {%1,%2,%3,%4}, [%5];" ::"r"(a), "r"(x), "r"(y), "r"(z), "r"(w), "r"(bar) : "memory");
}
__device__ __forceinline__ void st_async2(uint32_t a, uint32_t x, uint32_t y, uint32_t bar) {
    asm volatile("st.async.shared::cluster.mbarrier::complete_tx::bytes.v2.b32 [%0], {%1,%2}, [%3];" ::"r"(a), "r"(x), "r"(y), "r"(bar) : "memory");
}
__device__ __forceinline__ void st_async2f(uint32_t a, float x, float y, uint32_t bar) {
    asm volatile("st.async.shared::cluster.mbarrier::complete_tx::bytes.v2.f32 [%0], {%1,%2}, [%3];" ::"r"(a), "f"(x), "f"(y), "r"(bar) : "memory");
}
__device__ __forceinline__ void ldm4(uint32_t a, uint32_t& r0, uint32_t& r1, uint32_t& r2, uint32_t& r3) {
    asm volatile("ldmatrix.sync.aligned.m8n8.x4.shared.b16 {%0,%1,%2,%3}, [%4];" : "=r"(r0), "=r"(r1), "=r"(r2), "=r"(r3) : "r"(a) : "memory");
}
__device__ __forceinline__ void ldm4t(uint32_t a, uint32_t (&r)[4]) {
    asm volatile("ldmatrix.sync.aligned.m8n8.x4.trans.shared.b16 {%0,%1,%2,%3}, [%4];" : "=r"(r[0]), "=r"(r[1]), "=r"(r[2]), "=r"(r[3]) : "r"(a) : "memory");
}
__device__ __forceinline__ void ldm2(uint32_t a, uint32_t& r0, uint32_t& r1) {
    asm volatile("ldmatrix.sync.aligned.m8n8.x2.shared.b16 {%0,%1}, [%2];" : "=r"(r0), "=r"(r1) : "r"(a) : "memory");
}
__device__ __forceinline__ void ldm2t(uint32_t a, uint32_t& r0, uint32_t& r1) {
    asm volatile("ldmatrix.sync.aligned.m8n8.x2.trans.shared.b16 {%0,%1}, [%2];" : "=r"(r0), "=r"(r1) : "r"(a) : "memory");
}
__device__ __forceinline__ void stm4(uint32_t a, uint32_t r0, uint32_t r1, uint32_t r2, uint32_t r3) {
    asm volatile("stmatrix.sync.aligned.m8n8.x4.shared.b16 [%0], {%1,%2,%3,%4};" ::"r"(a), "r"(r0), "r"(r1), "r"(r2), "r"(r3) : "memory");
}
__device__ __forceinline__ void stm4t(uint32_t a, uint32_t r0, uint32_t r1, uint32_t r2, uint32_t r3) {
    asm volatile("stmatrix.sync.aligned.m8n8.x4.trans.shared.b16 [%0], {%1,%2,%3,%4};" ::"r"(a), "r"(r0), "r"(r1), "r"(r2), "r"(r3) : "memory");
}
__device__ __forceinline__ void stm2t(uint32_t a, uint32_t r0, uint32_t r1) {
    asm volatile("stmatrix.sync.aligned.m8n8.x2.trans.shared.b16 [%0], {%1,%2};" ::"r"(a), "r"(r0), "r"(r1) : "memory");
}
__device__ __forceinline__ uint32_t movm(uint32_t a) { uint32_t d; asm volatile("movmatrix.sync.aligned.m8n8.trans.b16 %0, %1;" : "=r"(d) : "r"(a)); return d; }
__device__ __forceinline__ void mma_bf(float (&c)[4], uint32_t a0, uint32_t a1, uint32_t a2, uint32_t a3, uint32_t b0, uint32_t b1) {
    asm volatile("mma.sync.aligned.m16n8k16.row.col.f32.bf16.bf16.f32 {%0,%1,%2,%3},{%4,%5,%6,%7},{%8,%9},{%0,%1,%2,%3};"
                 : "+f"(c[0]), "+f"(c[1]), "+f"(c[2]), "+f"(c[3]) : "r"(a0), "r"(a1), "r"(a2), "r"(a3), "r"(b0), "r"(b1));
}
__device__ __forceinline__ void mma_bf8(float (&c)[4], uint32_t a0, uint32_t a1, uint32_t b0) {
    asm volatile("mma.sync.aligned.m16n8k8.row.col.f32.bf16.bf16.f32 {%0,%1,%2,%3},{%4,%5},{%6},{%0,%1,%2,%3};"
                 : "+f"(c[0]), "+f"(c[1]), "+f"(c[2]), "+f"(c[3]) : "r"(a0), "r"(a1), "r"(b0));
}
__device__ __forceinline__ void mma_h(float (&c)[4], uint32_t a0, uint32_t a1, uint32_t a2, uint32_t a3, uint32_t b0, uint32_t b1) {
    asm volatile("mma.sync.aligned.m16n8k16.row.col.f32.f16.f16.f32 {%0,%1,%2,%3},{%4,%5,%6,%7},{%8,%9},{%0,%1,%2,%3};"
                 : "+f"(c[0]), "+f"(c[1]), "+f"(c[2]), "+f"(c[3]) : "r"(a0), "r"(a1), "r"(a2), "r"(a3), "r"(b0), "r"(b1));
}
__device__ __forceinline__ void mma_h8(float (&c)[4], uint32_t a0, uint32_t a1, uint32_t b0) {
    asm volatile("mma.sync.aligned.m16n8k8.row.col.f32.f16.f16.f32 {%0,%1,%2,%3},{%4,%5},{%6},{%0,%1,%2,%3};"
                 : "+f"(c[0]), "+f"(c[1]), "+f"(c[2]), "+f"(c[3]) : "r"(a0), "r"(a1), "r"(b0));
}
template <int LIM>
__device__ __forceinline__ void mma_hp(int n, float (&d)[4], const float (&c)[4], uint32_t a0, uint32_t a1, uint32_t a2, uint32_t a3, uint32_t b0, uint32_t b1) {
    asm volatile("{.reg .pred p; setp.gt.s32 p, %14, %15;\n"
                 "@p mma.sync.aligned.m16n8k16.row.col.f32.f16.f16.f32 {%0,%1,%2,%3},{%4,%5,%6,%7},{%8,%9},{%10,%11,%12,%13};}"
                 : "+f"(d[0]), "+f"(d[1]), "+f"(d[2]), "+f"(d[3])
                 : "r"(a0), "r"(a1), "r"(a2), "r"(a3), "r"(b0), "r"(b1), "f"(c[0]), "f"(c[1]), "f"(c[2]), "f"(c[3]), "r"(n), "n"(LIM));
}
template <int LIM>
__device__ __forceinline__ void mma_hq(int n, float (&d)[4], uint32_t a0, uint32_t a1, uint32_t a2, uint32_t a3, uint32_t b0, uint32_t b1) {
    asm volatile("{.reg .pred p; setp.gt.s32 p, %10, %11;\n"
                 "@p mma.sync.aligned.m16n8k16.row.col.f32.f16.f16.f32 {%0,%1,%2,%3},{%4,%5,%6,%7},{%8,%9},{%0,%1,%2,%3};}"
                 : "+f"(d[0]), "+f"(d[1]), "+f"(d[2]), "+f"(d[3]) : "r"(a0), "r"(a1), "r"(a2), "r"(a3), "r"(b0), "r"(b1), "r"(n), "n"(LIM));
}
__device__ __forceinline__ void mma_hc(float (&d)[4], const float (&c)[4], uint32_t a0, uint32_t a1, uint32_t a2, uint32_t a3, uint32_t b0, uint32_t b1) {
    asm volatile("mma.sync.aligned.m16n8k16.row.col.f32.f16.f16.f32 {%0,%1,%2,%3},{%4,%5,%6,%7},{%8,%9},{%10,%11,%12,%13};"
                 : "=f"(d[0]), "=f"(d[1]), "=f"(d[2]), "=f"(d[3]) : "r"(a0), "r"(a1), "r"(a2), "r"(a3), "r"(b0), "r"(b1), "f"(c[0]), "f"(c[1]), "f"(c[2]), "f"(c[3]));
}
__device__ __forceinline__ uint32_t pack_bf(float lo, float hi) { uint32_t r; asm("cvt.rn.bf16x2.f32 %0, %1, %2;" : "=r"(r) : "f"(hi), "f"(lo)); return r; }
__device__ __forceinline__ uint32_t pack_h(float lo, float hi) { uint32_t r; asm("cvt.rn.f16x2.f32 %0, %1, %2;" : "=r"(r) : "f"(hi), "f"(lo)); return r; }
__device__ __forceinline__ float bf_lo(uint32_t w) { return __uint_as_float(w << 16); }
__device__ __forceinline__ float bf_hi(uint32_t w) { return __uint_as_float(w & 0xFFFF0000u); }
__device__ __forceinline__ float bf_round(float x) { return __uint_as_float(pack_bf(0.f, x)); }
__device__ __forceinline__ uint32_t badd(uint32_t a, uint32_t b) { uint32_t r; asm("add.rn.bf16x2 %0, %1, %2;" : "=r"(r) : "r"(a), "r"(b)); return r; }
__device__ __forceinline__ uint32_t bsub(uint32_t a, uint32_t b) { uint32_t r; asm("sub.rn.bf16x2 %0, %1, %2;" : "=r"(r) : "r"(a), "r"(b)); return r; }
__device__ __forceinline__ uint32_t bmul(uint32_t a, uint32_t b) { uint32_t r; asm("mul.rn.bf16x2 %0, %1, %2;" : "=r"(r) : "r"(a), "r"(b)); return r; }
__device__ __forceinline__ uint32_t bfma(uint32_t a, uint32_t b, uint32_t c) { uint32_t r; asm("fma.rn.bf16x2 %0, %1, %2, %3;" : "=r"(r) : "r"(a), "r"(b), "r"(c)); return r; }
__device__ __forceinline__ uint32_t hadd(uint32_t a, uint32_t b) { uint32_t r; asm("add.rn.f16x2 %0, %1, %2;" : "=r"(r) : "r"(a), "r"(b)); return r; }
__device__ __forceinline__ uint32_t prmt(uint32_t a, uint32_t b, uint32_t s) { uint32_t r; asm("prmt.b32 %0, %1, %2, %3;" : "=r"(r) : "r"(a), "r"(b), "r"(s)); return r; }
__device__ __forceinline__ uint32_t lop_ne(uint32_t a, uint32_t b, uint32_t c) { uint32_t r; asm("lop3.b32 %0, %1, %2, %3, 0x7E;" : "=r"(r) : "r"(a), "r"(b), "r"(c)); return r; }
__device__ __forceinline__ float ex2f(float x) { float r; asm("ex2.approx.ftz.f32 %0, %1;" : "=f"(r) : "f"(x)); return r; }
__device__ __forceinline__ float rcpf(float x) { float r; asm("rcp.approx.ftz.f32 %0, %1;" : "=f"(r) : "f"(x)); return r; }
__device__ __forceinline__ float sqrt_ap(float x) { float r; asm("sqrt.approx.ftz.f32 %0, %1;" : "=f"(r) : "f"(x)); return r; }
__device__ __forceinline__ float tanh_ap(float x) { float r; asm("tanh.approx.f32 %0, %1;" : "=f"(r) : "f"(x)); return r; }
__device__ __forceinline__ float sigm(float x) { return rcpf(1.f + ex2f(-1.4426950408889634f * x)); }
__device__ __forceinline__ float silu_half(float h) { return fmaf(h, tanh_ap(h), h); }
__device__ __forceinline__ uint32_t clk32() { uint32_t c; asm volatile("mov.u32 %0, %%clock;" : "=r"(c)); return c; }
__device__ __forceinline__ void spin_until(uint32_t t0, int dt) {
#pragma unroll 1
    while ((int)(clk32() - t0) < dt) __nanosleep(32);
}
__device__ __forceinline__ void cp16(uint32_t dst, const void* src) { asm volatile("cp.async.cg.shared.global [%0], [%1], 16;" ::"r"(dst), "l"(src) : "memory"); }

__device__ __forceinline__ uint32_t xslot(int s, int h) { return XX + 32 * (s & ~1) + 16 * ((2 * h + (s & 1)) ^ ((s >> 1) & 2)); }

struct cf { float x, y; };
__device__ __forceinline__ cf cmul(cf a, cf b) { return {a.x * b.x - a.y * b.y, a.x * b.y + a.y * b.x}; }
__device__ __forceinline__ cf csq(cf a) { return {a.x * a.x - a.y * a.y, (a.x + a.x) * a.y}; }
__device__ __forceinline__ cf cpow_direct(float zr2, float zi, float l) {
    const float mag = ex2f(zr2 * l), th = zi * l;
    return {mag * __cosf(th), mag * __sinf(th)};
}
struct hp { uint32_t re, im; };
struct hm { __half2 v; };
__device__ __forceinline__ __half2 as_h2(uint32_t v) { return *reinterpret_cast<__half2*>(&v); }
__device__ __forceinline__ uint32_t as_u32(__half2 v) { return *reinterpret_cast<uint32_t*>(&v); }
__device__ __forceinline__ hp mk2(cf a, cf b) { return {pack_h(a.x, b.x), pack_h(a.y, b.y)}; }
__device__ __forceinline__ hm mk1(cf a) { return {as_h2(pack_h(a.x, a.y))}; }
__device__ __forceinline__ hp his(hp a, hp b) { return {prmt(a.re, b.re, 0x7632), prmt(a.im, b.im, 0x7632)}; }
__device__ __forceinline__ hp operator*(hp a, hm b) {
    const __half2 c = __low2half2(b.v), s = __high2half2(b.v), x = as_h2(a.re), y = as_h2(a.im);
    return {as_u32(__hfma2(x, c, __hneg2(__hmul2_rn(y, s)))), as_u32(__hfma2(x, s, __hmul2_rn(y, c)))};
}
__device__ __forceinline__ hp operator*(hp a, hp b) {
    const __half2 c = as_h2(b.re), s = as_h2(b.im), x = as_h2(a.re), y = as_h2(a.im);
    return {as_u32(__hfma2(x, c, __hneg2(__hmul2_rn(y, s)))), as_u32(__hfma2(x, s, __hmul2_rn(y, c)))};
}
struct KParams { uint32_t are, aim, bre, bim, cre, cim, ldt, dsk, sa, la, lb, sb, sm, lm, l3, l4; };

__device__ __forceinline__ void kgen_addr(KParams& kp, uint32_t scr, int lane) {
    const int g = lane >> 2, t = lane & 3, mi = lane >> 3, j = lane & 7;
    kp.sa = keep(scr + 16 * lane);
    kp.sb = keep(scr + 128 * t + 16 * (g ^ (2 * t)));
    kp.la = keep(scr + 512 * (mi & 1) + 128 * (mi >> 1) + 16 * (j ^ (mi & 2)));
    kp.lb = keep((kp.la ^ 64) + 256);
    kp.sm = keep(scr + 2048 + 144 * mi + 16 * j);
    kp.lm = keep(scr + 2048 + 16 * mi);
    kp.l3 = keep(kp.lm + 144 * (j & 1));
    kp.l4 = keep(kp.lm + 288 - 72 * (j & 2));
}

__device__ __forceinline__ uint32_t kgen(KParams kp, uint32_t scr, uint32_t oth, int bar, int lane, float (&d)[5][4], float& k0, int nc, uint32_t pause, uint32_t zero) {
    const float dt = bf_round(ex2f(bf_lo(kp.ldt) * 1.4426950408889634f));
    cf w = cmul({bf_lo(kp.cre), bf_lo(kp.cim)}, {dt * bf_lo(kp.bre), dt * bf_lo(kp.bim)});
    cf w1 = cmul({bf_hi(kp.cre), bf_hi(kp.cim)}, {dt * bf_hi(kp.bre), dt * bf_hi(kp.bim)});
    const float dk = bf_lo(kp.dsk), dt2 = dt * 1.4426950408889634f;
    uint32_t z = prmt(kp.are, kp.aim, 0x5410), z1 = prmt(kp.are, kp.aim, 0x7632);
    uint32_t eb = __reduce_max_sync(~0u, __float_as_uint(fmaxf(fmaxf(fmaxf(fabsf(w.x), fabsf(w.y)), fmaxf(fabsf(w1.x), fabsf(w1.y))), fabsf(dk) * 0x1p-20f)));
    k0 = w.x + w1.x;
    const uint32_t sa = kp.sa, la = kp.la, lb = kp.lb;
    sts128(oth + 2048 + 16 * lane, __float_as_uint(w1.x), __float_as_uint(w1.y), z1, __float_as_uint(k0));
    sts32(oth + 2560, eb);
    bar_sync(bar, 64);
    const uint4 ov = lds128(sa + 2048);
    eb = min(max(max(eb, lds32(scr + 2560)) & 0x7F800000u, 0x00800000u), 0x7A000000u);
    const float sc = __uint_as_float(0x7B000000u - eb);
    k0 = fmaf(dk, sc, 0x1p-28f * __reduce_add_sync(~0u, __float2int_rn((k0 + __uint_as_float(ov.w)) * sc * 0x1p28f)));
#pragma unroll
    for (int i = 0; i < 5; i++) d[i][0] = d[i][1] = d[i][2] = d[i][3] = 0.f;
    const uint32_t sb = kp.sb, sm = kp.sm, lm = kp.lm, l3 = kp.l3, l4 = kp.l4;
    auto st = [&](int grp, hp a, hp b, hp c, hp e) { sts128v(sb + 1024 * grp, a.re, b.re, c.re, e.re); sts128v(sb + 1024 * grp + 512, a.im, b.im, c.im, e.im); };
#pragma unroll 1
    do {
        const float zr2 = dt2 * bf_lo(z), zi = dt * bf_hi(z);
        const cf ws = {w.x * sc, w.y * sc};
        z = z1; w = w1;
        z1 = ov.z; w1 = {__uint_as_float(ov.x), __uint_as_float(ov.y)};
        const cf a1 = cpow_direct(zr2, zi, 1.f), a256 = cpow_direct(zr2, zi, 256.f), b1 = cpow_direct(-zr2, zi, -16.f);
        const cf b2 = csq(b1), b4 = csq(b2), a2 = csq(a1), a4 = csq(a2), a512 = csq(a256), a514 = cmul(a512, a2), c1 = cmul(ws, a1);
        const hm n4 = mk1(b4), m8 = mk1(csq(a4));
        const hp u0 = mk2({1.f, 0.f}, b1), u1 = u0 * mk1(b2), v0 = mk2(c1, cmul(c1, a2)), v1 = v0 * mk1(a4);
        __syncwarp();
        stm4t(sm, as_u32(mk1(cmul(a514, a256)).v), as_u32(mk1(a512).v), as_u32(mk1(csq(a514)).v), as_u32(mk1(a256).v));
        stm2t(sm + 576, as_u32(mk1(csq(b4)).v), as_u32(mk1(a1).v));
        st(0, u0, u1, u0 * n4, u1 * n4);
        st(1, v0, v1, v0 * m8, v1 * m8);
        __syncwarp();
#pragma unroll
        for (int h = 0; h < 2; h++) {
            if (h && pause) { mbar_wait(pause, 0); pause = 0; }
            uint32_t a[4], b[4], q[5][4];
            ldm4t(h ? lb : la, a);
            ldm4t((h ? lb : la) + 1024, b);
#pragma unroll
            for (int e = 0; e < 5; e++) ldm4((e == 3 ? l3 : (e == 4 ? l4 : lm + (e == 2 ? 432 : 576 + 144 * e))) + 64 * h, q[e][0], q[e][1], q[e][2], q[e][3]);
#pragma unroll
            for (int e = 0; e < 4; e += 2) {
                auto mul = [&](int i) { return hp{q[i][e], q[i][e + 1]}; };
                const hp y0 = {b[e], b[e + 1]}, y1 = y0 * mul(1), y2 = y1 * mul(2), y3 = y1 * mul(3), y4 = y3 * mul(4), x1 = hp{a[e], a[e + 1]} * mul(0);
                const uint32_t a0 = a[e] | zero, a2 = a[e + 1] | zero;
                mma_h(d[0], a0, x1.re, a2, x1.im, y0.re, y0.im);
                mma_h(d[1], a0, x1.re, a2, x1.im, y1.re, y1.im);
                mma_h(d[2], a0, x1.re, a2, x1.im, y2.re, y2.im);
                mma_h(d[3], a0, x1.re, a2, x1.im, y3.re, y3.im);
                mma_h(d[4], a0, x1.re, a2, x1.im, y4.re, y4.im);
            }
        }
    } while (--nc);
    return eb;
}

__device__ __forceinline__ void near_lags(uint32_t S, int k, uint32_t yo, uint32_t eb, const uint32_t (&xa)[8], uint32_t step  ) {
    const int lane = threadIdx.x & 31, g = lane >> 2, t = lane & 3, mi = lane >> 3, j = lane & 7, warp = k;
    const uint32_t cb = S + SM_CH + k * CH;
    uint32_t R[66];
#pragma unroll
    for (int i = 0; i < 66; i++) R[i] = lds32(cb + TAB + 4 * (7 + g - 2 * t) + 32 * i);
    bar_arrive(1 + k, 64);
    float w[5][4];
#pragma unroll
    for (int i = 0; i < 5; i++) w[i][0] = w[i][1] = w[i][2] = w[i][3] = 0.f;
    uint32_t xo = cb;
    uint32_t fa = xa[0], idm = 0;
    uint32_t ya[2], yb[2];
#pragma unroll
    for (int e = 0; e < 2; e++) {
        yb[e] = mapa(S + B_Y * 8, 4 * e + (g >> 1));
        ya[e] = yb[e] - B_Y * 8 + SM_CH + k * CH + YIN + (yo ^ (8 * j));
    }
    const uint32_t sc = prmt(eb + 0x04800000u, 0, 0x3232);
    uint32_t z = lds32(cb + XX + 4 * lane);
    mbar_wait(S + B_X * 8, 0);
    uint32_t A[3][4], x[5];
    ldm4(xo + xa[0], x[1], x[2], x[0], x[3]);
    ldm2(xo + xa[1], x[3], x[4]);
    auto send = [&](int e) { st_async2(ya[e], bmul(pack_bf(w[0][0], w[0][1]), sc), bmul(pack_bf(w[0][2], w[0][3]), sc), yb[e]); };
    auto tile = [&](auto nj, auto l4, auto par) {
        constexpr int NJ = decltype(nj)::value, L4 = decltype(l4)::value, P = decltype(par)::value;
        asm volatile("" : "+r"(z), "+r"(xo));
        uint32_t f0, f1;
        if (P < 2) ldm2(xo + fa, f0, f1);
        if (P < 2) send(P);
#pragma unroll
        for (int q = 1; q <= 8; q++) {
            const uint32_t ad = xo + xa[(q + 1) & 7] + 32 * ((q + 1) & 8);
            if (!L4) {
                A[0][0] = x[1]; A[0][1] = x[2]; A[0][2] = x[0] | z; A[0][3] = x[1] | z;
                x[0] = x[2]; x[1] = x[3]; x[2] = x[4];
                ldm2(ad, x[3], x[4]);
            } else {
                ldm4(ad, A[2][0], A[2][1], A[2][2], A[2][3]);
            }
            const float zero[4] = {0.f, 0.f, 0.f, 0.f};
#pragma unroll
            for (int i = 0; i < (NJ < 4 ? NJ : 4); i++) {
                const int s = 16 * i + 16 - 2 * q;
                if (q == 1) mma_hc(w[i], w[i + 1], A[0][0], A[0][1], A[0][2], A[0][3], R[s], R[s + 1]);
                else mma_h(w[i], A[0][0], A[0][1], A[0][2], A[0][3], R[s], R[s + 1]);
            }
            if (q == 4 && P < 2) mma_h8(w[1], f0, f1, idm);
            if (q == 7 && P < 2) {
                const uint32_t zz = A[0][0] & z;
                ya[P & 1] += 512 + zz; yb[P & 1] += 8 + zz;
            }
            if (q == 8 && NJ == 5) mma_hc(w[4], zero, A[0][0], A[0][1], A[0][2], A[0][3], R[64], R[65]);
#pragma unroll
            for (int e = 0; e < 4 * L4; e++) { A[0][e] = A[1][e]; A[1][e] = A[2][e]; }
        }
        xo += step;
    };
    tile(Int<5>(), Int<0>(), Int<2>());
    int n = 17, c = 1;
#pragma unroll 1
    do {
#pragma unroll 1
        do {
            tile(Int<5>(), Int<0>(), Int<0>());
            tile(Int<5>(), Int<0>(), Int<1>());
        } while (--c);
        n -= 4; c = 2;
        const int lane = laneid(), g = lane >> 2, t = lane & 3;
        fa = TAB - 768 + 16 * (lane & 15);
        idm = g == 2 * t ? 0x3C00u : (g == 2 * t + 1 ? 0x3C000000u : 0u);
#pragma unroll 1
        while (lds32v(S + SM_PROG + 4 * k) >= n) __nanosleep(40);
    } while (n > 5);
    ldm4(xo + xa[0], A[0][0], A[0][1], A[0][2], A[0][3]);
    ldm4(xo + xa[1], A[1][0], A[1][1], A[1][2], A[1][3]);
    tile(Int<5>(), Int<1>(), Int<0>());
    tile(Int<4>(), Int<1>(), Int<1>());
    tile(Int<3>(), Int<1>(), Int<0>());
    {
        uint32_t B[16][4], f0, f1;
        ldm2(xo + fa, f0, f1);
        send(1);
#pragma unroll
        for (int e = 0; e < 4; e++) { B[0][e] = A[0][e]; B[1][e] = A[1][e]; }
        const uint32_t x2 = xo + step;
#pragma unroll
        for (int q = 0; q < 8; q++) {
            ldm4(x2 + xa[q], B[8 + q][0], B[8 + q][1], B[8 + q][2], B[8 + q][3]);
            if (q < 6) ldm4(xo + xa[q + 2], B[q + 2][0], B[q + 2][1], B[q + 2][2], B[q + 2][3]);
        }
        w[3][0] = w[3][1] = w[3][2] = w[3][3] = 0.f;
        mma_h8(w[3], f0, f1, idm);
#pragma unroll
        for (int q = 0; q < 8; q++) {
            mma_h(w[1], B[q][0], B[q][1], B[q][2], B[q][3], R[14 - 2 * q], R[15 - 2 * q]);
            mma_h(w[2], B[q][0], B[q][1], B[q][2], B[q][3], R[30 - 2 * q], R[31 - 2 * q]);
            mma_h(w[3], B[8 + q][0], B[8 + q][1], B[8 + q][2], B[8 + q][3], R[14 - 2 * q], R[15 - 2 * q]);
        }
        ya[1] += 512; yb[1] += 8;
#pragma unroll
        for (int e = 0; e < 4; e++) w[0][e] = w[1][e];
        send(0);
#pragma unroll
        for (int e = 0; e < 4; e++) w[0][e] = w[2][e] + w[3][e];
        send(1);
    }
}

__global__ void __cluster_dims__(8, 1, 1) __launch_bounds__(NTHREADS, 1) fused_kernel(const __grid_constant__ Hot p, const __grid_constant__ Maps m) {
    extern __shared__ __align__(1024) char smem[];
    const uint32_t t0 = clk32();
    const int tid = threadIdx.x, lane = tid & 31, bx = blockIdx.x;
    {
        const uint32_t a = min(tid >> 5, 5), ln = 10 * bx + lane;
        const void* pa = at256(p.u + ln * 64, (&p.bre)[a]);
        asm volatile("{.reg .pred p; setp.lt.u32 p, %1, 10; setp.lt.and.u32 p, %2, 192, p; setp.lt.and.u32 p, %3, 1152, p;\n@p prefetch.global.L2 [%0];}"
                     ::"l"(pa), "r"(lane), "r"(tid), "r"(ln) : "memory");
    }
    const int g = lane >> 2, t = lane & 3, mi = lane >> 3, j = lane & 7;
    const uint32_t role = __shfl_sync(~0u, (tid >> 5) | ((uint32_t)((bx < 24 ? 0x5776666632103210ull : 0x5436666621043210ull) >> ((tid >> 3) & 60)) & 15) << 8 |
                                               max(4 * (bx >> 3), 5 * (bx >> 3) - 3) << 16 | bx << 24, 0);
    const int warp = role & 255, k = (role >> 8) & 255, cbase = (role >> 13) & 0x7F8, bid = role >> 24, r = bid & 7, cl = role >> 27;
    const int pair = cl > 2, nch = 4 + pair;
    uint32_t S = smem_u32(smem);
    asm volatile("" : "+r"(S));

    const int half = warp >= nch;
    const bool two = cl == 1 || cl == 2, extra = two && k == 7, svcwarp = (warp >> 2) == 2;
    KParams kp;
    uint32_t epoch, pre[8];
    if (k < nch) {
        const uint32_t ch = cbase + 8 * k + r;
        const char* pb = (const char*)p.u + (ch * 256 + half * 128 + lane * 4);
        kp.bre = ldg1(at256(pb, p.bre)); kp.bim = ldg1(at256(pb, p.bim));
        kp.cre = ldg1(at256(pb, p.cre)); kp.cim = ldg1(at256(pb, p.cim));
        kp.ldt = ldg16(at256(p.u + ch, lane & 1 ? p.dskip : p.logdt));
        kp.are = ldg1(at256(pb, p.are)); kp.aim = ldg1(at256(pb, p.aim));
        sts128(S + SM_CH + k * CH + 16 * lane + (half ? FT : (lane < 2 ? TAB : (lane < 8 ? TAB + 2048 : FT + 384))), 0u, 0u, 0u, 0u);
        sts32(S + SM_PROG + 4 * k, 13);
        kgen_addr(kp, S + SM_CH + k * CH + BOX + 3072 * half, lane);
        if (half) {
            const uint32_t a0 = BOX + 16 + 576 * (j & 1) + 16 * (j >> 1);
            pre[0] = keep(a0 + (mi == 1 ? 1152 : (mi == 2 ? 1136 : 0)));
            pre[1] = keep(a0 + 2304 + 1152 * (mi & 1) + 64 * (mi >> 1));
            pre[2] = keep(BOX + 16 + 4608 + 576 * (mi & 1) + 128 * (mi >> 1) + 16 * j);
            pre[3] = keep(BOX + 16 + (lane < 2 ? 1152 + 576 * lane : 2896));
            pre[4] = keep(xslot(8 + lane, 0));
            pre[5] = keep(xslot(7 + lane, 0));
            pre[6] = keep(FT + 504 - 128 * (t & 1) + 4 * g + (t & 2));
            pre[7] = keep(g == 2 * t ? 0x4432 : (g == 2 * t + 1 ? 0x3244 : 0x4444));
        } else {
            const uint32_t v = xslot(lane & 15, lane >> 4);
#pragma unroll
            for (int i = 0; i < 8; i++) pre[i] = __shfl_sync(~0u, v, j + i + (mi == 1 ? 17 : (mi == 2 ? 16 : 1)));
        }
    } else if (warp == 12) {
        if (elect()) {
            mbar_init(S + B_WR * 8, 1);
            mbar_init(S + B_ROWS * 8, 1);
            mbar_expect(S + B_WR * 8, 1152);
            bulk_g2s(S + SM_B + 2048, (const char*)p.u + p.wr * 256ll, 1152, S + B_WR * 8);
            while ((int)(clk32() - t0) < p.tn.t_rows) {}
            mbar_expect(S + B_ROWS * 8, two ? 36864 : 18432);
            const __nv_bfloat16* src = p.u + (8 * (cl & 14) + 2 * r + (cl & 1)) * 9216;
            bulk_g2s(S + SM_TOTAL - 18432, src, 18432, S + B_ROWS * 8);
            if (two) bulk_g2s(S + SM_CH + 4 * CH - 128, p.u + (113 + 2 * r) * 9216, 18432, S + B_ROWS * 8);
        }
    } else if (svcwarp) {
        if (elect()) {
#pragma unroll
            for (int i = 0; i < 16; i++) mbar_init(S + (warp & 3) * 128 + i * 8, warp > (i < 14 ? 10 : 9) ? 4 : 1);
            asm volatile("fence.mbarrier_init.release.cluster;" ::: "memory");
        }
        __syncwarp();
        sts128(S + SM_B + 16 * tid, 0x3F803F80u, 0x3F803F80u, 0x3F803F80u, 0x3F803F80u);
        if (tid < 256 + B_RAW) mbar_expect(S + lane * 8, (uint32_t)(0x0808480101180804ull >> (8 * max(lane - 7, 0)) & 255) * (lane < B_TOP ? 128 * nch : 128));
    }
    if (svcwarp || extra) epoch = ld_rlx(at256(p.u + bid * 16, p.ep));
    __syncthreads();
    asm volatile("barrier.cluster.arrive.relaxed.aligned;" ::: "memory");
    const uint2* sp = &p.s->stat[256 * r + 2 * (tid & 127)];
    uint4 sw;
    if (svcwarp) sw = ld_rlx4(sp);
    if (svcwarp || extra) {
        const uint32_t tag = ~epoch & 1;
        const int tile = extra ? 15 : cl, wj = extra ? warp + 2 * cl - 15 : warp & 3;
        float d2[4] = {0, 0, 0, 0}, d3[4] = {0, 0, 0, 0}, d4[4] = {0, 0, 0, 0}, d5[4] = {0, 0, 0, 0}, d6[4] = {0, 0, 0, 0}, d7[4] = {0, 0, 0, 0};
        const uint32_t xa = S + (extra ? SM_CH + 4 * CH - 128 : SM_TOTAL - 18432) + (8 * (mi >> 1) + 2 * wj + (mi & 1)) * 1152 + 16 * j;
        const uint32_t wa = S + SM_B + 4104 - 2056 * (g & 1) + 64 * (g >> 2) + 16 * t + 2 * (g & 2), ones = 0x3F803F80u;
        uint32_t wv[18];
        mbar_wait_short(S + B_WR * 8);
#pragma unroll
        for (int i = 0; i < 18; i++) wv[i] = lds32(wa + 128 * (i >> 1) + 8 * (i & 1));
        spin_until(t0, 2400);
#pragma unroll
        for (int i = 0; i < 9; i++) mma_bf(d5, ones, ones, ones, ones, wv[2 * i], wv[2 * i + 1]);
        float wsum = d5[1] + __shfl_xor_sync(~0u, d5[1], 1);
        wsum += __shfl_xor_sync(~0u, wsum, 2);
        mbar_wait_short((S + B_ROWS * 8) | (__float_as_uint(wsum) & p.tn.zero));
        __syncwarp();
#pragma unroll
        for (int i = 0; i < 9; i++) {
            const uint4 x = lds128(xa + 128 * i);
            mma_bf8(d3, x.x, x.y, x.x);
            mma_bf8(d4, x.x, x.y, x.y);
            mma_bf8(d6, x.z, x.w, x.z);
            mma_bf8(d7, x.z, x.w, x.w);
            mma_bf(d2, x.x, x.y, x.z, x.w, wv[2 * i], wv[2 * i + 1]);
        }
        float sx = d2[0] + d2[2], sq = (g & 1) ? (d3[1] + d4[3]) + (d6[1] + d7[3]) : (d3[0] + d4[2]) + (d6[0] + d7[2]);
        float dot = (t & 1) ? d2[3] : d2[1];
        sx += __shfl_xor_sync(~0u, sx, 4);
        sq = __shfl_sync(~0u, sq, 9 * mi) + __shfl_sync(~0u, sq, 9 * mi + 4);
        dot += __shfl_xor_sync(~0u, dot, 1);
        dot += __shfl_xor_sync(~0u, dot, 6);
        const float mean = sx * (1.f / 576.f), var = fmaxf(sq * (1.f / 576.f) - mean * mean, 0.f);
        const float mu = bf_round(mean), sd = bf_round(sqrt_ap(bf_round(bf_round(var) + 1e-5f)));
        const uint32_t idx = 2047 - (128 * (tile & 14) + 32 * r + 16 * (tile & 1) + 8 * (mi >> 1) + 2 * wj + (mi & 1));
        const uint32_t rb = pack_bf(0.f, (dot - mu * wsum) * rcpf(sd));
        uint2 v = make_uint2((__float_as_uint(mu) >> 16) | __float_as_uint(sd), (((rb ^ (((int)rb >> 31) | 0x80000000u)) >> 1) & 0x7FFF8000u) | (tag << 31) | idx);
        uint2* const dst = &p.s->stat[256 * r + 16 * tile];
        if (extra) {
            if (j == 0) st_rlx2(dst + 4 * wj + mi, v.x, v.y);
            bar_arrive(13, 224);
        } else {
        const uint32_t ga = S + SM_B + 3200 + 32 * wj;
        if (j == 0) sts64(ga + 8 * mi, v.x, v.y);
        bar_sync(15, 128);
        if (tid < 272) {
            v = lds64(ga + 8 * lane);
            st_rlx2(dst + lane, v.x, v.y);
        }
        if (lane == 0) mbar_arrive(S + (B_EMPTY + 10) * 8);
        }
    }

    if (k < nch) {
        const uint32_t cb = S + SM_CH + k * CH, scr = cb + BOX + 3072 * half, oth = cb + BOX + 3072 - 3072 * half;
        float d[5][4], k0;
        kp.dsk = __shfl_sync(~0u, kp.ldt, 1);
        kp.ldt = __shfl_sync(~0u, kp.ldt, 0);
        const uint32_t eb = kgen(kp, scr, oth, 1 + k, lane, d, k0, k > 7 - nch ? 3 - 2 * half : 2, ((p.tn.stag >> warp) & 1) ? S + (B_EMPTY + 10) * 8 : 0, p.tn.zero);
        __syncwarp();
#pragma unroll
        for (int i = 0; i < 5; i++)
            if (half == (i < 3)) sts128f(kp.sa + i * 512, d[i][0], d[i][1], d[i][2], d[i][3]);
        bar_sync(1 + k, 64);
        auto both = [&](int i) {
            const uint4 v = lds128(oth + i * 512 + lane * 16);
            d[i][0] += __uint_as_float(v.x); d[i][1] += __uint_as_float(v.y); d[i][2] += __uint_as_float(v.z); d[i][3] += __uint_as_float(v.w);
        };
        if (half) {
            both(3); both(4);
            const uint32_t o = cb + FT + 56 + 2 * lane, q = cb + pre[6];
#pragma unroll
            for (int e = 0; e < 2; e++) {
                const uint32_t a = pack_h(d[3][e], d[3][2 + e]), b = pack_h(d[4][e], d[4][2 + e]);
                sts16(o + 128 - 128 * e, a); sts16(o + 192 - 128 * e, a >> 16);
                sts16(q + 64 - 64 * e, b); sts16(q + 96 - 64 * e, b >> 16);
            }
            bar_sync(1 + k, 64);
        } else {
            {
                both(0); both(1); both(2);
                const uint32_t a[2] = {pack_h(d[0][0], d[1][0]), pack_h(d[0][2], d[1][2])}, b[2] = {pack_h(d[0][1], d[1][1]), pack_h(d[0][3], d[1][3])};
                const uint32_t c[2] = {pack_h(d[2][0], d[2][1]), pack_h(d[2][2], d[2][3])};
                uint32_t last = pack_h(k0, k0);
                const uint32_t o = cb + TAB + 32 + 16 * lane;
                sts16(cb + TAB + 28, last);
#pragma unroll
                for (int h = 0; h < 4; h++) {
                    const uint32_t e = h < 2 ? b[h] : c[h - 2], pv = __shfl_sync(~0u, lane == 31 ? last : e, lane - 1);
                    if (h < 2) sts128(o + 512 * h, prmt(a[h], pv, 0x7610), prmt(a[h], 0, 0x1032), prmt(e, a[h], 0x7610), prmt(e, 0, 0x1032));
                    else sts128(o + 512 * h, prmt(pv, 0, 0x3232), prmt(e, pv, 0x7610), prmt(e, 0, 0x1032), prmt(e, 0, 0x3232));
                    last = e;
                }
                if (lane == 31) sts128(o + 1552, prmt(last, 0, 0x3232), prmt(last, 0, 0x3232), last & 0xFFFF0000u, 0u);
                __syncwarp();
            }
            near_lags(S, k, 64 * r + 16 * ((2 * k + (cbase >> 2) + (r >> 2)) & 3), eb, pre, p.tn.c256);
            return;
        }
    }

    const int ph0 = pair & ~r, f0 = pair ? 32 * (bid & ~1) + 768 : 64 * bid;
    if (k == 7) {
        spin_until(t0, p.tn.t_pf);
#pragma unroll 1
        for (int e = tid - 224; e < 576; e += 64) {
            asm volatile("prefetch.global.L2 [%0];" ::"l"(p.wg + e * F_ + f0) : "memory");
            __nanosleep(100);
        }
        return;
    }
    if (warp == 12) {
        if (elect()) {
            asm volatile("prefetch.tensormap [%0];" ::"l"(m.w + ph0) : "memory");
            asm volatile("prefetch.tensormap [%0];" ::"l"(&m.u) : "memory");
            spin_until(t0, p.tn.t_tile);
            auto raw = [&]() {
                mbar_expect(S + B_RAW * 8, 256 * PITCH);
                asm volatile("cp.async.bulk.tensor.5d.shared::cluster.global.mbarrier::complete_tx::bytes [%0], [%1, {%3, 0, %4, 0, 0}], [%2];"
                             ::"r"(S + SM_RAW), "l"(&m.u), "r"(S + B_RAW * 8), "r"(cbase), "r"(4 * r) : "memory");
            };
            raw();
            uint32_t bar = S + B_FULL * 8, dst = S + SM_W, em = 0x1249400u, wm = pair ? p.tn.win5 : p.tn.win4, wb = bar;
#pragma unroll 1
            for (int ph = ph0; ph < 3; ph += 1 + (pair & r)) {
                const int c0 = ph < 2 ? f0 : cbase, c1 = ph < 2 ? 0 : 576 * r;
#pragma unroll 1
                for (int n = 0; n < 576; n += 64) {
                    if (wm & 3) { wb += 8 * (wm & 3); mbar_wait(wb - 8, 0); }
                    if (em & 1) mbar_wait(bar + 8 * (B_EMPTY - B_FULL), 0);
                    mbar_expect(bar, ph < 2 ? 8192 : 128 * 40);
                    tma2d(dst, m.w + ph, c0, c1 + n, bar);
                    bar += 8; em >>= 1; wm = wm >> 2 | 0x40000000u;
                    dst = dst == S + SM_W + (NRING - 1) * 8192 ? S + SM_W : dst + 8192;
                }
            }
        }
        return;
    }

    if (warp == 15) {
        asm volatile("barrier.cluster.wait.aligned;" ::: "memory");
        sts32(S + SM_SKIP + 4 * j, 0u);
        const uint32_t ob = mapa(S, g);
        bar_sync(13, two ? 224 : 160);
        const uint4 ka = lds128(S + SM_B + 256 + 16 * lane), kb = lds128(S + SM_B + 768 + 16 * lane);
        uint32_t k0 = ka.x, k1 = ka.y, mine = 0, c = 0;
        int rank = lane;
#pragma unroll 1
        for (int pass = 0;; pass++) {
#pragma unroll 1
            for (int n = 0; n < (pass < 2 ? 4 : 8); n++) {
                const uint32_t a = __viaddmin_u32(k0, c, __viaddmin_u32(k1, c, ka.z + c)), b = __viaddmin_u32(ka.w, c, __viaddmin_u32(kb.x, c, kb.y + c));
                c += ~__reduce_min_sync(~0u, __vimin3_u32(a, b, __viaddmin_u32(kb.z, c, kb.w + c)));
                if ((pass < 2 ? t : j) == n) mine = c;
            }
            if (pass == 2) break;
            asm volatile("st.async.shared::cluster.mbarrier::complete_tx::bytes.b32 [%0], %1, [%2];" ::"r"(ob + SM_CAND + 128 * pass + 16 * r + 4 * t), "r"(~mine), "r"(ob + (B_TOP + pass) * 8) : "memory");
            mbar_wait_short(S + (B_TOP + pass) * 8);
            const uint32_t v = lds32(S + SM_CAND + 4 * lane);
            if (pass) {
                k0 = v; k1 = lds32(S + SM_CAND + 128 + 4 * lane); c = 0;
            } else {
                uint32_t cn[4] = {0, 0, 0, 0};
#pragma unroll 4
                for (int e = 0; e < 128; e += 16) {
                    const uint4 o = lds128(S + SM_CAND + e);
                    cn[0] += (o.x - v) >> 31; cn[1] += (o.y - v) >> 31; cn[2] += (o.z - v) >> 31; cn[3] += (o.w - v) >> 31;
                }
                const int rk = (cn[0] + cn[1]) + (cn[2] + cn[3]);
                if (!__any_sync(~0u, t == 3 && rk < 8)) { rank = rk; mine = ~v; break; }
            }
        }
        const uint32_t row = ~mine & 2047, ix = (row & 0xE0) * 8 + ((row >> 3) & 0xE0) + (row & 0x11) + ((row >> 2) & 2) + (row & 6) * 2;
        const uint32_t mr = __reduce_or_sync(~0u, rank == r ? row : 0u);
        if (elect()) {
            bulk_mc(S + SM_B + BP * r, p.u + mr * D_, 1152, S + B_XS * 8);
        }
        const bool own = rank < 8 && (ix >> 8) == r;
        const uint32_t m2 = 2 * mine, rb = (m2 ^ ((~(int)m2 >> 31) | 0x80000000u)) & 0xFFFF0000u;
        if (rank < 8) sts64(S + SM_SEL + 8 * rank, ix | rb, row | ((row & 0x700) + 32 * (row & 6) + 2 * (row & 24) + 8 * (row & 1)) << 16);
        if (own) asm volatile("red.shared.or.b32 [%0], %1;" ::"r"(S + SM_SKIP + 4 * (ix & 7)), "r"(1u << ((ix >> 3) & 31)) : "memory");
        const int no = __popc(__ballot_sync(~0u, own));
        if (lane < 2) mbar_expect(S + (B_FIN + lane) * 8, lane ? 0 : no * (nch - 2) * 256);
        __syncwarp();
        const uint2 sv = lds64(S + SM_SEL + 8 * j);
        float sa, sb;
        asm volatile("ld.shared::cluster.v2.f32 {%0, %1}, [%2];" : "=f"(sa), "=f"(sb) : "r"(mapa(S + SM_ST + (sv.y >> 16), (sv.x >> 8) & 7)) : "memory");
        const float m1 = -sb * rcpf(sa);
        const uint32_t mu = pack_bf(m1, m1), bw = S + SM_B + BP * j + 16 * mi;
        sts32(S + SM_PROG + 32 + 4 * j, __float_as_uint(sa + sa));
        mbar_wait_short(S + B_XS * 8);
#pragma unroll 1
        for (int n = 0; n < 1152; n += 576) {
            uint4 v[9];
#pragma unroll
            for (int e = 0; e < 9; e++) v[e] = lds128(bw + n + 64 * e);
#pragma unroll
            for (int e = 0; e < 9; e++) sts128(bw + n + 64 * e, bsub(v[e].x, mu), bsub(v[e].y, mu), bsub(v[e].z, mu), bsub(v[e].w, mu));
        }
        bar_arrive(14, 160);
    }

    if (svcwarp) {
        const uint32_t tag = ~epoch & 1;
        const int fw = warp & 3, i = tid & 127;
        uint32_t xbar = mapa(S + B_X * 8, g), xd = keep(xbar - B_X * 8 + SM_CH + xslot(8 + 2 * r + (t >> 1), t & 1) + 256 * (fw & 2));
        uint32_t ra = keep(S + SM_RAW + (64 * mi + j + 4 * (fw & 2)) * PITCH), sa = keep(S + SM_ST + 16 * t + 128 * (fw & 2));
        const uint32_t ta = keep(S + SM_ST + 16 * (i & 0x71) + 32 * (i & 6) + 4 * (i & 8));
        asm volatile("barrier.cluster.wait.aligned;" ::: "memory");
        mbar_wait_short(S + B_RAW * 8);
#pragma unroll 1
        for (int it = 0; it < SPIN_LIMIT && (int)((sw.y ^ -tag) | (sw.w ^ -tag)) < 0; it++) sw = ld_rlx4(sp);
        sts64(S + SM_B + 256 + 8 * i, ~sw.y, ~sw.w);
        {
            const float r0 = 0.5f * rcpf(bf_hi(sw.x)), r1 = 0.5f * rcpf(bf_hi(sw.z));
            sts128f(ta, r0, -bf_lo(sw.x) * r0, r1, -bf_lo(sw.z) * r1);
        }
        bar_sync(13, two ? 224 : 160);
        if (i == 0) st_rlx(&p.s->ep[bid * 8], epoch + 1);
        {
#pragma unroll 1
            for (int u = fw; u < fw + 4; u++) {
                uint4 s[4];
#pragma unroll
                for (int e = 0; e < 4; e++) s[e] = lds128(sa + 64 * e);
#pragma unroll 1
                for (int n = u & 1; n < nch; n += 2) {
                    uint32_t a[4];
                    ldm4t(ra + 16 * n, a);
#pragma unroll
                    for (int e = 0; e < 4; e++)
                        a[e] = pack_h(fmaf(bf_lo(a[e]), __uint_as_float(s[e].x), __uint_as_float(s[e].y)), fmaf(bf_hi(a[e]), __uint_as_float(s[e].z), __uint_as_float(s[e].w)));
                    st_async4(xd + n * CH, a[0], a[1], a[2], a[3], xbar);
                }
                xd += 1024; ra += 16 * PITCH; sa += 512; xbar |= 8;
            }
        }
        const int mt = (fw + 3) & 3;
        const uint32_t bw = keep(S + SM_B + BP * j + 16 * (i >> 3)), ba = keep(S + SM_B + BP * j + 16 * mi);
        const uint32_t aa = keep(S + SM_W + (8 * (mi >> 1) + j) * 128 + (((2 * mt + (mi & 1)) ^ j) << 4));
        uint32_t bar = S + B_FULL * 8, of = 0;
        bar_sync(14, 160);
        const uint2 sv = lds64(S + SM_SEL + 8 * j), ri = lds64(S + SM_PROG + 32 + 8 * t);
        float r0 = __uint_as_float(ri.x), r1 = __uint_as_float(ri.y);
        const uint32_t tx = clk32();
        float d[4][4];
#pragma unroll 1
        for (int ph = ph0;; ph++) {
            if (ph == 2) {
                bar_sync(15, 128);
                spin_until(tx, p.tn.da);
                r0 = r1 = 1.f;
                const uint32_t* const hp = p.s->h + 2304 * r + 4 * i;
                uint4 v[5];
                const uint32_t tm = -tag;
#pragma unroll 1
                for (int it = 0; it < SPIN_LIMIT; it++) {
                    uint32_t bad = 0;
#pragma unroll
                    for (int n = 0; n < 5; n++) v[n] = ld_rlx4(hp + (n < 4 ? 512 * n : 1792));
#pragma unroll
                    for (int n = 0; n < 5; n++) bad |= lop_ne(v[n].x, v[n].z, tm);
                    if (!(bad & 1)) break;
                }
#pragma unroll
                for (int n = 0; n < 5; n++) sts128(bw + (n < 4 ? 256 * n : 896), v[n].x, v[n].y, v[n].z, v[n].w);
                bar_sync(15, 128);
            }
            if (ph == 2 && mt >= nch - 2) break;
#pragma unroll
            for (int e = 0; e < 4; e++) d[0][e] = d[1][e] = d[2][e] = d[3][e] = 0.f;
#pragma unroll 1
            for (int n = 0; n < 1152; n += 384) {
                uint32_t a[12][4], b[24];
                mbar_wait(bar + 8 * min(lane, 2), 0);
                __syncwarp();
#pragma unroll
                for (int e = 0; e < 12; e++) {
                    if (!(e & 1)) ldm4(ba + n + 32 * e, b[2 * e], b[2 * e + 1], b[2 * e + 2], b[2 * e + 3]);
                    ldm4t(aa + of + 2048 * e, a[e]);
                }

#pragma unroll
                for (int e = 0; e < 12; e++) mma_bf(d[e & 3], a[e][0], a[e][1], a[e][2], a[e][3], b[2 * e], b[2 * e + 1]);
                if (lane == 0) mbar_arrive(min(bar + (B_EMPTY + NRING - B_FULL) * 8, S + 63 * 8));
                bar += 24;
                of = of == 8192 * (NRING - 3) ? 0 : of + 24576;
            }
#pragma unroll
            for (int e = 0; e < 4; e++) d[0][e] = (d[0][e] + d[1][e]) + (d[2][e] + d[3][e]);
            uint32_t k0 = pack_bf(d[0][0] * r0, d[0][1] * r1), k1 = pack_bf(d[0][2] * r0, d[0][3] * r1);
            const uint32_t ea = SM_FIN + 6144 + 8 * i, eb = B_UP * 8;
            if (ph == 0) {
                const uint32_t ob = mapa(S, r & ~pair);
                st_async2(ob + ea, k0, k1, ob + eb);
                ph += pair;
                continue;
            }
            if (ph == 1) {
                k0 = pack_bf(silu_half(0.5f * bf_lo(k0)), silu_half(0.5f * bf_hi(k0))); k1 = pack_bf(silu_half(0.5f * bf_lo(k1)), silu_half(0.5f * bf_hi(k1)));
                mbar_wait_short((S + eb) | (k0 & k1 & p.tn.zero));
                const uint2 v = lds64(S + ea);
                k0 = bmul(k0, v.x); k1 = bmul(k1, v.y);
                __syncwarp();
            }
            k0 = movm(k0); k1 = movm(k1);
            if (ph == 2) {
                const uint32_t ob = mapa(S, (__shfl_sync(~0u, sv.x, g) >> 8) & 7);
                st_async2(ob + SM_FIN + 768 * g + 96 * r + 32 * mt + 8 * t, k0, k1, ob + B_FIN * 8);
                break;
            }
            const uint32_t o = __shfl_xor_sync(~0u, (lane & 1) ? k0 : k1, 1);
            st_rlx2(p.s->h + 4 * f0 + 64 * mt + 31 * (lane & 1) + lane, (((lane & 1) ? o : k0) & ~1u) | tag, (lane & 1) ? k1 : o);
        }
        const int l = min(lane, 4 * nch - 1);
        int n = fw;
#pragma unroll 1
        for (uint32_t own = __ballot_sync(~0u, ((sv.x >> 8) & 7) == r) & 255; own; own &= own - 1) {
            if (n-- & 3) continue;
            const int tk = __ffs(own) - 1;
            const uint2 e = lds64(S + SM_SEL + 8 * tk), st = lds64(S + SM_ST + (e.y >> 16));
            const uint32_t ix = e.x, x = lds32(S + SM_RAW + (16 * (ix & 12) + ((ix >> 2) & 60) + (ix & 3)) * PITCH + 4 * l);
            const uint32_t yb = S + SM_CH + YIN + (l >> 2) * CH + 16 * (ix & 0xE0) + 128 * (l & 3) + 16 * (((ix >> 3) ^ ((l >> 1) + (cbase >> 2))) & 3) + 2 * (ix & 7);
            const float sg = 0.5f * sigm(bf_hi(ix));
            const uint32_t hx = pack_bf(fmaf(bf_lo(x), __uint_as_float(st.x), __uint_as_float(st.y)), fmaf(bf_hi(x), __uint_as_float(st.x), __uint_as_float(st.y))), sg2 = pack_bf(sg, sg);
            mbar_wait((S + B_FIN * 8) | (hx & sg2 & p.tn.zero), 0);
            float a[2] = {0.f, 0.f}, b[2] = {0.f, 0.f};
#pragma unroll
            for (int q = 0; q < 8; q++) {
                const uint32_t v = lds32(S + SM_FIN + 768 * tk + 96 * q + 4 * (l & 24) + 8 * (l & 3) + (l & 4));
                a[q & 1] += bf_lo(v); b[q & 1] += bf_hi(v);
            }
            const uint32_t hv = badd(hx, bmul(pack_bf(a[0] + a[1], b[0] + b[1]), sg2)), gt = pack_bf(silu_half(bf_lo(hv)), silu_half(bf_hi(hv)));
            mbar_wait((S + B_Y * 8 + ((ix >> 2) & 56)) | (gt & p.tn.zero), 0);
            *(uint32_t*)(p.out + (e.y & 2047) * D_ + cbase + 2 * l) = bfma(lds16(yb) | (lds16(yb + 64) << 16), gt, x);
        }
        return;
    }

    mbar_wait(S + B_X * 8, 0);
    if (k < nch) {
        const uint32_t cb = S + SM_CH + k * CH, bx = cb + BOX + 16;
        float u[4][4], v[4][4], w[4][4];
#pragma unroll
        for (int i = 0; i < 4; i++) v[i][0] = v[i][1] = v[i][2] = v[i][3] = w[i][0] = w[i][1] = w[i][2] = w[i][3] = 0.f;
        uint2 T4[10];
        const uint32_t ta = cb + FT + 4 * (g - t);
#pragma unroll
        for (int e = 0; e < 10; e++) T4[e] = lds64(ta + 24 + 32 * e + 4 * (g - t));
        const uint32_t tb = prmt(lds32(cb + FT + 308), 0, pre[7]);
        const uint32_t a4 = cb + pre[0], a8 = cb + pre[1], at = cb + pre[2], hb = cb + pre[3], o = bx + 16 * lane;
        uint32_t xi = cb + pre[4], xp = cb + pre[5], hs = cb + XX;
#pragma unroll 1
        for (int n = 9; n > 0; n -= 4) {
            {
                const uint4 hv = lds128(hs);
                hs = hb + 496;
                const uint2 v0 = lds64(xp + 8);
                const uint4 v1 = lds128(xp ^ 32), v2 = lds128(xi), v3 = lds128(xi ^ 32);
                xi += 1024; xp += 1024;
                __syncwarp();
                if (lane < 3) sts128(hb - 16, hv.x, hv.y, hv.z, hv.w);
                const uint32_t P[13] = {v0.x, v0.y, v1.x, v1.y, v1.z, v1.w, v2.x, v2.y, v2.z, v2.w, v3.x, v3.y, v3.z};
                uint32_t Q[12], s2[12], s4[10], b3[11], b5[9];
#pragma unroll
                for (int e = 0; e < 12; e++) { Q[e] = prmt(P[e], P[e + 1], 0x5432); s2[e] = hadd(P[e], Q[e]); }
#pragma unroll
                for (int e = 0; e < 11; e++) b3[e] = hadd(Q[e], s2[e + 1]);
#pragma unroll
                for (int e = 0; e < 10; e++) s4[e] = hadd(s2[e], s2[e + 1]);
#pragma unroll
                for (int e = 0; e < 9; e++) b5[e] = hadd(s4[e + 1], P[e + 3]);
                sts128(o, b3[3], b3[4], b3[5], b3[6]);
                sts128(o + 1152, b3[7], b3[8], b3[9], b3[10]);
                sts128(o + 576, b5[0], b5[1], b5[2], b5[3]);
                sts128(o + 1728, b5[4], b5[5], b5[6], b5[7]);
                if (n > 4) {
                    sts128(o + 4608, s2[4], s2[5], s2[6], s2[7]);
                    sts128(o + 5184, s2[8], s2[9], s2[10], s2[11]);
                    sts128(o + 2304, hadd(b3[0], s4[2]), hadd(b3[1], s4[3]), hadd(b3[2], s4[4]), hadd(b3[3], s4[5]));
                    sts128(o + 3456, hadd(b3[4], s4[6]), hadd(b3[5], s4[7]), hadd(b3[6], s4[8]), hadd(b3[7], s4[9]));
                    sts128(o + 4032, hadd(s4[0], b5[1]), hadd(s4[1], b5[2]), hadd(s4[2], b5[3]), hadd(s4[3], b5[4]));
                    sts128(o + 2896, hadd(s4[4], b5[5]), hadd(s4[5], b5[6]), hadd(s4[6], b5[7]), hadd(s4[7], b5[8]));
                }
                __syncwarp();
            }
            uint32_t A[8][4];
#pragma unroll
            for (int e = 0; e < 8; e++) ldm4t(a4 + 64 * e, A[e]);
#pragma unroll
            for (int e = 0; e < 8; e++)
#pragma unroll
                for (int b = 3; b >= e / 2; b--) {
                    const uint2 T = T4[2 * (b - e / 2) + 1 - (e & 1)];
                    if (e == 0) mma_hc(u[b], v[b], A[e][0], A[e][1], A[e][2], A[e][3], T.x, T.y);
                    else mma_h(u[b], A[e][0], A[e][1], A[e][2], A[e][3], T.x, T.y);
                }
            if (n == 9) mbar_wait_short(S + (B_X + 1) * 8);
#pragma unroll
            for (int e = 0; e < 2; e++)
                stm4t(cb + TAB + 2304 - 256 * n + 512 * e + 16 * lane, pack_h(u[2 * e][0], u[2 * e][1]), pack_h(u[2 * e][2], u[2 * e][3]),
                      pack_h(u[2 * e + 1][0], u[2 * e + 1][1]), pack_h(u[2 * e + 1][2], u[2 * e + 1][3]));
            __syncwarp();
            sts32v(S + SM_PROG + 4 * k, n);
            if (n == 1) break;
            uint32_t C[4][4], E[2][4], T8[16];
#pragma unroll
            for (int e = 0; e < 4; e++) ldm4t(a8 + 128 * e, C[e]);
#pragma unroll
            for (int e = 0; e < 2; e++) ldm4t(at + 256 * e, E[e]);
#pragma unroll
            for (int e = 0; e < 8; e++) T8[e] = lds32(ta + 376 + 32 * (e >> 1) - 16 * (e & 1));
#pragma unroll
            for (int e = 7; e >= 0; e--)
#pragma unroll
                for (int b = 0; b <= e / 2; b++) {
                    const uint2 T = T4[2 * (4 + b - e / 2) + 1 - (e & 1)];
                    if (e == 7) mma_hc(v[b], w[b], A[e][0], A[e][1], A[e][2], A[e][3], T.x, T.y);
                    else mma_h(v[b], A[e][0], A[e][1], A[e][2], A[e][3], T.x, T.y);
                }
#pragma unroll
            for (int e = 3; e >= 0; e--) {
                mma_h8(v[e], E[e >> 1][2 * (e & 1)], E[e >> 1][2 * (e & 1) + 1], tb);
#pragma unroll
                for (int b = 3; b >= e; b--) mma_h(v[b], C[e][0], C[e][1], C[e][2], C[e][3], T8[2 * (b - e)], T8[2 * (b - e) + 1]);
            }
            if (n == 9) {
#pragma unroll
                for (int e = 8; e < 16; e++) T8[e] = lds32(ta + 376 + 32 * (e >> 1) - 16 * (e & 1));
#pragma unroll
                for (int e = 3; e >= 0; e--)
#pragma unroll
                    for (int b = 0; b < 4; b++) mma_h(w[b], C[e][0], C[e][1], C[e][2], C[e][3], T8[2 * (4 + b - e)], T8[2 * (4 + b - e) + 1]);
            }
        }
    }

  {
    int lane;
    asm volatile("mov.u32 %0, %%laneid;" : "=r"(lane));
    const int g = lane >> 2, t = lane & 3, mi = lane >> 3, j = lane & 7, sh = (cbase >> 3) & 1;
    mbar_wait_short(S + B_SEL * 8);
    if (k < nch - 2 || k == 5) {
        const int one = k == 2, st = k == 5 ? 1 : 2, kk = one ? 4 - 4 * sh : sh + 2 * st - 2;
        const int q0 = k == 1, qx = q0 + (one & (t >> 1)), cx = 16 * kk + 8 * (one ? t & 1 : t);
        uint32_t xa = S + SM_RAW + (16 * (g & 4) + (g & 3) + 8 * qx) * PITCH + cx, sa = S + SM_ST + 16 * (g & 4) + 8 * (g & 3) + 256 * qx, bar = S + (B_Y + qx) * 8;
        uint32_t ya = S + SM_CH + YIN + kk * CH + (j >> 2) * (one ? 512 : CH) + 128 * (j & 2) + 128 * (mi & 1) + 64 * (j & 1) + 512 * q0 +
                      16 * ((mi >> 1) ^ (one ? 2 * sh + ((j >> 1) & 1) : j >> 1));
        uint32_t sk = lds32(S + SM_SKIP + 4 * g) >> (4 * qx);
        char* o = (char*)p.out + ((256 * qx + 32 * r + 4 * (g & 2) + 2 * (g >> 2) + (g & 1)) * D_ + cbase) * 2 + cx;
#pragma unroll 1
        for (int n = 0; n < 8; n += st) {
            uint2 x[4];
            uint32_t gt[8], y[2][4];
#pragma unroll
            for (int e = 0; e < 4; e++) {
                x[e] = lds64(xa + (128 * (e & 1) + 2 * (e & 2)) * PITCH);
                const uint2 s = lds64(sa + 128 * (e & 1) + 16 * (e & 2));
                const float a = __uint_as_float(s.x), b = __uint_as_float(s.y);
                gt[2 * e] = pack_bf(silu_half(fmaf(bf_lo(x[e].x), a, b)), silu_half(fmaf(bf_hi(x[e].x), a, b)));
                gt[2 * e + 1] = pack_bf(silu_half(fmaf(bf_lo(x[e].y), a, b)), silu_half(fmaf(bf_hi(x[e].y), a, b)));
            }
            mbar_wait(bar | (((gt[0] | gt[1] | gt[2]) | (gt[3] | gt[4] | gt[5]) | (gt[6] | gt[7])) & p.tn.zero), 0);
            __syncwarp();
            ldm4t(ya, y[0]);
            ldm4t(ya ^ 32, y[1]);
#pragma unroll
            for (int e = 0; e < 4; e++)
                asm volatile("{.reg .pred p; setp.eq.u32 p, %3, 0;\n@p st.global.v2.u32 [%0], {%1, %2};}" ::"l"(o + (8 * (e & 1) + 16 * (e & 2)) * D_),
                             "r"(bfma(y[e >> 1][2 * (e & 1)], gt[2 * e], x[e].x)), "r"(bfma(y[e >> 1][2 * (e & 1) + 1], gt[2 * e + 1], x[e].y)), "r"(sk & (1 << e)) : "memory");
            xa += 8 * PITCH * st; sa += 256 * st; ya += 512 * st; bar += 8 * st; sk >>= 4 * st; o += 512 * D_ * st;
        }
    }
  }
}

typedef CUresult (*EncodeFn)(CUtensorMap*, CUtensorMapDataType, cuuint32_t, void*, const cuuint64_t*, const cuuint64_t*, const cuuint32_t*,
                             const cuuint32_t*, CUtensorMapInterleave, CUtensorMapSwizzle, CUtensorMapL2promotion, CUtensorMapFloatOOBfill);

static void make2d(EncodeFn enc, CUtensorMap* m, const void* base, uint64_t cols, uint64_t rows, uint32_t bc = 64) {
    cuuint64_t gd[2] = {cols, rows};
    cuuint64_t gs[1] = {cols * 2};
    cuuint32_t bd[2] = {bc, 64}, es[2] = {1, 1};
    enc(m, CU_TENSOR_MAP_DATA_TYPE_BFLOAT16, 2, const_cast<void*>(base), gd, gs, bd, es, CU_TENSOR_MAP_INTERLEAVE_NONE, CU_TENSOR_MAP_SWIZZLE_128B,
        CU_TENSOR_MAP_L2_PROMOTION_L2_128B, CU_TENSOR_MAP_FLOAT_OOB_FILL_NONE);
}

static void make5d(EncodeFn enc, CUtensorMap* m, const void* base, uint32_t cols, CUtensorMapSwizzle sw) {
    cuuint64_t gd[5] = {D_, 2, 32, 8, 4};
    cuuint64_t gs[4] = {D_ * 2, D_ * 16, D_ * 512, D_ * 4};
    cuuint32_t bd[5] = {cols, 2, 4, 8, 4}, es[5] = {1, 1, 1, 1, 1};
    enc(m, CU_TENSOR_MAP_DATA_TYPE_BFLOAT16, 5, const_cast<void*>(base), gd, gs, bd, es, CU_TENSOR_MAP_INTERLEAVE_NONE, sw,
        CU_TENSOR_MAP_L2_PROMOTION_NONE, CU_TENSOR_MAP_FLOAT_OOB_FILL_NONE);
}

static Tune g_tune = {2000, 24807, 256, 1431655504, 1431635200, 800, 5000, 6500, 0};

static int max_clusters() {
    cudaFuncSetAttribute(fused_kernel, cudaFuncAttributeMaxDynamicSharedMemorySize, SM_TOTAL);
    cudaLaunchConfig_t cfg = {};
    cudaLaunchAttribute at[1];
    at[0].id = cudaLaunchAttributeClusterDimension;
    at[0].val.clusterDim.x = 8; at[0].val.clusterDim.y = 1; at[0].val.clusterDim.z = 1;
    cfg.gridDim = dim3(NCTA); cfg.blockDim = dim3(NTHREADS); cfg.dynamicSmemBytes = SM_TOTAL; cfg.attrs = at; cfg.numAttrs = 1;
    int n = 0;
    if (cudaOccupancyMaxActiveClusters(&n, fused_kernel, &cfg) != cudaSuccess) { cudaGetLastError(); n = 0; }
    return n;
}

static bool launch(void* const* d_in, void* d_out) {
    static EncodeFn enc = nullptr;
    static Scratch* gs = nullptr;
    if (!enc) {
        void* fn = nullptr;
        cudaDriverEntryPointQueryResult qr;
        cudaGetDriverEntryPoint("cuTensorMapEncodeTiled", &fn, cudaEnableDefault, &qr);
        enc = (EncodeFn)fn;
        cudaFuncSetAttribute(fused_kernel, cudaFuncAttributeMaxDynamicSharedMemorySize, SM_TOTAL);
        cudaGetSymbolAddress((void**)&gs, g_s);
    }
    Hot p;
    Maps m;
    auto in = [&](int i) { return (const __nv_bfloat16*)d_in[i]; };
    bool ok = true;
    auto off = [&](const void* q) {
        const long long d = (const char*)q - (const char*)d_in[0];
        ok = ok && d / 256 * 256 == d && (int)(d / 256) == d / 256;
        return (int)(d / 256);
    };
    p.u = in(0); p.are = off(in(1)); p.aim = off(in(2)); p.bre = off(in(3)); p.bim = off(in(4)); p.cre = off(in(5)); p.cim = off(in(6));
    p.logdt = off(in(7)); p.dskip = off(in(8)); p.wr = off(in(10)); p.ep = off(gs->ep);
    if (!ok) return false;
    p.out = (__nv_bfloat16*)d_out;
    p.wg = in(11);
    p.tn = g_tune;
    p.s = gs;
    make2d(enc, &m.w[0], in(12), F_, D_);
    make2d(enc, &m.w[1], in(11), F_, D_);
    make2d(enc, &m.w[2], in(13), D_, F_, 40);
    make5d(enc, &m.u, in(0), 40, CU_TENSOR_MAP_SWIZZLE_NONE);
    fused_kernel<<<NCTA, NTHREADS, SM_TOTAL>>>(p, m);
    return true;
}

}

namespace v2 {

constexpr int L_ = 2048, D_ = 576, F_ = 4608;
constexpr int NDOWN = 72, NMAIN = 128, NCTA = 132, NTHREADS = 512;
constexpr int SPIN_LIMIT = 1 << 16;
constexpr uint32_t SLOT_FREE = 0x7FFFABCDu;

constexpr int SM_PART = 544;
constexpr int SM_RED = SM_PART;
constexpr int SM_STA = 2080;
constexpr int SM_ONES = 2176;
constexpr int SM_KINF = 2192;
constexpr int SM_RP = 2272;
constexpr int SM_XS = 2704;
constexpr int KR_STRIDE = 1296;
constexpr int SM_X0 = 12080, X0_STRIDE = 4512, X0_ODD = 2240;
constexpr int SM_KT = 30128, KT_STRIDE = 3584, KT_P4 = 2144, KT_P8 = 2896;
constexpr int SM_FAR = 44544, FAR_STRIDE = 11328;
constexpr int FB5 = 0, FB3 = 3328, FB9E = 6656, FB9O = 7824, FB7E = 8992, FB7O = 10160;
constexpr int SM_ROWS = SM_FAR, ROW_STRIDE = 1168;
constexpr int SM_STG = SM_FAR + 19968;
constexpr int KG_SCR = 3072;
constexpr int SM_EX = 89856;
constexpr int EX_KT = SM_EX + X0_STRIDE, EX_FAR = EX_KT + KT_STRIDE, EX_HAND = 109312;
constexpr int SM_W_DOWN = 90112, SM_W_BIG = 121856, STAGE = 6144;
constexpr int SM_W_LAST = 12288;
constexpr int SM_TOTAL = 232448;
constexpr int SM_EPOCH = 2528, SM_SKIP = 2536;
static_assert(SM_STG + 8 * KG_SCR <= SM_EX && SM_STG % 128 == 0 && EX_HAND % 128 == 0 && EX_FAR + FAR_STRIDE <= EX_HAND && EX_HAND + 12288 <= SM_W_BIG, "scratch");

enum { B_ROWS = 0, B_KG, B_X0, B_X1, B_BOX  , B_TAB, B_EM = 6, B_SP = 10, B_OUT = 14, B_H = 15, B_RED = 16, B_TAB1 = 17, B_XS = 18, B_GX = 19, B_YIN = 22, B_P1 = 26, B_FD, B_GU = 28, B_W = 34, B_COUNT = 58 };

struct Tune { short f_start, f_t3, w2, w2b, w3, t_xs, t_svc, t_marg, f_t2, w1, zero, pad; };

struct Scratch {
    uint32_t x[144 * 4096];
    uint32_t y[128 * 4608];
    uint32_t h[2][F_ * 4];
    uint32_t key[L_];
    uint32_t stat[L_];
    uint32_t sel[4][32];
    uint32_t cnt[17 * 32];
};
__device__ __align__(1024) Scratch g_s;

struct Hot {
    const __nv_bfloat16* u;
    Scratch* s;
    const __nv_bfloat16 *wr, *are, *aim, *bre, *bim, *cre, *cim, *logdt;
    Tune tn;
    const __nv_bfloat16 *dskip, *pwg, *pwu, *pwd;
    __nv_bfloat16* out;
};
struct Maps { CUtensorMap wg, wu, wd; };

__device__ __forceinline__ uint32_t smem_u32(const void* p) { return (uint32_t)__cvta_generic_to_shared(p); }
__device__ __forceinline__ void mbar_init(uint32_t b, int c) { asm volatile("mbarrier.init.shared::cta.b64 [%0], %1;" ::"r"(b), "r"(c) : "memory"); }
__device__ __forceinline__ void mbar_expect(uint32_t b, int bytes) { asm volatile("mbarrier.arrive.expect_tx.shared::cta.b64 _, [%0], %1;" ::"r"(b), "r"(bytes) : "memory"); }
__device__ __forceinline__ void mbar_arrive(uint32_t b) { asm volatile("mbarrier.arrive.shared::cta.b64 _, [%0];" ::"r"(b) : "memory"); }
__device__ __forceinline__ bool elect() { uint32_t d; asm volatile("{.reg .pred p; elect.sync _|p, 0xffffffff; selp.u32 %0,1,0,p;}" : "=r"(d)); return d; }
__device__ __forceinline__ bool mbar_test(uint32_t b, int par) {
    uint32_t d;
    asm volatile("{.reg .pred p; mbarrier.test_wait.parity.shared::cta.b64 p, [%1], %2; selp.u32 %0,1,0,p;}" : "=r"(d) : "r"(b), "r"(par) : "memory");
    return d;
}
#define WAIT_LOOP(ins) "{\n.reg .pred p;\n.reg .u32 n;\nmov.u32 n, 0;\nLW:\n" ins " p, [%0], %1;\n@p bra LD;\nadd.u32 n, n, 1;\nsetp.lt.u32 p, n, 16384;\n@p bra LW;\nLD:\n}"
__device__ __forceinline__ void mbar_wait(uint32_t b, int par) { asm volatile(WAIT_LOOP("mbarrier.try_wait.parity.shared::cta.b64")::"r"(b), "r"(par) : "memory"); }
__device__ __forceinline__ uint32_t mapa(uint32_t a, uint32_t rank) { uint32_t d; asm("mapa.shared::cluster.u32 %0, %1, %2;" : "=r"(d) : "r"(a), "r"(rank)); return d; }
__device__ __forceinline__ void bulk_g2s(uint32_t dst, const void* src, int bytes, uint32_t bar) {
    asm volatile("cp.async.bulk.shared::cluster.global.mbarrier::complete_tx::bytes [%0], [%1], %2, [%3];" ::"r"(dst), "l"(src), "r"(bytes), "r"(bar) : "memory");
}
__device__ __forceinline__ void tma2d(uint32_t dst, const CUtensorMap* m, int c0, int c1, uint32_t bar) {
    asm volatile("cp.async.bulk.tensor.2d.shared::cluster.global.mbarrier::complete_tx::bytes [%0], [%1, {%3, %4}], [%2];" ::"r"(dst), "l"(m), "r"(bar), "r"(c0), "r"(c1) : "memory");
}
__device__ __forceinline__ void pf_tmap(const CUtensorMap* m) { asm volatile("prefetch.tensormap [%0];" ::"l"(m) : "memory"); }
__device__ __forceinline__ void bar_sync(int id, int n) { asm volatile("bar.sync %0, %1;" ::"r"(id), "r"(n) : "memory"); }
__device__ __forceinline__ uint4 ld_rlx4(const void* p) { uint4 v; asm volatile("ld.relaxed.gpu.global.v4.u32 {%0,%1,%2,%3}, [%4];" : "=r"(v.x), "=r"(v.y), "=r"(v.z), "=r"(v.w) : "l"(p) : "memory"); return v; }
__device__ __forceinline__ uint32_t ld_rlx(const void* p) { uint32_t v; asm volatile("ld.relaxed.gpu.global.u32 %0, [%1];" : "=r"(v) : "l"(p) : "memory"); return v; }
__device__ __forceinline__ void st_rlx(void* p, uint32_t v) { asm volatile("st.relaxed.gpu.global.u32 [%0], %1;" ::"l"(p), "r"(v) : "memory"); }
__device__ __forceinline__ uint32_t lds32(uint32_t a) { uint32_t v; asm volatile("ld.shared.u32 %0, [%1];" : "=r"(v) : "r"(a) : "memory"); return v; }
__device__ __forceinline__ uint32_t lds32v(uint32_t a) { uint32_t v; asm volatile("ld.volatile.shared.u32 %0, [%1];" : "=r"(v) : "r"(a) : "memory"); return v; }
__device__ __forceinline__ uint4 lds128v(uint32_t a) { uint4 v; asm volatile("ld.volatile.shared.v4.u32 {%0,%1,%2,%3}, [%4];" : "=r"(v.x), "=r"(v.y), "=r"(v.z), "=r"(v.w) : "r"(a) : "memory"); return v; }
__device__ __forceinline__ uint32_t lds16(uint32_t a) { uint16_t v; asm volatile("ld.shared.u16 %0, [%1];" : "=h"(v) : "r"(a) : "memory"); return v; }
__device__ __forceinline__ uint2 lds64(uint32_t a) { uint2 v; asm volatile("ld.shared.v2.u32 {%0,%1}, [%2];" : "=r"(v.x), "=r"(v.y) : "r"(a) : "memory"); return v; }
__device__ __forceinline__ uint4 lds128(uint32_t a) { uint4 v; asm volatile("ld.shared.v4.u32 {%0,%1,%2,%3}, [%4];" : "=r"(v.x), "=r"(v.y), "=r"(v.z), "=r"(v.w) : "r"(a) : "memory"); return v; }
__device__ __forceinline__ void sts16(uint32_t a, uint32_t v) { asm volatile("st.shared.u16 [%0], %1;" ::"r"(a), "h"((uint16_t)v) : "memory"); }
__device__ __forceinline__ void sts32(uint32_t a, uint32_t v) { asm volatile("st.shared.u32 [%0], %1;" ::"r"(a), "r"(v) : "memory"); }
__device__ __forceinline__ void sts64(uint32_t a, uint32_t x, uint32_t y) { asm volatile("st.shared.v2.u32 [%0], {%1,%2};" ::"r"(a), "r"(x), "r"(y) : "memory"); }
__device__ __forceinline__ void sts128(uint32_t a, uint32_t x, uint32_t y, uint32_t z, uint32_t w) { asm volatile("st.shared.v4.u32 [%0], {%1,%2,%3,%4};" ::"r"(a), "r"(x), "r"(y), "r"(z), "r"(w) : "memory"); }
__device__ __forceinline__ void st_async32(uint32_t a, uint32_t v, uint32_t bar) {
    asm volatile("st.async.shared::cluster.mbarrier::complete_tx::bytes.b32 [%0], %1, [%2];" ::"r"(a), "r"(v), "r"(bar) : "memory");
}
__device__ __forceinline__ void ldm4(uint32_t a, uint32_t& r0, uint32_t& r1, uint32_t& r2, uint32_t& r3) {
    asm volatile("ldmatrix.sync.aligned.m8n8.x4.shared.b16 {%0,%1,%2,%3}, [%4];" : "=r"(r0), "=r"(r1), "=r"(r2), "=r"(r3) : "r"(a) : "memory");
}
__device__ __forceinline__ void ldm4t(uint32_t a, uint32_t& r0, uint32_t& r1, uint32_t& r2, uint32_t& r3) {
    asm volatile("ldmatrix.sync.aligned.m8n8.x4.trans.shared.b16 {%0,%1,%2,%3}, [%4];" : "=r"(r0), "=r"(r1), "=r"(r2), "=r"(r3) : "r"(a) : "memory");
}
__device__ __forceinline__ void ldm2(uint32_t a, uint32_t& r0, uint32_t& r1) {
    asm volatile("ldmatrix.sync.aligned.m8n8.x2.shared.b16 {%0,%1}, [%2];" : "=r"(r0), "=r"(r1) : "r"(a) : "memory");
}
__device__ __forceinline__ void stm4(uint32_t a, uint32_t r0, uint32_t r1, uint32_t r2, uint32_t r3) {
    asm volatile("stmatrix.sync.aligned.m8n8.x4.shared.b16 [%0], {%1,%2,%3,%4};" ::"r"(a), "r"(r0), "r"(r1), "r"(r2), "r"(r3) : "memory");
}
__device__ __forceinline__ void mma_bf(float& c0, float& c1, float& c2, float& c3, uint32_t a0, uint32_t a1, uint32_t a2, uint32_t a3, uint32_t b0, uint32_t b1) {
    asm volatile("mma.sync.aligned.m16n8k16.row.col.f32.bf16.bf16.f32 {%0,%1,%2,%3},{%4,%5,%6,%7},{%8,%9},{%0,%1,%2,%3};"
                 : "+f"(c0), "+f"(c1), "+f"(c2), "+f"(c3) : "r"(a0), "r"(a1), "r"(a2), "r"(a3), "r"(b0), "r"(b1));
}
__device__ __forceinline__ void mma_bf(float (&c)[4], uint32_t a0, uint32_t a1, uint32_t a2, uint32_t a3, uint32_t b0, uint32_t b1) { mma_bf(c[0], c[1], c[2], c[3], a0, a1, a2, a3, b0, b1); }
__device__ __forceinline__ void mma_h(float (&c)[4], uint32_t a0, uint32_t a1, uint32_t a2, uint32_t a3, uint32_t b0, uint32_t b1) {
    asm volatile("mma.sync.aligned.m16n8k16.row.col.f32.f16.f16.f32 {%0,%1,%2,%3},{%4,%5,%6,%7},{%8,%9},{%0,%1,%2,%3};"
                 : "+f"(c[0]), "+f"(c[1]), "+f"(c[2]), "+f"(c[3]) : "r"(a0), "r"(a1), "r"(a2), "r"(a3), "r"(b0), "r"(b1));
}
__device__ __forceinline__ void mma_bf8(float (&c)[4], uint32_t a0, uint32_t a1, uint32_t b0) {
    asm volatile("mma.sync.aligned.m16n8k8.row.col.f32.bf16.bf16.f32 {%0,%1,%2,%3},{%4,%5},{%6},{%0,%1,%2,%3};"
                 : "+f"(c[0]), "+f"(c[1]), "+f"(c[2]), "+f"(c[3]) : "r"(a0), "r"(a1), "r"(b0));
}
__device__ __forceinline__ uint32_t pack_bf(float lo, float hi) { uint32_t r; asm("cvt.rn.bf16x2.f32 %0, %1, %2;" : "=r"(r) : "f"(hi), "f"(lo)); return r; }
__device__ __forceinline__ uint32_t pack_h(float lo, float hi) { uint32_t r; asm("cvt.rn.f16x2.f32 %0, %1, %2;" : "=r"(r) : "f"(hi), "f"(lo)); return r; }
__device__ __forceinline__ float bf_lo(uint32_t w) { return __uint_as_float(w << 16); }
__device__ __forceinline__ float bf_hi(uint32_t w) { return __uint_as_float(w & 0xFFFF0000u); }
__device__ __forceinline__ float bf_round(float x) { return bf_lo(pack_bf(x, 0.f)); }
__device__ __forceinline__ uint32_t badd(uint32_t a, uint32_t b) { uint32_t r; asm("add.rn.bf16x2 %0, %1, %2;" : "=r"(r) : "r"(a), "r"(b)); return r; }
__device__ __forceinline__ uint32_t bsub(uint32_t a, uint32_t b) { uint32_t r; asm("sub.rn.bf16x2 %0, %1, %2;" : "=r"(r) : "r"(a), "r"(b)); return r; }
__device__ __forceinline__ uint32_t bmul(uint32_t a, uint32_t b) { uint32_t r; asm("mul.rn.bf16x2 %0, %1, %2;" : "=r"(r) : "r"(a), "r"(b)); return r; }
__device__ __forceinline__ uint32_t bfma(uint32_t a, uint32_t b, uint32_t c) { uint32_t r; asm("fma.rn.bf16x2 %0, %1, %2, %3;" : "=r"(r) : "r"(a), "r"(b), "r"(c)); return r; }
__device__ __forceinline__ uint32_t prmt(uint32_t a, uint32_t b, uint32_t s) { uint32_t r; asm("prmt.b32 %0, %1, %2, %3;" : "=r"(r) : "r"(a), "r"(b), "r"(s)); return r; }
__device__ __forceinline__ float ex2f(float x) { float r; asm("ex2.approx.ftz.f32 %0, %1;" : "=f"(r) : "f"(x)); return r; }
__device__ __forceinline__ float rcpf(float x) { float r; asm("rcp.approx.ftz.f32 %0, %1;" : "=f"(r) : "f"(x)); return r; }
__device__ __forceinline__ float silu_f(float x) { return x * rcpf(1.f + ex2f(-1.4426950408889634f * x)); }
__device__ __forceinline__ uint32_t norm2(uint32_t x, uint32_t m, uint32_t hi, uint32_t lo) { uint32_t d = bsub(x, m); return bfma(d, hi, bmul(d, lo)); }
__device__ __forceinline__ uint32_t clk32() { uint32_t c; asm volatile("mov.u32 %0, %%clock;" : "=r"(c)); return c; }
__device__ __forceinline__ void spin_until(uint32_t t0, int dt) {
#pragma unroll 1
    while ((int)(clk32() - t0) < dt) __nanosleep(32);
}
__device__ __forceinline__ float sqrt_ap(float x) { float r; asm("sqrt.approx.ftz.f32 %0, %1;" : "=f"(r) : "f"(x)); return r; }

__device__ __forceinline__ void cp16(uint32_t dst, const void* src) { asm volatile("cp.async.cg.shared.global [%0], [%1], 16;" ::"r"(dst), "l"(src) : "memory"); }
__device__ __forceinline__ void pf_l2(const void* p) { asm volatile("cp.async.bulk.prefetch.L2.global [%0], 16;" ::"l"(p) : "memory"); }
__device__ __forceinline__ void bulk_s2g(void* dst, uint32_t src, int bytes) {
    asm volatile("cp.async.bulk.global.shared::cta.bulk_group [%0], [%1], %2;" ::"l"(dst), "r"(src), "r"(bytes) : "memory");
}
__device__ __forceinline__ uint32_t ld_acq(const void* p) { uint32_t v; asm volatile("ld.acquire.gpu.global.u32 %0, [%1];" : "=r"(v) : "l"(p) : "memory"); return v; }
__device__ __forceinline__ void red_add(void* p) { asm volatile("red.relaxed.gpu.global.add.u32 [%0], 1;" ::"l"(p) : "memory"); }
__device__ __forceinline__ void fence_async() { asm volatile("fence.proxy.async.shared::cta;" ::: "memory"); }
__device__ __forceinline__ void fence_async_g() { asm volatile("fence.proxy.async.global;" ::: "memory"); }
__device__ __forceinline__ void red_rel(void* p) { asm volatile("red.release.gpu.global.add.u32 [%0], 1;" ::"l"(p) : "memory"); }
__device__ __forceinline__ void wait_count(const uint32_t* p, uint32_t want) {
#pragma unroll 1
    for (int it = 0; it < SPIN_LIMIT && ld_rlx(p) != want; it++) __nanosleep(20);
}
__device__ __forceinline__ uint32_t ld_stat(const uint32_t* p, uint32_t tag) {
    uint32_t v = 0;
#pragma unroll 1
    for (int it = 0; it < SPIN_LIMIT; it++) {
        v = ld_rlx(p);
        if ((v >> 31) == tag) break;
    }
    return v & 0x7FFFFFFFu;
}
__device__ __forceinline__ uint32_t hadd(uint32_t a, uint32_t b) { uint32_t r; asm("add.rn.f16x2 %0, %1, %2;" : "=r"(r) : "r"(a), "r"(b)); return r; }
__device__ __forceinline__ float h_lo(uint32_t w) { return __half2float(__ushort_as_half((unsigned short)w)); }
__device__ __forceinline__ float h_hi(uint32_t w) { return __half2float(__ushort_as_half((unsigned short)(w >> 16))); }
__device__ __forceinline__ uint32_t x0_chunk(uint32_t xb, int c) { return xb + ((c & 1) ? X0_ODD + 120 : 128) + 8 * c; }

struct cf { float x, y; };
__device__ __forceinline__ cf cmul(cf a, cf b) { return {a.x * b.x - a.y * b.y, a.x * b.y + a.y * b.x}; }
__device__ __forceinline__ cf csq(cf a) { return {a.x * a.x - a.y * a.y, (a.x + a.x) * a.y}; }
__device__ __forceinline__ cf cpow_direct(float zr2, float zi, float l) {
    const float mag = ex2f(zr2 * l), th = zi * l;
    return {mag * __cosf(th), mag * __sinf(th)};
}
__device__ __forceinline__ __half2 as_h2(uint32_t v) { return *reinterpret_cast<__half2*>(&v); }
__device__ __forceinline__ uint32_t as_u32(__half2 v) { return *reinterpret_cast<uint32_t*>(&v); }
struct hm { uint32_t v, s; };
__device__ __forceinline__ hm mk_hm(cf a) {
    const uint32_t v = pack_h(a.x, a.y);
    return {v, prmt(v, v, 0x1032) ^ 0x8000u};
}
__device__ __forceinline__ uint32_t hcmul(uint32_t x, hm y) {
    const __half2 xx = as_h2(x);
    return as_u32(__hfma2(__high2half2(xx), as_h2(y.s), __hmul2(__low2half2(xx), as_h2(y.v))));
}

struct KParams { uint32_t are, aim, bre, bim, cre, cim, ldt; };
__device__ __forceinline__ KParams kgen_load(const Hot& p, int ch, int half, int lane) {
    const uint32_t po = ch * 64 + half * 32 + lane;
    KParams k;
    k.are = __ldg((const uint32_t*)p.are + po); k.aim = __ldg((const uint32_t*)p.aim + po);
    k.bre = __ldg((const uint32_t*)p.bre + po); k.bim = __ldg((const uint32_t*)p.bim + po);
    k.cre = __ldg((const uint32_t*)p.cre + po); k.cim = __ldg((const uint32_t*)p.cim + po);
    k.ldt = __ldg((const uint16_t*)p.logdt + ch + (lane & p.tn.zero));
    return k;
}

__device__ __forceinline__ void kgen(KParams kp, uint32_t scr, uint32_t os, int c0, int c1, uint32_t pause) {
    const int lane = threadIdx.x & 31;
    const float dt = bf_round(ex2f(bf_lo(kp.ldt) * 1.4426950408889634f));
    const cf w0 = cmul({bf_lo(kp.cre), bf_lo(kp.cim)}, {dt * bf_lo(kp.bre), dt * bf_lo(kp.bim)});
    const cf w1 = cmul({bf_hi(kp.cre), bf_hi(kp.cim)}, {dt * bf_hi(kp.bre), dt * bf_hi(kp.bim)});
    uint32_t eb = __reduce_max_sync(~0u, __float_as_uint(fmaxf(fmaxf(fabsf(w0.x), fabsf(w0.y)), fmaxf(fabsf(w1.x), fabsf(w1.y))))) & 0x7F800000u;
    eb = min(max(eb, 0x00800000u), 0x7E800000u);
    const float sc = __uint_as_float(0x7F000000u - eb);
    float k0 = c0 ? 0.f : w0.x + w1.x;
#pragma unroll
    for (int o = 16; o > 0; o >>= 1) k0 += __shfl_xor_sync(~0u, k0, o);
    float d[5][4];
#pragma unroll
    for (int i = 0; i < 5; i++) d[i][0] = d[i][1] = d[i][2] = d[i][3] = 0.f;
    const int mi = lane >> 3, j = lane & 7;
    const uint32_t st0 = scr + mi * 128 + ((j ^ mi) << 4), st1 = st0 ^ 64;
    const uint32_t la = scr + (lane & 15) * 128 + (((lane >> 4) ^ j) << 4), lb = scr + j * 128 + ((mi ^ j) << 4);
    auto st = [&](int row, uint32_t a, uint32_t b, uint32_t c, uint32_t e) { stm4(((row & 4) ? st1 : st0) + row * 128, a, b, c, e); };
#pragma unroll 1
    for (int c = c0; c < c1; c++) {
        if (c > c0 && pause) mbar_wait(pause, 0);
        const float zr2 = dt * (c ? bf_hi(kp.are) : bf_lo(kp.are)) * 1.4426950408889634f;
        const float zi = dt * (c ? bf_hi(kp.aim) : bf_lo(kp.aim));
        const cf w = {(c ? w1.x : w0.x) * sc, (c ? w1.y : w0.y) * sc};
        const cf a1 = cpow_direct(zr2, zi, 1.f), a256 = cpow_direct(zr2, zi, 256.f);
        uint32_t a[4][4];
        {
            const cf a16 = cpow_direct(-zr2, zi, -16.f);
            const cf a32 = csq(a16), a48 = cmul(a32, a16), a64 = csq(a32), a128 = csq(a64), a192 = cmul(a128, a64);
            const uint32_t p1 = pack_h(a16.x, a16.y), p2 = pack_h(a32.x, a32.y), p3 = pack_h(a48.x, a48.y);
            const hm q1 = mk_hm(a64), q2 = mk_hm(a128), q3 = mk_hm(a192);
            __syncwarp();
            st(0, 0x00003C00u, p1, p2, p3);
            st(4, q1.v, hcmul(p1, q1), hcmul(p2, q1), hcmul(p3, q1));
            st(8, q2.v, hcmul(p1, q2), hcmul(p2, q2), hcmul(p3, q2));
            st(12, q3.v, hcmul(p1, q3), hcmul(p2, q3), hcmul(p3, q3));
            __syncwarp();
#pragma unroll
            for (int k = 0; k < 4; k++) ldm4(la ^ (k * 32), a[k][0], a[k][1], a[k][2], a[k][3]);
        }
        auto tile = [&](int T, int row) {
#pragma unroll
            for (int kp2 = 0; kp2 < 2; kp2++) {
                uint32_t b0, b1, b2, b3;
                ldm4((lb ^ (kp2 * 64)) + row * 128, b0, b1, b2, b3);
                mma_h(d[T], a[2 * kp2][0], a[2 * kp2][1], a[2 * kp2][2], a[2 * kp2][3], b0, b1);
                mma_h(d[T], a[2 * kp2 + 1][0], a[2 * kp2 + 1][1], a[2 * kp2 + 1][2], a[2 * kp2 + 1][3], b2, b3);
            }
        };
        const cf a2 = csq(a1), a4 = csq(a2), a8 = csq(a4), a12 = cmul(a8, a4);
        const cf u1 = cmul(w, a1), u2 = cmul(w, a2), u3 = cmul(u2, a1), u4 = cmul(w, a4);
        uint32_t v[16];
        v[0] = pack_h(u1.x, u1.y); v[1] = pack_h(u2.x, u2.y); v[2] = pack_h(u3.x, u3.y); v[3] = pack_h(u4.x, u4.y);
        const hm m4 = mk_hm(a4), m8 = mk_hm(a8), m12 = mk_hm(a12);
#pragma unroll
        for (int i = 0; i < 4; i++) { v[4 + i] = hcmul(v[i], m4); v[8 + i] = hcmul(v[i], m8); v[12 + i] = hcmul(v[i], m12); }
        const hm m256 = mk_hm(a256);
        __syncwarp();
#pragma unroll
        for (int i = 0; i < 4; i++) st(4 * i, v[4 * i], v[4 * i + 1], v[4 * i + 2], v[4 * i + 3]);
        st(16, hcmul(v[1], m256), hcmul(v[3], m256), hcmul(v[5], m256), hcmul(v[7], m256));
        st(20, hcmul(v[9], m256), hcmul(v[11], m256), hcmul(v[13], m256), hcmul(v[15], m256));
        __syncwarp();
        tile(0, 0); tile(1, 8); tile(2, 16);
        const cf a512 = csq(a256), a768 = cmul(a512, a256), a1024 = csq(a512);
        const cf a1280 = cmul(a1024, a256), a1536 = csq(a768), a1792 = cmul(a1024, a768);
        const hm m512 = mk_hm(a512), m768 = mk_hm(a768);
        const hm n0 = mk_hm(a1024), n1 = mk_hm(a1280), n2 = mk_hm(a1536), n3 = mk_hm(a1792);
        __syncwarp();
        st(0, hcmul(v[3], m512), hcmul(v[7], m512), hcmul(v[11], m512), hcmul(v[15], m512));
        st(4, hcmul(v[3], m768), hcmul(v[7], m768), hcmul(v[11], m768), hcmul(v[15], m768));
        st(8, hcmul(v[7], n0), hcmul(v[15], n0), hcmul(v[7], n1), hcmul(v[15], n1));
        st(12, hcmul(v[7], n2), hcmul(v[15], n2), hcmul(v[7], n3), hcmul(v[15], n3));
        __syncwarp();
        tile(3, 0); tile(4, 8);
    }
    __syncwarp();
#pragma unroll
    for (int i = 0; i < 5; i++) sts128(os + i * 512 + lane * 16, __float_as_uint(d[i][0]), __float_as_uint(d[i][1]), __float_as_uint(d[i][2]), __float_as_uint(d[i][3]));
    sts64(os + 2560, eb, __float_as_uint(k0));
}

__device__ __forceinline__ void ktables(uint32_t os, int ostep, int np, uint32_t kr, uint32_t kt, uint32_t kinf, int part) {
    const int lane = threadIdx.x & 31, g = lane >> 2, t = lane & 3;
    uint32_t eb = 0;
    float k0 = 0.f, f[4];
#pragma unroll
    for (int q = 0; q < 4; q++) {
        uint2 v = make_uint2(0u, 0u);
        if (q < np) v = lds64(os + q * ostep + 2560);
        eb = max(eb, v.x);
        k0 += __uint_as_float(v.y);
        f[q] = __uint_as_float(v.x);
    }
    const float rs = __uint_as_float(0x7F000000u - eb);
#pragma unroll
    for (int q = 0; q < 4; q++) f[q] *= rs;
#pragma unroll 1
    for (int i = (part & 1) ? 0 : 2; i < ((part & 2) ? 5 : 3); i++) {
        float a0 = 0.f, a1 = 0.f, a2 = 0.f, a3 = 0.f;
        uint4 v[4];
#pragma unroll
        for (int q = 0; q < 4; q++) {
            v[q] = make_uint4(0u, 0u, 0u, 0u);
            if (q < np) v[q] = lds128(os + q * ostep + i * 512 + lane * 16);
        }
#pragma unroll
        for (int q = 0; q < 4; q++) { a0 += __uint_as_float(v[q].x) * f[q]; a1 += __uint_as_float(v[q].y) * f[q]; a2 += __uint_as_float(v[q].z) * f[q]; a3 += __uint_as_float(v[q].w) * f[q]; }
        const int sg = 32 >> max(i - 1, 0);
        const uint32_t o = kr + 4 + (i < 2 ? 16 * i : 256 * i) + sg * g + (i < 3 ? 8 : 128) * (t >> 1) + (i < 4 ? 4 : 64) * (t & 1);
        sts32(o, pack_h(a0, a1));
        sts32(o + 8 * sg, pack_h(a2, a3));
    }
    sts32(kr, pack_h(0.f, k0 * rs));
    __syncwarp();
    if (part & 1) {
        uint32_t w0[4], w1[4], a[2], b[2];
#pragma unroll
        for (int r = 0; r < 4; r++) { w0[r] = lds32(kr + 4 * lane + 128 * r); w1[r] = lds32(kr + 4 * lane + 128 * r + 4); }
#pragma unroll
        for (int r = 0; r < 2; r++) { a[r] = lds32(kr + 512 + 4 * lane + 128 * r); b[r] = lds32(kr + 516 + 4 * lane + 128 * r); }
#pragma unroll
        for (int r = 0; r < 4; r++) sts64(kt + 8 * lane + 256 * r + 32, prmt(w0[r], w0[r], 0x1032), prmt(w0[r], w1[r], 0x3254));
        if (lane == 31) b[1] = pack_h(h_lo(b[1]) - h_hi(b[1]), 0.f);
#pragma unroll
        for (int r = 0; r < 2; r++)
            sts128(kt + 4 * 264 + 16 * lane + 512 * r, prmt(a[r], a[r], (r == 0 && lane == 0) ? 0x1032 : 0x3232), prmt(a[r], a[r], 0x3232), prmt(a[r], b[r], 0x3254), prmt(b[r], b[r], 0x1032));
        if (lane < 24) sts32(kt + 4 * (lane < 8 ? lane : 512 + lane), 0u);
    }
    if (part & 2) {
        const uint32_t k512 = lds16(kr + 2 * 385), k1024 = lds16(kr + 2 * 513);
        if (lane == 0) {
            sts128(kinf, eb, __float_as_uint(h_lo(k512)), k1024, 0u);
            sts16(kr + 2 * 512, pack_h(h_lo(lds16(kr + 2 * 512)) - h_lo(k1024), 0.f));
        }
#pragma unroll
        for (int r = 0; r < 3; r++)
            if (r < 2 || lane < 26) sts128(kt + KT_P4 + 16 * lane + 512 * r, 0u, 0u, 0u, 0u);
        __syncwarp();
        uint32_t x0[5], x1[5], y0[5], y1[5];
#pragma unroll
        for (int r = 0; r < 5; r++) {
            const int m = min(126 + lane + 32 * r, 256);
            x0[r] = lds16(kr + 2 * (257 + m)); x1[r] = lds16(kr + 2 * (259 + m)); y0[r] = lds16(kr + 2 * (385 + m)); y1[r] = lds16(kr + 2 * (387 + m));
        }
#pragma unroll
        for (int r = 0; r < 5; r++) {
            const int m = 126 + lane + 32 * r;
            if (m < 128) x0[r] = y0[r] = 0;
            if (m > 253) x1[r] = 0;
            if (m > 254) y1[r] = 0;
            if (m < 256) sts32(kt + KT_P4 + 4 * (((m - 96) & ~3) | ((m & 1) << 1) | ((m >> 1) & 1)), x0[r] | (x1[r] << 16));
            if (m < 257) sts32(kt + KT_P8 + 4 * (m - 96), y0[r] | (y1[r] << 16));
        }
    }
    __syncwarp();
}

__device__ __forceinline__ void mma_hc(float (&d)[4], const float (&c)[4], uint32_t a0, uint32_t a1, uint32_t a2, uint32_t a3, uint32_t b0, uint32_t b1) {
    asm volatile("mma.sync.aligned.m16n8k16.row.col.f32.f16.f16.f32 {%0,%1,%2,%3},{%4,%5,%6,%7},{%8,%9},{%10,%11,%12,%13};"
                 : "=f"(d[0]), "=f"(d[1]), "=f"(d[2]), "=f"(d[3]) : "r"(a0), "r"(a1), "r"(a2), "r"(a3), "r"(b0), "r"(b1), "f"(c[0]), "f"(c[1]), "f"(c[2]), "f"(c[3]));
}
template <int Q0, int Q1>
__device__ __forceinline__ void sweep_steps(float (&w)[5][4], const uint32_t (&R)[66], uint32_t xa, uint32_t (&x)[5], uint32_t z) {
#pragma unroll
    for (int q = Q0; q <= Q1; q++) {
        uint32_t n0, n1;
        ldm2(xa + 16 * (q + 1), n0, n1);
        const uint32_t a2 = x[0] | z, a3 = x[1] | z;
#pragma unroll
        for (int j = 0; j < 4; j++) {
            const int s = 8 * j + 8 - q;
            if (q == 1) mma_hc(w[j], w[j + 1], x[1], x[2], a2, a3, R[2 * s], R[2 * s + 1]);
            else mma_h(w[j], x[1], x[2], a2, a3, R[2 * s], R[2 * s + 1]);
        }
        if (q == 8) {
            const float zero[4] = {0.f, 0.f, 0.f, 0.f};
            mma_hc(w[4], zero, x[1], x[2], a2, a3, R[64], R[65]);
        }
        x[0] = x[2]; x[1] = x[3]; x[2] = x[4]; x[3] = n0; x[4] = n1;
    }
}

__device__ __forceinline__ void box_round(uint32_t xb, uint32_t fa, int rho, int lane) {
    if (rho == 6) {
        const int a = lane >> 3, j = lane & 7;
        sts128(fa + 3328 * (lane >> 4) + 16 * ((lane & 15) < 15 ? (lane & 15) : 207), 0u, 0u, 0u, 0u);
        sts128(fa + FB9E + 1168 * a + 16 * (j < 7 ? j : 71 + (a & 1)), 0u, 0u, 0u, 0u);
        __syncwarp();
    }
    const int c = rho < 6 ? 32 * rho + lane : -1;
    const uint4 pv = lds128(x0_chunk(xb, c - 1)), ow = lds128(x0_chunk(xb, c));
    const uint2 nx = lds64(x0_chunk(xb, c + 1));
    const uint32_t P[9] = {pv.y, pv.z, pv.w, ow.x, ow.y, ow.z, ow.w, nx.x, nx.y};
    uint32_t Q[8], b3[6], b5[4];
#pragma unroll
    for (int k = 0; k < 8; k++) Q[k] = prmt(P[k], P[k + 1], 0x5432);
#pragma unroll
    for (int k = 0; k < 6; k++) b3[k] = hadd(hadd(Q[k], Q[k + 1]), P[k + 1]);
#pragma unroll
    for (int k = 0; k < 4; k++) b5[k] = hadd(b3[k + 2], hadd(P[k + 2], P[k + 4]));
    sts128(fa + FB5 + 240 + 16 * c, b5[0], b5[1], b5[2], b5[3]);
    sts128(fa + FB3 + 240 + 16 * c, b3[0], b3[1], b3[2], b3[3]);
    if (rho < 4 || rho == 6) {
        uint32_t b7[4], b9[4];
#pragma unroll
        for (int k = 0; k < 4; k++) {
            b7[k] = hadd(b5[k], hadd(Q[k + 1], Q[k + 4]));
            b9[k] = hadd(b7[k], hadd(P[k + 1], P[k + 5]));
        }
        const uint32_t ad = fa + ((c & 1) ? FB9O + 120 : FB9E + 112) + 8 * c;
        sts128(ad, b9[0], b9[1], b9[2], b9[3]);
        sts128(ad + (FB7E - FB9E), b7[0], b7[1], b7[2], b7[3]);
    }
}

__global__ void __cluster_dims__(2, 1, 1) __launch_bounds__(NTHREADS, 1) fused_kernel(const Hot p, const __grid_constant__ Maps m) {
    extern __shared__ __align__(1024) char smem[];
    const uint32_t t0 = clk32();
    const int tid = (threadIdx.x + 32 * 0) & (NTHREADS - 1), lane = tid & 31, warp = __shfl_sync(~0u, tid >> 5, 0), bid = blockIdx.x;
    const uint32_t S = smem_u32(smem), z = (uint32_t)p.tn.zero;
    const bool down = bid < NDOWN, rowcta = bid < NMAIN, big = rowcta && !down;
    const int xd = rowcta ? bid : 142 + ((bid - NMAIN) >> 1);
    const int slot = warp < 8 ? (warp & 3) : 4;
    const bool has = warp < 8 ? (rowcta || (slot >> 1) == (bid & 1)) : (big && warp < 12);
    const int ch = slot < 4 ? 4 * xd + slot : 512 + bid - NDOWN;
    KParams kp;
    if (has) kp = kgen_load(p, ch, warp < 8 ? warp >> 2 : (warp >> 1) & 1, lane);
    if (elect()) {
#pragma unroll 1
        for (int i = warp; i < B_COUNT; i += 16) {
            const uint32_t c = i < 16 ? (uint32_t)((big ? 0x1411115555412290ull : 0x1411114444412290ull) >> (4 * i)) & 15 : 1;
            mbar_init(S + i * 8, c ? c : NTHREADS);
        }
        asm volatile("fence.mbarrier_init.release.cluster;" ::: "memory");
    }
    if (rowcta) {
#pragma unroll 1
        for (int i = tid; i < 1224; i += NTHREADS)
            cp16(S + SM_ROWS + 16 * (i + min((i * 911) >> 16, 16)), i < 1152 ? (const uint4*)p.u + bid * 1152 + i : (const uint4*)p.wr + (i - 1152));
    }
    if (tid >= 256 && tid < 336) {
        const int i = tid - 256;
        if (i < 64 || big) sts128(S + (i < 64 ? SM_X0 + (i >> 4) * X0_STRIDE : SM_EX) + ((i & 8) ? X0_ODD : 0) + 16 * (i & 7), 0u, 0u, 0u, 0u);
    }
    if (tid == 447) sts128(S + SM_ONES, 0x3F803F80u, 0x3F803F80u, 0x3F803F80u, 0x3F803F80u);
    __syncthreads();
    if (rowcta) asm volatile("cp.async.mbarrier.arrive.noinc.shared::cta.b64 [%0];" ::"r"(S + B_ROWS * 8) : "memory");
    if (warp == 15 && lane < 4) mbar_expect(S + (lane < 3 ? B_GX + lane : B_RED) * 8, 256);
    asm volatile("barrier.cluster.arrive.relaxed.aligned;" ::: "memory");
    const int g = lane >> 2, t = lane & 3, mi = lane >> 3, j = lane & 7;
    const uint32_t SW = S + (down ? SM_W_DOWN : SM_W_BIG);
    const int pr = bid >> 1, r = bid & 1, nsl = pr >= 54 ? 3 : 2, sl0 = pr < 54 ? 2 * pr : 3 * pr - 54;

    if (warp == 12) {
        if (elect()) {
            const int ng = 6 * nsl, ns = down ? 24 : ng;
            const CUtensorMap* mg = r ? &m.wu : &m.wg;
            pf_tmap(mg);
            if (down) pf_tmap(&m.wd);
            const uint32_t epoch = ld_rlx(&p.s->cnt[16 * 32]) + 1;
            spin_until(t0, p.tn.f_start);
            int done = 0;
#pragma unroll 1
            for (int s = 0; s < ns; s++) {
                if (s == ng) spin_until(t0, p.tn.f_t3);
                #pragma unroll 1
                for (int it = 0; it < SPIN_LIMIT; it++) {
                    const int w = s >= ng ? p.tn.w3 : ((int)(clk32() - t0) < p.tn.f_t2 ? p.tn.w1 : (nsl == 3 ? p.tn.w2b : p.tn.w2));
                    if (s - done < w) break;
                    if (mbar_test(S + (B_W + done) * 8, 0)) done++;
                    else __nanosleep(32);
                }
                const uint32_t bar = S + (B_W + s) * 8;
                uint32_t dst = SW + s * STAGE;
                if (s == 23) { mbar_wait(S + B_EM * 8, 0); fence_async(); dst = S + SM_W_LAST; }
                mbar_expect(bar, STAGE);
                const int u = (s * 43) >> 8;
                if (s < ng) tma2d(dst, mg, 32 * (sl0 + u), 96 * (s - 6 * u), bar);
                else tma2d(dst, &m.wd, 16 * pr, r * 2304 + 192 * (s - 12), bar);
            }
            if (rowcta) {
                mbar_wait(S + B_FD * 8, 0);
                fence_async();
#pragma unroll 1
                for (int q = 0; q < 4; q++) {
                    wait_count(&p.s->cnt[(8 + q) * 32], epoch * (uint32_t)D_);
                    fence_async_g();
                    mbar_expect(S + (B_YIN + q) * 8, 4608);
                    bulk_g2s(S + SM_STG + q * 4608, p.s->y + (32 * q + (bid >> 2)) * 4608 + (bid & 3) * 1152, 4608, S + (B_YIN + q) * 8);
                }
            }
        }
        return;
    }

    uint32_t epoch = 0;
    if (warp >= 8 || !rowcta) epoch = ld_rlx(&p.s->cnt[16 * 32] + (lane & z)) + 1;
    const uint32_t tag = epoch & 1;
    const int hw = warp < 12 ? warp - 8 : warp - 9;

    if (rowcta && warp >= 8 && warp < 15) {
        const uint32_t ad = S + SM_ROWS + (lane & 15) * ROW_STRIDE + 192 * hw + 16 * (lane >> 4);
        uint32_t wd = j ? S + SM_ROWS + 16 * ROW_STRIDE + 192 * hw + 16 * mi : S + SM_ONES;
        const uint32_t wstep = j ? 64 : 0, ones = 0x3F803F80u | z;
        float d1[4] = {0, 0, 0, 0}, d2[4] = {0, 0, 0, 0}, d3[4] = {0, 0, 0, 0}, d4[4] = {0, 0, 0, 0};
        mbar_wait(S + B_ROWS * 8, 0);
#pragma unroll
        for (int kk = 0; kk < 3; kk++) {
            uint32_t w[4];
            ldm4(wd, w[0], w[1], w[2], w[3]);
            wd += wstep;
#pragma unroll
            for (int e = 0; e < 2; e++) {
                uint32_t a0, a1, a2, a3;
                ldm4(ad + 64 * kk + 32 * e, a0, a1, a2, a3);
                mma_bf(d1, a0, a1, a2, a3, w[2 * e], w[2 * e + 1]);
                mma_bf(d2, a0, a1, a2, a3, a0, a2);
                mma_bf(d3, a0, a1, a2, a3, a1, a3);
                mma_bf(d4, ones, ones ^ z, ones + z, ones - z, w[2 * e], w[2 * e + 1]);
            }
        }
        float* part = (float*)(smem + SM_PART + hw * 256) + g * 4;
        if (t == 0) {
            *(float2*)part = make_float2(d1[0], d1[1]);
            *(float2*)(part + 32) = make_float2(d1[2], d1[3]);
            part[3] = d4[1];
            part[35] = d4[1];
        }
        if (t == (g >> 1)) {
            part[2] = (g & 1) ? d2[1] : d2[0];
            part[34] = (g & 1) ? d3[3] : d3[2];
        }
        bar_sync(1, 192);
        if (hw == 0 && lane < 16) {
            float4 s = *(const float4*)(smem + SM_PART + lane * 16);
#pragma unroll
            for (int w = 1; w < 6; w++) {
                const float4 v = *(const float4*)(smem + SM_PART + w * 256 + lane * 16);
                s.x += v.x; s.y += v.y; s.z += v.z; s.w += v.w;
            }
            const float mean = s.x * (1.f / 576.f);
            const float var = fmaxf(s.z * (1.f / 576.f) - mean * mean, 0.f);
            const uint32_t mm = pack_bf(mean, mean);
            const float mu = bf_lo(mm), sd = bf_round(sqrt_ap(bf_round(bf_round(var) + 1e-5f))), ri = rcpf(sd);
            const uint32_t hi = pack_bf(ri, ri);
            const float rl = ri - bf_lo(hi);
            sts16(S + SM_STA + 2 * lane, mm); sts16(S + SM_STA + 32 + 2 * lane, hi); sts16(S + SM_STA + 64 + 2 * lane, pack_bf(rl, rl));
            const uint32_t rb = pack_bf(0.f, (s.y - mu * s.w) * ri);
            const int row = bid * 16 + lane;
            p.s->stat[row] = (mm & 0xFFFFu) | __float_as_uint(sd) | (tag << 31);
            p.s->key[row] = ((rb ^ (((int)rb >> 31) | 0x80000000u)) & 0xFFFF0000u) | (tag << 15) | (2047 - row);
        }
        bar_sync(1, 192);
        if (tid == 256) mbar_arrive(S + B_P1 * 8);
        {
            const uint2 sm = lds64(S + SM_STA + 8 * t), sh = lds64(S + SM_STA + 32 + 8 * t), sl = lds64(S + SM_STA + 64 + 8 * t);
            const uint32_t at = S + SM_ROWS + (4 * (j >> 1) + (j & 1) + 2 * (mi & 1)) * ROW_STRIDE + 32 * hw + 16 * (mi >> 1);
            uint2* dst = (uint2*)p.s->x + (4 * hw + (g >> 2)) * 2048 + bid * 16 + (g & 3) * 4 + t;
            uint32_t r4[6][4];
#pragma unroll
            for (int n = 5; n >= 0; n--) ldm4t(at + 192 * n, r4[n][0], r4[n][1], r4[n][2], r4[n][3]);
#pragma unroll
            for (int n = 5; n >= 0; n--) {
                uint32_t o[4];
#pragma unroll
                for (int e = 0; e < 4; e++) {
                    const uint32_t v = (e & 1) ? norm2(r4[n][e], sm.y, sh.y, sl.y) : norm2(r4[n][e], sm.x, sh.x, sl.x);
                    o[e] = pack_h(bf_lo(v), bf_hi(v));
                }
                dst[n * 49152] = make_uint2((o[0] & ~1u) | tag, o[1]);
                dst[n * 49152 + 4096] = make_uint2((o[2] & ~1u) | tag, o[3]);
            }
        }
        bar_sync(1, 192);
    }

    if (has) {
        asm volatile("" : "+r"(kp.ldt), "+r"(kp.are), "+r"(kp.aim), "+r"(kp.bre), "+r"(kp.bim), "+r"(kp.cre), "+r"(kp.cim));

        const uint32_t scr = warp < 8 ? S + SM_STG + warp * KG_SCR : S + EX_HAND + hw * KG_SCR;
        kgen(kp, scr, warp < 8 ? scr : S + EX_FAR + hw * 2576, warp < 8 ? 0 : warp & 1, warp < 8 ? 2 : (warp & 1) + 1, rowcta ? S + B_P1 * 8 : 0);
        if (warp >= 8) { __syncwarp(); if (lane == 0) mbar_arrive(S + B_TAB * 8); }
    }
    if (warp < 8 || warp == 15) {
        if (warp < 8 ? has : big) {
            if (warp < 8) bar_sync(4 + slot, 64); else mbar_wait(S + B_TAB * 8, 0);
            ktables(warp < 8 ? S + SM_STG + slot * KG_SCR : S + EX_FAR, warp < 8 ? 4 * KG_SCR : 2576, warp < 8 ? 2 : 4, S + SM_XS + slot * KR_STRIDE,
                    S + (warp < 8 ? SM_KT + slot * KT_STRIDE : EX_KT), S + SM_KINF + slot * 16, warp < 8 ? 1 + (warp >> 2) : 3);
        }
        if (lane == 0) { mbar_arrive(S + B_KG * 8); if (warp == 15) mbar_arrive(S + B_TAB1 * 8); }
    }

    if (!rowcta && warp < 8 && !has) {
        const int w4 = (warp >> 2) * 2 + (warp & 1), i = 32 * w4 + lane;
#pragma unroll 1
        for (int pass = 1; pass < 2; pass++) {
        uint4 k[4];
        if (pass) spin_until(t0, p.tn.t_svc - 1500);
#pragma unroll 1
        for (int it = 0; it < SPIN_LIMIT; it++) {
            if (!pass) {
#pragma unroll
                for (int q = 0; q < 4; q++) k[q] = make_uint4(16 * i + 4 * q, 16 * i + 4 * q + 1, 16 * i + 4 * q + 2, 16 * i + 4 * q + 3);
                break;
            }
            uint32_t bad = 0;
#pragma unroll
            for (int q = 0; q < 4; q++) k[q] = ld_rlx4(&p.s->key[4 * i + 512 * q]);
#pragma unroll
            for (int q = 0; q < 4; q++) bad |= tag ? ~(k[q].x & k[q].y & k[q].z & k[q].w) : (k[q].x | k[q].y | k[q].z | k[q].w);
            if (!(bad & 0x8000u)) break;
            __nanosleep(100);
        }
        const uint32_t sc = S + SM_XS + ((bid & 1) ? 0 : 2) * KR_STRIDE;
        auto pk = [](uint32_t v) { return ((v >> 16) << 11) | (v & 2047u); };
        auto gt = [](uint32_t a, uint32_t b) { return (b - a) >> 31; };
        uint32_t mx = 0;
#pragma unroll
        for (int q = 0; q < 4; q++) {
            k[q] = make_uint4(pk(k[q].x), pk(k[q].y), pk(k[q].z), pk(k[q].w));
            mx = max(max(mx, max(k[q].x, k[q].y)), max(k[q].z, k[q].w));
        }
        bar_sync(1, 128);
        sts32(sc + 4 * i, mx);
        if (i == 0) sts32(sc + 1024, 0u);
        bar_sync(1, 128);
        int rank;
        {
            int c[8] = {0, 0, 0, 0, 0, 0, 0, 0};
#pragma unroll 1
            for (int q = 0; q < 32; q += 4) {
                uint4 v[4];
#pragma unroll
                for (int e = 0; e < 4; e++) v[e] = lds128(sc + 16 * (q + e));
#pragma unroll
                for (int e = 0; e < 4; e++) {
                    c[(2 * e) & 7] += gt(v[e].x, mx); c[(2 * e + 1) & 7] += gt(v[e].y, mx);
                    c[(2 * e + 4) & 7] += gt(v[e].z, mx); c[(2 * e + 5) & 7] += gt(v[e].w, mx);
                }
            }
            rank = ((c[0] + c[1]) + (c[2] + c[3])) + ((c[4] + c[5]) + (c[6] + c[7]));
        }
        if (rank == 7) sts32(sc + 1028, mx);
        bar_sync(1, 128);
        if (rank < 8) {
            const uint32_t lb = lds32(sc + 1028);
            int cq[4];
#pragma unroll
            for (int q = 0; q < 4; q++) cq[q] = (gt(lb, k[q].x) + gt(lb, k[q].y)) + (gt(lb, k[q].z) + gt(lb, k[q].w));
            const int c = 16 - ((cq[0] + cq[1]) + (cq[2] + cq[3]));
            uint32_t pos;
            asm volatile("atom.shared.add.u32 %0, [%1], %2;" : "=r"(pos) : "r"(sc + 1024), "r"(c) : "memory");
            pos = sc + 512 + 4 * pos;
#pragma unroll
            for (int q = 0; q < 4; q++) {
                if (k[q].x >= lb) { sts32(pos, k[q].x); pos += 4; }
                if (k[q].y >= lb) { sts32(pos, k[q].y); pos += 4; }
                if (k[q].z >= lb) { sts32(pos, k[q].z); pos += 4; }
                if (k[q].w >= lb) { sts32(pos, k[q].w); pos += 4; }
            }
        }
        bar_sync(1, 128);
        const int n = lds32(sc + 1024);
        if (i < n) {
            const uint32_t mine = lds32(sc + 512 + 4 * i);
            rank = 0;
#pragma unroll 1
            for (int q = 0; q < n; q += 4) {
                const uint4 v = lds128(sc + 512 + 4 * q);
                rank += ((v.x > mine) + (q + 1 < n && v.y > mine)) + ((q + 2 < n && v.z > mine) + (q + 3 < n && v.w > mine));
            }
            const uint32_t k32 = (mine >> 11) << 16, rb = (k32 ^ ((~(int)k32 >> 31) | 0x80000000u)) & 0xFFFF0000u;
            if (rank < 8 && pass) st_rlx(&p.s->sel[bid - NMAIN][rank], (2047 - (mine & 2047)) | (tag << 15) | (pack_bf(rcpf(1.f + ex2f(-1.4426950408889634f * __uint_as_float(rb))), 0.f) << 16));
        }
        }
    }

    if (warp == 13 || warp == 14) {
        const int i = tid - 416;
        if (i == 0) sts32(S + SM_EPOCH, tag);
        if (rowcta) {
            if (p.tn.t_marg <= 600) {
                const uint32_t back = ld_rlx(p.s->x + 2 * ((4 * hw + 2 + (g >> 2)) * 2048 + bid * 16 + (g & 3) * 4 + t));
                if (back == 0xFFFFFFFFu) __nanosleep(20);
            }
            spin_until(clk32(), p.tn.t_marg);
        } else {
            spin_until(t0, p.tn.t_svc);
        }
        const uint4* xa = (const uint4*)p.s->x + xd * 1024 + i;
        const int e = bid - NDOWN;
        const uint4* xe = (const uint4*)p.s->x + (128 + (e >> 2)) * 1024 + (i >> 1) * 8 + (e & 3) * 2 + (i & 1);
        const uint32_t da = S + SM_X0 + ((i >> 1) & 3) * X0_STRIDE + ((i & 1) ? X0_ODD : 0) + 128 + 16 * (i >> 3);
        const uint32_t de = S + SM_EX + ((i & 1) ? X0_ODD : 0) + 128 + 16 * (i >> 1);
        uint4 v[2][10];
        auto fetch = [&](int half) {
#pragma unroll
            for (int k = 0; k < 10; k++) {
                v[half][k].x = v[half][k].z = tag;
                if (k < 8 || big) v[half][k] = ld_rlx4(k < 8 ? xa + 512 * half + 64 * k : xe + 512 * half + 256 * (k - 8));
            }
        };
        fetch(0); fetch(1);
#pragma unroll
        for (int half = 0; half < 2; half++) {
#pragma unroll 1
            for (int it = 0; it < SPIN_LIMIT; it++) {
                uint32_t bad = 0;
#pragma unroll
                for (int k = 0; k < 10; k++) bad |= (v[half][k].x ^ tag) | (v[half][k].z ^ tag);
                if (!(bad & 1)) break;
                __nanosleep(60);
                fetch(half);
            }
#pragma unroll
            for (int k = 0; k < 10; k++)
                if (k < 8 || big) sts128(k < 8 ? da + 1024 * half + 128 * k : de + 1024 * half + 512 * (k - 8), v[half][k].x & ~1u, v[half][k].y, v[half][k].z & ~1u, v[half][k].w);
            __syncwarp();
            if (lane == 0) mbar_arrive(S + (B_X0 + half) * 8);
        }
    }

    if (warp < 12) {
        const bool cw = warp >= 8;
        if (has) {
            const uint32_t xb = S + (cw ? SM_EX : SM_X0 + slot * X0_STRIDE), kt = S + (cw ? EX_KT : SM_KT + slot * KT_STRIDE);
            const int g0 = cw ? warp - 8 : 0, g1 = cw ? warp - 7 : 4;
            const uint32_t park = (cw ? S + EX_HAND + g0 * 2048 : kt) + lane * 16;
            if (cw) mbar_wait(S + B_TAB1 * 8, 0);
            const uint4 ki = lds128(S + SM_KINF + slot * 16);
            const float inv = __uint_as_float(ki.x);
            if (warp >= 4) {
                const uint32_t fa = S + (cw ? EX_FAR : SM_FAR + slot * FAR_STRIDE);
                mbar_wait(S + (cw ? B_X1 : B_X0) * 8, 0);
                mbar_wait(S + B_KG * 8, 0);
#pragma unroll 1
                for (int rho = cw ? g0 : 0; rho < (cw ? 7 : 4); rho += cw ? 4 : 1) box_round(xb, fa, (!cw && rho == 3) ? 6 : rho, lane);
                if (cw) bar_sync(2, 128); else __syncwarp();
                const int dd = g - 2 * t, gf = g0 ? g0 : 1;
                const uint32_t tb0 = dd == -5 ? ki.z : (dd == -4 ? ki.z << 16 : 0u), tb1 = dd == 3 ? ki.z : (dd == 4 ? ki.z << 16 : 0u);
                uint32_t tad = xb + (mi == 1 ? 144 : mi == 2 ? 128 : X0_ODD + 128) + 16 * j + 512 * gf - 1024;
                uint32_t ad8 = fa + (mi == 0 ? FB9E : mi == 1 ? FB7O : mi == 2 ? FB9O + 16 : FB7E) + 112 - 16 * j + 512 * gf - 768;
                uint32_t ad4 = fa + ((mi & 1) ? FB3 : FB5) + 240 + 16 * (8 * (mi >> 1) - j) + 1024 * gf - 640;
                const uint32_t p4 = kt + KT_P4 + 16 * (g + t), p8 = kt + KT_P8 + 8 * (g + 2 * t);
#pragma unroll 1
                for (int grp = gf; grp < g1; grp++) {
                    float a[4][4], e[2][4], o[2][4];
#pragma unroll
                    for (int k = 0; k < 4; k++) a[0][k] = a[1][k] = a[2][k] = a[3][k] = e[0][k] = e[1][k] = o[0][k] = o[1][k] = 0.f;
                    {
                        if (!cw && grp == 2) {
                            mbar_wait(S + B_X1 * 8, 0);
#pragma unroll 1
                            for (int rho = 3; rho < 6; rho++) box_round(xb, fa, rho, lane);
                            __syncwarp();
                        }
                        {
                            uint4 A4[10];
#pragma unroll
                            for (int s = 0; s < 10; s++) A4[s] = lds128(p4 + 64 * s);
                            auto s4 = [&](int m) {
                                uint32_t b[4];
                                ldm4t(ad4 - 256 * m, b[0], b[1], b[2], b[3]);
#pragma unroll
                                for (int h = 1; h >= 0; h--)
#pragma unroll
                                    for (int i = 0; i < 4; i++) {
                                        const int s = 2 * m - 2 + 2 * i + (1 - h), k = m + (i & 2);
                                        if (k <= 5 && k >= ((i & 1) ? 0 : 1) && !((i & 1) && k == 5)) mma_h(a[i], A4[s >= 0 && s < 10 ? s : 0].x, A4[s >= 0 && s < 10 ? s : 0].y, A4[s >= 0 && s < 10 ? s : 0].z, A4[s >= 0 && s < 10 ? s : 0].w, b[2 * h], b[2 * h + 1]);
                                    }
                            };
                            auto tap = [&](int i) {
                                uint32_t b[4];
                                ldm4(tad + 128 * i, b[0], b[1], b[2], b[3]);
                                mma_h(a[i], b[0], b[1], b[2], b[3], tb1, tb0);
                            };
                            s4(1); s4(0); s4(2); s4(-1); tap(3); s4(-2);
                            if (grp >= 2) { s4(3); tap(0); s4(4); tap(1); s4(5); tap(2); }
                        }
                        {
                            uint32_t A8[9][4];
#pragma unroll
                            for (int k = 0; k < 9; k++) { A8[k][0] = lds32(p8 + 64 * k); A8[k][1] = lds32(p8 + 64 * k + 64); A8[k][2] = lds32(p8 + 64 * k + 4); A8[k][3] = lds32(p8 + 64 * k + 68); }
                            auto s8 = [&](int m) {
                                uint32_t b[4];
                                ldm4t(ad8 - 128 * m, b[0], b[1], b[2], b[3]);
                                mma_h(e[1], A8[m + 2][0], A8[m + 2][1], A8[m + 2][2], A8[m + 2][3], b[0], b[1]);
                                mma_h(o[1], A8[m + 2][0], A8[m + 2][1], A8[m + 2][2], A8[m + 2][3], b[2], b[3]);
                                if (m >= 0) {
                                    mma_h(e[0], A8[m >= 0 ? m : 0][0], A8[m >= 0 ? m : 0][1], A8[m >= 0 ? m : 0][2], A8[m >= 0 ? m : 0][3], b[0], b[1]);
                                    mma_h(o[0], A8[m >= 0 ? m : 0][0], A8[m >= 0 ? m : 0][1], A8[m >= 0 ? m : 0][2], A8[m >= 0 ? m : 0][3], b[2], b[3]);
                                }
                            };
                            s8(-2);
                            if (grp >= 2) {
                                s8(-1); s8(0); s8(1); s8(2);
                                if (grp >= 3) { s8(3); s8(4); s8(5); s8(6); }
                            }
                        }
                    }
                    tad += 512; ad8 += 512; ad4 += 1024;
#pragma unroll
                    for (int pp = 0; pp < 2; pp++) {
                        if (!cw) {
#pragma unroll 1
                            for (int it = 0; it < SPIN_LIMIT && !__all_sync(~0u, lds32v(park + (2 * pp + 1) * 512) == SLOT_FREE); it++) __nanosleep(32);
                        }
#pragma unroll
                        for (int i = 0; i < 2; i++)
                            sts128(park + (2 * pp + i) * 512, __float_as_uint((a[2 * pp + i][0] + e[pp][2 * i]) * inv), __float_as_uint((a[2 * pp + i][1] + e[pp][2 * i + 1]) * inv),
                                   __float_as_uint((a[2 * pp + i][2] + o[pp][2 * i]) * inv), __float_as_uint((a[2 * pp + i][3] + o[pp][2 * i + 1]) * inv));
                    }
                }
            }
            if ((warp & 12) != 4) {
                uint32_t R[66], x[5];
#pragma unroll
                for (int i = 0; i < 66; i++) R[i] = lds32(kt + 4 * (8 + g - 2 * t) + 32 * i);
                float w[5][4];
#pragma unroll
                for (int i = 0; i < 5; i++) w[i][0] = w[i][1] = w[i][2] = w[i][3] = 0.f;
                uint32_t xa = xb + ((lane & 8) ? X0_ODD + 16 : 16) + 16 * j + 512 * g0;
                uint2* yo = (uint2*)p.s->y + (32 * g0 + g) * 2304 + ch * 4 + t;
                mbar_wait(S + B_X0 * 8, 0);
                const uint32_t ytag = lds32(S + SM_EPOCH);
                if (g0 == 0) {
                    const uint32_t x01 = lds32(xb + 128);
                    const float c0 = lane == 31 ? __uint_as_float(ki.y) * inv * h_lo(x01) : 0.f, c1 = lane == 31 ? c0 + __uint_as_float(ki.y) * inv * h_hi(x01) : 0.f;
                    __syncwarp();
#pragma unroll
                    for (int i = 0; i < 4; i++) sts128(park + i * 512, 0u, 0u, i == 3 ? __float_as_uint(c0) : 0u, i == 3 ? __float_as_uint(c1) : 0u);
                }
                ldm2(xa - 16, x[1], x[0]);
                ldm2(xa, x[1], x[2]);
                ldm2(xa + 16, x[3], x[4]);
                uint32_t zz = z, pk = park;
                float sc = inv;
                const bool direct = g0 == 0;
                uint32_t dir = direct;
                asm volatile("" : "+r"(pk));
#pragma unroll 1
                for (int gq = g0; gq < g1; gq++) {
                    uint32_t pa = pk;
#pragma unroll 1
                    for (int n = 4; n > 0; n--) {
                        asm volatile("" : "+r"(zz), "+f"(sc), "+r"(pa), "+r"(dir));
                        sweep_steps<1, 5>(w, R, xa, x, zz);
                        uint4 v = lds128v(pa | (x[4] & zz));
                        sweep_steps<6, 8>(w, R, xa, x, zz);
                        xa += 128;
                        if (__any_sync(~0u, v.x == SLOT_FREE)) {
#pragma unroll 1
                            for (int it = 0; it < SPIN_LIMIT; it++) {
                                v = lds128v(pa);
                                if (!__any_sync(~0u, v.x == SLOT_FREE)) break;
                            }
                        }
                        const float y0 = fmaf(w[0][0], sc, __uint_as_float(v.x)), y1 = fmaf(w[0][1], sc, __uint_as_float(v.y));
                        const float y2 = fmaf(w[0][2], sc, __uint_as_float(v.z)), y3 = fmaf(w[0][3], sc, __uint_as_float(v.w));
                        if (dir) {
                            *yo = make_uint2((pack_bf(y0, y1) & ~1u) | ytag, pack_bf(y2, y3));
                            sts32(pa, SLOT_FREE);
                        } else {
                            sts128(pa, __float_as_uint(y0), __float_as_uint(y1), __float_as_uint(y2), __float_as_uint(y3));
                        }
                        yo += 18432;
                        pa += 512;
                    }
                    if (direct && lane == 0) red_add(&p.s->cnt[(8 + gq) * 32]);
                }
                __syncwarp();
                if (lane == 0) mbar_arrive(S + (direct ? B_EM : B_SP + g0) * 8);
                if (cw && g0 < 3) {
                    mbar_wait(S + (B_SP + g0 + 1) * 8, 0);
#pragma unroll
                    for (int i = 0; i < 4; i++) {
                        const uint4 v = lds128(park + 2048 + i * 512);
                        yo[i * 18432] = make_uint2((pack_bf(fmaf(w[i + 1][0], inv, __uint_as_float(v.x)), fmaf(w[i + 1][1], inv, __uint_as_float(v.y))) & ~1u) | ytag,
                                                   pack_bf(fmaf(w[i + 1][2], inv, __uint_as_float(v.z)), fmaf(w[i + 1][3], inv, __uint_as_float(v.w))));
                    }
                    if (lane == 0) red_add(&p.s->cnt[(8 + g0 + 1) * 32]);
                }
            }
        }
        if (rowcta && (warp & 12) == 4) {
            bar_sync(10, 128);
            const int i = tid - 128, rb0 = 16 * (bid >> 2), c0 = 144 * (bid & 3);
            if (i == 0) mbar_arrive(S + B_FD * 8);
#pragma unroll 3
            for (int v = i; v < 1152; v += 128) {
                const int row = (v * 3641) >> 16, vv = v - 18 * row;
                cp16(S + SM_ROWS + row * 304 + 16 * vv, (const uint4*)(p.u + (size_t)(512 * (row >> 4) + rb0 + (row & 15)) * D_ + c0) + vv);
            }
            if (i < 64) {
                const uint32_t sw = ld_stat(&p.s->stat[512 * (i >> 4) + rb0 + (i & 15)], lds32(S + SM_EPOCH));
                const float ri = rcpf(bf_hi(sw));
                const uint32_t hi = pack_bf(ri, ri);
                const float rl = ri - bf_lo(hi);
                sts128(S + SM_KT + KT_P4 + 16 * i, prmt(sw, sw, 0x1010), hi, pack_bf(rl, rl), 0u);
            }
            asm volatile("cp.async.wait_all;" ::: "memory");
            __syncwarp();
            if (lane == 0) mbar_arrive(S + B_OUT * 8);
        }
        if (!rowcta) return;

        const int rb0 = 16 * (bid >> 2), c0 = 144 * (bid & 3);
        mbar_wait(S + B_OUT * 8, 0);
        mbar_wait(S + B_XS * 8, 0);
        const uint32_t otag = lds32(S + SM_EPOCH) * 0x00010001u;
        const uint2 skip = lds64(S + SM_SKIP);
        const int pi_g = (g & 1) + 8 * ((g >> 1) & 1) + 2 * (g >> 2), pi_j = (j & 1) + 8 * ((j >> 1) & 1) + 2 * (j >> 2);
#pragma unroll 1
        for (int un = warp; un < 36; un += 12) {
            const int q = (un * 57) >> 9, cu = un - 9 * q;
            const uint32_t rw = S + SM_ROWS + 16 * q * 304 + 32 * cu;
            const uint32_t ad = rw + (pi_j + 4 * (mi & 1)) * 304 + 16 * (mi >> 1);
            const uint32_t dk0 = __ldg((const uint32_t*)p.dskip + (c0 >> 1) + 8 * cu + t), dk1 = __ldg((const uint32_t*)p.dskip + (c0 >> 1) + 8 * cu + 4 + t);
            const uint4 sa = lds128(S + SM_KT + KT_P4 + 16 * (16 * q + pi_g)), sb = lds128(S + SM_KT + KT_P4 + 16 * (16 * q + 4 + pi_g));
            uint32_t x[4], tt[4], gt[4], y[4];
            ldm4(ad, x[0], x[1], x[2], x[3]);
#pragma unroll
            for (int e = 0; e < 4; e++) {
                const uint4 s = (e & 1) ? sb : sa;
                const uint32_t xn = norm2(x[e], s.x, s.y, s.z);
                tt[e] = bmul(xn, e < 2 ? dk0 : dk1);
                gt[e] = pack_bf(silu_f(bf_lo(xn)), silu_f(bf_hi(xn)));
            }
            mbar_wait(S + (B_YIN + q) * 8, 0);
            const uint32_t yb = S + SM_STG + q * 4608 + 512 * cu;
#pragma unroll 1
            for (int it = 0; it < SPIN_LIMIT; it++) {
                ldm4t(yb + (8 * (mi >> 1) + j) * 32 + 16 * (mi & 1), y[0], y[1], y[2], y[3]);
                const uint32_t bad = ((y[0] ^ otag) | (y[1] ^ otag) | (y[2] ^ otag) | (y[3] ^ otag)) & 0x00010001u;
                if (!__any_sync(~0u, (g & 3) == 0 && bad)) break;
                const uint4 v = ld_rlx4((const uint4*)(p.s->y + (32 * q + (bid >> 2)) * 4608 + (bid & 3) * 1152 + 128 * cu) + lane);
                __syncwarp();
                sts128(yb + 16 * lane, v.x, v.y, v.z, v.w);
                __syncwarp();
            }
#pragma unroll
            for (int e = 0; e < 4; e++) y[e] = badd(x[e], bmul(badd(y[e], tt[e]), gt[e]));
            stm4(ad, y[0], y[1], y[2], y[3]);
            __syncwarp();
            const int row = lane >> 1;
            const uint4 o = lds128(rw + row * 304 + 16 * (lane & 1));
            if (!((((q & 2) ? skip.y : skip.x) >> (16 * (q & 1) + row)) & 1))
                *((uint4*)(p.out + (size_t)(512 * q + rb0 + row) * D_ + c0 + 16 * cu) + (lane & 1)) = o;
        }
        return;
    }

    {
        const int fw = warp - 13;
        if (fw < nsl) {
            st_rlx(&p.s->h[tag ^ 1][(32 * (sl0 + fw) + 16 * r) * 4 + lane], 0u);
            st_rlx(&p.s->h[tag ^ 1][(32 * (sl0 + fw) + 16 * r) * 4 + 32 + lane], 0u);
        }
        if (fw == 2) {
            spin_until(t0, p.tn.t_xs);
            uint32_t sv = 0;
#pragma unroll 1
            for (int it = 0; it < SPIN_LIMIT; it++) {
                sv = ld_rlx(&p.s->sel[bid & 3][j]);
                if (__all_sync(~0u, ((sv >> 15) & 1) == tag)) break;
                __nanosleep(40);
            }
            mbar_wait(S + B_KG * 8, 0);
            if (lane == 0) { fence_async(); mbar_expect(S + B_BOX * 8, 8 * 1152); }
            __syncwarp();
            if (lane < 8) bulk_g2s(S + SM_XS + lane * ROW_STRIDE, p.u + (size_t)(sv & 2047) * D_, 1152, S + B_BOX * 8);
            const uint32_t st = ld_stat(&p.s->stat[sv & 2047], tag);
            const float ri = rcpf(bf_hi(st));
            const uint32_t hi = pack_bf(ri, ri);
            const float rl = ri - bf_lo(hi);
            if (lane == 0) sts64(S + SM_SKIP, 0u, 0u);
            __syncwarp();
            if (lane < 8) {
                const int row = sv & 2047;
                if (((row >> 4) & 31) == (bid >> 2)) asm volatile("red.shared.or.b32 [%0], %1;" ::"r"(S + SM_SKIP + 4 * (row >> 10)), "r"(1u << (16 * ((row >> 9) & 1) + (row & 15))) : "memory");
                sts32(S + SM_XS + 8 * ROW_STRIDE + 4 * lane, sv);
                sts128(S + SM_RP + 16 * lane, prmt(st, st, 0x1010), hi, pack_bf(rl, rl), 0u);
            }
        }
        asm volatile("barrier.cluster.wait.aligned;" ::: "memory");
        bar_sync(9, 96);
        mbar_wait(S + B_BOX * 8, 0);
#pragma unroll
        for (int k = 0; k < 6; k++) {
            const int v = tid - 416 + 96 * k, tk = (v * 911) >> 16;
            const uint4 x = lds128(S + SM_XS + 16 * (v + tk)), st = lds128(S + SM_RP + 16 * tk);
            sts128(S + SM_XS + 16 * (v + tk), norm2(x.x, st.x, st.y, st.z), norm2(x.y, st.x, st.y, st.z), norm2(x.z, st.x, st.y, st.z), norm2(x.w, st.x, st.y, st.z));
        }
        bar_sync(9, 96);
        if (tid == 416) mbar_arrive(S + B_XS * 8);
        const uint32_t ob = mapa(S, r ^ 1);
        if (fw == 2) {
            if (elect()) {
#pragma unroll 1
                for (int st = 0; st < (down ? 24 : 6 * nsl); st++) {
                    if (st == 12 && down) break;
                    mbar_wait(S + (B_W + st) * 8, 0);
                    if (st % 3 == 2) mbar_arrive(S + (B_GU + st / 3) * 8);
                }
            }
            __syncwarp();
        }
        if (fw < 2) {
            const uint32_t bad = S + SM_XS + j * ROW_STRIDE + mi * 16;
            uint32_t aad = (SW + (8 * (mi >> 1) + j) * 64 + 16 * ((mi & 1) ^ (j >> 1))) ^ ((r ^ fw) * 32);
            uint32_t b[18][4];
#pragma unroll
            for (int k = 0; k < 18; k++) ldm4(bad + 64 * k, b[k][0], b[k][1], b[k][2], b[k][3]);
#pragma unroll 1
            for (int u = 0; u < nsl; u++) {
                float d[4][4];
#pragma unroll
                for (int i = 0; i < 4; i++) d[i][0] = d[i][1] = d[i][2] = d[i][3] = 0.f;
#pragma unroll
                for (int hf = 0; hf < 2; hf++) {
                    mbar_wait(S + (B_GU + 2 * u + hf) * 8, 0);
#pragma unroll
                    for (int sub = 0; sub < 3; sub++) {
                        uint32_t a[6][4];
#pragma unroll
                        for (int k = 0; k < 6; k++) ldm4t(aad + 1024 * k, a[k][0], a[k][1], a[k][2], a[k][3]);
#pragma unroll
                        for (int k = 0; k < 6; k++) {
                            const int kb = 9 * hf + 3 * sub + (k >> 1);
                            mma_bf(d[k & 3], a[k][0], a[k][1], a[k][2], a[k][3], b[kb][2 * (k & 1)], b[kb][2 * (k & 1) + 1]);
                        }
                        aad += STAGE;
                    }
                }
                const uint32_t k0 = pack_bf((d[0][0] + d[1][0]) + (d[2][0] + d[3][0]), (d[0][1] + d[1][1]) + (d[2][1] + d[3][1]));
                const uint32_t k1 = pack_bf((d[0][2] + d[1][2]) + (d[2][2] + d[3][2]), (d[0][3] + d[1][3]) + (d[2][3] + d[3][3]));
                if (fw == 1) {
                    asm volatile("st.async.shared::cluster.mbarrier::complete_tx::bytes.v2.b32 [%0], {%1, %2}, [%3];" ::"r"(ob + SM_PART + u * 256 + lane * 8), "r"(k0), "r"(k1), "r"(ob + (B_GX + u) * 8) : "memory");
                } else {
                    mbar_wait(S + (B_GX + u) * 8, 0);
                    const uint2 o = lds64(S + SM_PART + u * 256 + lane * 8);
#pragma unroll
                    for (int i = 0; i < 2; i++) {
                        const uint32_t mine = i ? k1 : k0, other = i ? o.y : o.x, gb = r ? other : mine, ub = r ? mine : other;
                        uint32_t hv = bmul(pack_bf(silu_f(bf_lo(gb)), silu_f(bf_hi(gb))), ub);
                        if ((hv & 0xFFFFu) == 0) hv |= 0x8000u;
                        if ((hv >> 16) == 0) hv |= 0x80000000u;
                        st_rlx(&p.s->h[tag][(32 * (sl0 + u) + 16 * r) * 4 + 32 * i + lane], hv);
                    }
                    __syncwarp();
                    if (lane < 8) red_add(&p.s->cnt[lane * 32]);
                }
            }
        }
        if (!down) return;

        const int fi = 32 * fw + lane, tok = 4 * r + ((fi >> 4) & 3), cc = 16 * pr + (fi & 15);
        const uint32_t sel = lds32(S + SM_XS + 8 * ROW_STRIDE + 4 * tok);
        const int row = sel & 2047;
        const uint32_t* ya = p.s->y + (row >> 4) * 4608 + cc * 8 + (row & 6);
        const float xraw = __bfloat162float(p.u[(size_t)row * D_ + cc]), dsk = __bfloat162float(p.dskip[cc]);
        const float xn = bf_lo(lds16(S + SM_XS + tok * ROW_STRIDE + 2 * cc));
        if (fw == 0) {
#pragma unroll 1
            for (int st = 12; st < 24; st++) mbar_wait(S + (B_W + st) * 8, 0);
        }
        if (fw == 2 && elect()) wait_count(&p.s->cnt[(bid & 7) * 32], epoch * 288u);
        bar_sync(9, 96);
        float dn[4][4];
        uint2 yv2 = make_uint2(tag ^ 1, 0u);
#pragma unroll 1
        for (int ph = 0; ph < 64; ph++) {
            if (fw == 2 && elect()) {
                fence_async();
                fence_async_g();
                mbar_expect(S + B_H * 8, 36864);
                bulk_g2s(SW, (const char*)p.s->h[tag] + r * 36864, 36864, S + B_H * 8);
            }
            asm volatile("ld.relaxed.gpu.global.v2.u32 {%0,%1}, [%2];" : "=r"(yv2.x), "=r"(yv2.y) : "l"(ya) : "memory");
            mbar_wait(S + B_H * 8, ph & 1);
#pragma unroll
            for (int i = 0; i < 4; i++) dn[i][0] = dn[i][1] = dn[i][2] = dn[i][3] = 0.f;
            uint32_t bq[4] = {~0u, ~0u, ~0u, ~0u};
            const int fr = j + 8 * (mi >> 1);
            uint32_t wa = SW + 12 * STAGE + fw * 2048 + fr * 32 + (((mi & 1) ^ ((fr >> 2) & 1)) << 4), ha = SW + fw * 1024 + lane * 16;
#pragma unroll 1
            for (int s0 = 0; s0 < 12; s0 += 3) {
                uint32_t a[6][8], b[6][4];
#pragma unroll
                for (int s = 0; s < 3; s++) {
                    if (s == 2 && s0 == 9) wa += S + SM_W_LAST - (SW + 23 * STAGE);
#pragma unroll
                    for (int e = 0; e < 2; e++) {
                        ldm4t(ha + e * 512, b[2 * s + e][0], b[2 * s + e][1], b[2 * s + e][2], b[2 * s + e][3]);
                        ldm4t(wa + e * 1024, a[2 * s + e][0], a[2 * s + e][1], a[2 * s + e][2], a[2 * s + e][3]);
                        ldm4t(wa + e * 1024 + 512, a[2 * s + e][4], a[2 * s + e][5], a[2 * s + e][6], a[2 * s + e][7]);
                    }
                    wa += STAGE; ha += 3072;
                }
#pragma unroll
                for (int k = 0; k < 6; k++) {
                    mma_bf(dn[2 * (k & 1)], a[k][0], a[k][1], a[k][2], a[k][3], b[k][0], b[k][1]);
                    mma_bf(dn[2 * (k & 1) + 1], a[k][4], a[k][5], a[k][6], a[k][7], b[k][2], b[k][3]);
#pragma unroll
                    for (int q = 0; q < 4; q++) bq[q] = __vminu2(bq[q], b[k][q]);
                }
            }
            const uint32_t bm = __vminu2(__vminu2(bq[0], bq[1]), __vminu2(bq[2], bq[3])), bd = (bm - 0x00010001u) & ~bm;
            uint32_t anybad;
            asm volatile("{.reg .pred p, q; setp.ne.u32 p, %1, 0; bar.red.or.pred q, 9, 96, p; selp.u32 %0, 1, 0, q;}" : "=r"(anybad) : "r"(bd & 0x80008000u) : "memory");
            if (!anybad) break;
        }
        float* red = (float*)(smem + SM_RED + fw * 512);
        red[(2 * t) * 16 + g] = (dn[0][0] + dn[1][0]) + (dn[2][0] + dn[3][0]);
        red[(2 * t + 1) * 16 + g] = (dn[0][1] + dn[1][1]) + (dn[2][1] + dn[3][1]);
        red[(2 * t) * 16 + g + 8] = (dn[0][2] + dn[1][2]) + (dn[2][2] + dn[3][2]);
        red[(2 * t + 1) * 16 + g + 8] = (dn[0][3] + dn[1][3]) + (dn[2][3] + dn[3][3]);
        bar_sync(9, 96);
        if (fw < 2) {
            const float* rs = (const float*)(smem + SM_RED);
            const int mine = 64 * r + fi, other = mine ^ 64;
            st_async32(ob + SM_RP + 4 * fi, __float_as_uint(rs[other] + rs[128 + other] + rs[256 + other]), ob + B_RED * 8);
            const float s = rs[mine] + rs[128 + mine] + rs[256 + mine];
#pragma unroll 1
            for (int it = 0; it < SPIN_LIMIT && (yv2.x & 1) != tag; it++)
                asm volatile("ld.relaxed.gpu.global.v2.u32 {%0,%1}, [%2];" : "=r"(yv2.x), "=r"(yv2.y) : "l"(ya) : "memory");
            const uint32_t yw = (row & 8) ? yv2.y : yv2.x;
            const float sg = bf_round(((row & 1) ? bf_hi(yw) : bf_lo(yw)) + bf_round(xn * dsk));
            mbar_wait(S + B_RED * 8, 0);
            const float o = *(const float*)(smem + SM_RP + 4 * fi);
            const float yv = bf_round(bf_round(r == 0 ? s + o : o + s) * bf_hi(sel));
            p.out[(size_t)row * D_ + cc] = __float2bfloat16(xraw + bf_round(sg * bf_round(silu_f(bf_round(xn + yv)))));
            if (bid == 0 && fi == 0) st_rlx(&p.s->cnt[16 * 32], epoch);
        }
    }
}

typedef CUresult (*EncodeFn)(CUtensorMap*, CUtensorMapDataType, cuuint32_t, void*, const cuuint64_t*, const cuuint64_t*, const cuuint32_t*,
                             const cuuint32_t*, CUtensorMapInterleave, CUtensorMapSwizzle, CUtensorMapL2promotion, CUtensorMapFloatOOBfill);

static void make2d(EncodeFn enc, CUtensorMap* m, const void* base, uint64_t cols, uint64_t rows, uint32_t bc, uint32_t br, CUtensorMapSwizzle sw) {
    cuuint64_t gd[2] = {cols, rows};
    cuuint64_t gs[1] = {cols * 2};
    cuuint32_t bd[2] = {bc, br}, es[2] = {1, 1};
    enc(m, CU_TENSOR_MAP_DATA_TYPE_BFLOAT16, 2, const_cast<void*>(base), gd, gs, bd, es, CU_TENSOR_MAP_INTERLEAVE_NONE, sw,
        CU_TENSOR_MAP_L2_PROMOTION_L2_128B, CU_TENSOR_MAP_FLOAT_OOB_FILL_NONE);
}

static Tune g_tune = {2000, 9000, 3, 5, 8, 5000, 7500, 0, 9000, 1, 0, 0};


static void launch(void* const* d_in, void* d_out) {
    static EncodeFn enc = nullptr;
    static Scratch* gs = nullptr;
    if (!enc) {
        void* fn = nullptr;
        cudaDriverEntryPointQueryResult qr;
        cudaGetDriverEntryPoint("cuTensorMapEncodeTiled", &fn, cudaEnableDefault, &qr);
        enc = (EncodeFn)fn;
        cudaFuncSetAttribute(fused_kernel, cudaFuncAttributeMaxDynamicSharedMemorySize, SM_TOTAL);
        cudaGetSymbolAddress((void**)&gs, g_s);
    }
    Hot p;
    Maps m;
    auto in = [&](int i) { return (const __nv_bfloat16*)d_in[i]; };
    p.u = in(0); p.are = in(1); p.aim = in(2); p.bre = in(3); p.bim = in(4); p.cre = in(5); p.cim = in(6);
    p.logdt = in(7); p.dskip = in(8); p.wr = in(10); p.pwg = in(11); p.pwu = in(12); p.pwd = in(13);
    p.out = (__nv_bfloat16*)d_out;
    p.tn = g_tune;
    p.s = gs;
    make2d(enc, &m.wg, p.pwg, F_, D_, 32, 96, CU_TENSOR_MAP_SWIZZLE_64B);
    make2d(enc, &m.wu, p.pwu, F_, D_, 32, 96, CU_TENSOR_MAP_SWIZZLE_64B);
    make2d(enc, &m.wd, p.pwd, D_, F_, 16, 192, CU_TENSOR_MAP_SWIZZLE_32B);
    fused_kernel<<<NCTA, NTHREADS, SM_TOTAL>>>(p, m);
}

}

extern "C" void kernel_launch(void* const* d_in, const int* in_sizes, int n_in, void* d_out, int out_size) {
    static int clusters = -1;
    if (clusters < 0) clusters = v3::max_clusters();
    if (clusters < 15 || !v3::launch(d_in, d_out)) v2::launch(d_in, d_out);
}
```

```cpp
#include <cuda_runtime.h>
#include <cuda_bf16.h>
#include <cuda_fp16.h>
#include <cuda.h>
#include <stdint.h>
#include <stddef.h>
#include <type_traits>


namespace v3 {

template <int N> using Int = std::integral_constant<int, N>;

constexpr int D_ = 576, F_ = 4608;
constexpr int NCTA = 120, NTHREADS = 512;
constexpr int SPIN_LIMIT = 1 << 16;

enum { B_Y = 0, B_X = 8, B_TOP = 10, B_XS = 12, B_UP = 13, B_RAW = 15, B_FULL = 16, B_FIN = 43, B_SEL = 44, B_EMPTY = 38  , B_ROWS = 66, B_WR = 67 };
constexpr int SM_SKIP = 544, SM_SEL = 576;
constexpr int SM_ST = 640;
constexpr int SM_RAW = 2688, PITCH = 80;
constexpr int SM_CH = SM_RAW + 256 * PITCH, CH = 18304;
constexpr int TAB = 0, FT = 3072, XX = 3712, BOX = 8064, YIN = 14208;
constexpr int SM_B = SM_CH + 5 * CH, BP = 1168;
constexpr int SM_CAND = SM_B + 8 * BP, SM_PROG = SM_CAND + 256, SM_DUMP = SM_PROG + 128;
constexpr int NRING = 12, SM_W = SM_B + 10240, SM_FIN = SM_W + NRING * 8192, SM_TOTAL = 232448;
static_assert(SM_W % 1024 == 0 && SM_FIN + 8192 <= SM_TOTAL && SM_TOTAL - 18432 >= SM_W + 10 * 8192, "smem");

struct Tune { int t_tile, stag, c256, win5, win4, t_rows, da, t_pf, t_mma, zero; };

struct Scratch {
    uint32_t h[8 * 2304];
    uint2 stat[2048];
    uint32_t ep[NCTA * 8];
};
__device__ __align__(1024) Scratch g_s;

struct Hot {
    const __nv_bfloat16* u;
    int bre, bim, cre, cim, are, aim, logdt, dskip, wr, ep;
    Scratch* s;
    __nv_bfloat16* out;
    const __nv_bfloat16* wg;
    Tune tn;
};
struct Maps { CUtensorMap w[3], u; };

__device__ __forceinline__ uint32_t smem_u32(const void* p) { return (uint32_t)__cvta_generic_to_shared(p); }
__device__ __forceinline__ void mbar_init(uint32_t b, int c) { asm volatile("mbarrier.init.shared::cta.b64 [%0], %1;" ::"r"(b), "r"(c) : "memory"); }
__device__ __forceinline__ void mbar_expect(uint32_t b, int bytes) { asm volatile("mbarrier.arrive.expect_tx.shared::cta.b64 _, [%0], %1;" ::"r"(b), "r"(bytes) : "memory"); }
__device__ __forceinline__ void mbar_arrive(uint32_t b) { asm volatile("mbarrier.arrive.shared::cta.b64 _, [%0];" ::"r"(b) : "memory"); }
__device__ __forceinline__ bool elect() { uint32_t d; asm volatile("{.reg .pred p; elect.sync _|p, 0xffffffff; selp.u32 %0,1,0,p;}" : "=r"(d)); return d; }
__device__ __forceinline__ void mbar_wait(uint32_t b, int par) {
    asm volatile("{\n.reg .pred p;\nLW:\nmbarrier.try_wait.parity.shared::cta.b64 p, [%0], %1, 2000;\n@!p bra LW;\n}" ::"r"(b), "r"(par) : "memory");
}
__device__ __forceinline__ void mbar_wait_short(uint32_t b) {
    asm volatile("{\n.reg .pred p;\nLW:\nmbarrier.try_wait.parity.shared::cta.b64 p, [%0], 0;\n@!p bra LW;\n}" ::"r"(b) : "memory");
}
__device__ __forceinline__ uint32_t mapa(uint32_t a, uint32_t rank) { uint32_t d; asm("mapa.shared::cluster.u32 %0, %1, %2;" : "=r"(d) : "r"(a), "r"(rank)); return d; }
__device__ __forceinline__ void tma2d(uint32_t dst, const CUtensorMap* m, int c0, int c1, uint32_t bar) {
    asm volatile("cp.async.bulk.tensor.2d.shared::cluster.global.mbarrier::complete_tx::bytes [%0], [%1, {%3, %4}], [%2];" ::"r"(dst), "l"(m), "r"(bar), "r"(c0), "r"(c1) : "memory");
}
__device__ __forceinline__ void bulk_g2s(uint32_t dst, const void* src, int bytes, uint32_t bar) {
    asm volatile("cp.async.bulk.shared::cluster.global.mbarrier::complete_tx::bytes [%0], [%1], %2, [%3];" ::"r"(dst), "l"(src), "r"(bytes), "r"(bar) : "memory");
}
__device__ __forceinline__ void bulk_mc(uint32_t dst, const void* src, int bytes, uint32_t bar) {
    asm volatile("cp.async.bulk.shared::cluster.global.mbarrier::complete_tx::bytes.multicast::cluster [%0], [%1], %2, [%3], %4;"
                 ::"r"(dst), "l"(src), "r"(bytes), "r"(bar), "h"((uint16_t)255) : "memory");
}
__device__ __forceinline__ void bar_sync(int id, int n) { asm volatile("bar.sync %0, %1;" ::"r"(id), "r"(n) : "memory"); }
__device__ __forceinline__ void bar_arrive(int id, int n) { asm volatile("bar.arrive %0, %1;" ::"r"(id), "r"(n) : "memory"); }
__device__ __forceinline__ uint4 ld_rlx4(const void* p) { uint4 v; asm volatile("ld.relaxed.gpu.global.v4.u32 {%0,%1,%2,%3}, [%4];" : "=r"(v.x), "=r"(v.y), "=r"(v.z), "=r"(v.w) : "l"(p) : "memory"); return v; }
__device__ __forceinline__ uint2 ld_rlx2(const void* p) { uint2 v; asm volatile("ld.relaxed.gpu.global.v2.u32 {%0,%1}, [%2];" : "=r"(v.x), "=r"(v.y) : "l"(p) : "memory"); return v; }
__device__ __forceinline__ uint32_t ld_rlx(const void* p) { uint32_t v; asm volatile("ld.relaxed.gpu.global.u32 %0, [%1];" : "=r"(v) : "l"(p) : "memory"); return v; }
__device__ __forceinline__ void st_rlx(void* p, uint32_t v) { asm volatile("st.relaxed.gpu.global.u32 [%0], %1;" ::"l"(p), "r"(v) : "memory"); }
__device__ __forceinline__ void st_rlx2(void* p, uint32_t x, uint32_t y) { asm volatile("st.relaxed.gpu.global.v2.u32 [%0], {%1,%2};" ::"l"(p), "r"(x), "r"(y) : "memory"); }
__device__ __forceinline__ uint4 ldg4(const void* p) { uint4 v; asm volatile("ld.global.nc.v4.u32 {%0,%1,%2,%3}, [%4];" : "=r"(v.x), "=r"(v.y), "=r"(v.z), "=r"(v.w) : "l"(p)); return v; }
__device__ __forceinline__ uint32_t ldg1(const void* p) { uint32_t v; asm volatile("ld.global.nc.u32 %0, [%1];" : "=r"(v) : "l"(p)); return v; }
__device__ __forceinline__ uint32_t ldg16(const void* p) { uint16_t v; asm volatile("ld.global.nc.u16 %0, [%1];" : "=h"(v) : "l"(p)); return v; }
__device__ __forceinline__ const void* at256(const void* b, int o) { const void* r; asm("mad.wide.s32 %0, %1, 256, %2;" : "=l"(r) : "r"(o), "l"(b)); return r; }
__device__ __forceinline__ int laneid() { int v; asm volatile("mov.u32 %0, %%laneid;" : "=r"(v)); return v; }
__device__ __forceinline__ uint32_t keep(uint32_t v) { return __shfl_xor_sync(~0u, v, 0); }
__device__ __forceinline__ int ctaid() { int v; asm volatile("mov.u32 %0, %%ctaid.x;" : "=r"(v)); return v; }
__device__ __forceinline__ uint32_t lds32(uint32_t a) { uint32_t v; asm volatile("ld.shared.u32 %0, [%1];" : "=r"(v) : "r"(a) : "memory"); return v; }
__device__ __forceinline__ uint32_t lds32v(uint32_t a) { uint32_t v; asm volatile("ld.volatile.shared.u32 %0, [%1];" : "=r"(v) : "r"(a) : "memory"); return v; }
__device__ __forceinline__ uint32_t lds16(uint32_t a) { uint16_t v; asm volatile("ld.shared.u16 %0, [%1];" : "=h"(v) : "r"(a) : "memory"); return v; }
__device__ __forceinline__ uint2 lds64(uint32_t a) { uint2 v; asm volatile("ld.shared.v2.u32 {%0,%1}, [%2];" : "=r"(v.x), "=r"(v.y) : "r"(a) : "memory"); return v; }
__device__ __forceinline__ uint4 lds128(uint32_t a) { uint4 v; asm volatile("ld.shared.v4.u32 {%0,%1,%2,%3}, [%4];" : "=r"(v.x), "=r"(v.y), "=r"(v.z), "=r"(v.w) : "r"(a) : "memory"); return v; }
__device__ __forceinline__ void sts16(uint32_t a, uint32_t v) { asm volatile("st.shared.u16 [%0], %1;" ::"r"(a), "h"((uint16_t)v) : "memory"); }
__device__ __forceinline__ void sts32(uint32_t a, uint32_t v) { asm volatile("st.shared.u32 [%0], %1;" ::"r"(a), "r"(v) : "memory"); }
__device__ __forceinline__ void sts32v(uint32_t a, uint32_t v) { asm volatile("st.volatile.shared.u32 [%0], %1;" ::"r"(a), "r"(v) : "memory"); }
__device__ __forceinline__ void sts64(uint32_t a, uint32_t x, uint32_t y) { asm volatile("st.shared.v2.u32 [%0], {%1,%2};" ::"r"(a), "r"(x), "r"(y) : "memory"); }
__device__ __forceinline__ void sts128(uint32_t a, uint32_t x, uint32_t y, uint32_t z, uint32_t w) { asm volatile("st.shared.v4.u32 [%0], {%1,%2,%3,%4};" ::"r"(a), "r"(x), "r"(y), "r"(z), "r"(w) : "memory"); }
__device__ __forceinline__ void sts128v(uint32_t a, uint32_t x, uint32_t y, uint32_t z, uint32_t w) { asm volatile("st.volatile.shared.v4.u32 [%0], {%1,%2,%3,%4};" ::"r"(a), "r"(x), "r"(y), "r"(z), "r"(w) : "memory"); }
__device__ __forceinline__ void sts128f(uint32_t a, float x, float y, float z, float w) { asm volatile("st.shared.v4.f32 [%0], {%1,%2,%3,%4};" ::"r"(a), "f"(x), "f"(y), "f"(z), "f"(w) : "memory"); }
__device__ __forceinline__ void st_async4(uint32_t a, uint32_t x, uint32_t y, uint32_t z, uint32_t w, uint32_t bar) {
    asm volatile("st.async.shared::cluster.mbarrier::complete_tx::bytes.v4.b32 [%0], {%1,%2,%3,%4}, [%5];" ::"r"(a), "r"(x), "r"(y), "r"(z), "r"(w), "r"(bar) : "memory");
}
__device__ __forceinline__ void st_async2(uint32_t a, uint32_t x, uint32_t y, uint32_t bar) {
    asm volatile("st.async.shared::cluster.mbarrier::complete_tx::bytes.v2.b32 [%0], {%1,%2}, [%3];" ::"r"(a), "r"(x), "r"(y), "r"(bar) : "memory");
}
__device__ __forceinline__ void st_async2f(uint32_t a, float x, float y, uint32_t bar) {
    asm volatile("st.async.shared::cluster.mbarrier::complete_tx::bytes.v2.f32 [%0], {%1,%2}, [%3];" ::"r"(a), "f"(x), "f"(y), "r"(bar) : "memory");
}
__device__ __forceinline__ void ldm4(uint32_t a, uint32_t& r0, uint32_t& r1, uint32_t& r2, uint32_t& r3) {
    asm volatile("ldmatrix.sync.aligned.m8n8.x4.shared.b16 {%0,%1,%2,%3}, [%4];" : "=r"(r0), "=r"(r1), "=r"(r2), "=r"(r3) : "r"(a) : "memory");
}
__device__ __forceinline__ void ldm4t(uint32_t a, uint32_t (&r)[4]) {
    asm volatile("ldmatrix.sync.aligned.m8n8.x4.trans.shared.b16 {%0,%1,%2,%3}, [%4];" : "=r"(r[0]), "=r"(r[1]), "=r"(r[2]), "=r"(r[3]) : "r"(a) : "memory");
}
__device__ __forceinline__ void ldm2(uint32_t a, uint32_t& r0, uint32_t& r1) {
    asm volatile("ldmatrix.sync.aligned.m8n8.x2.shared.b16 {%0,%1}, [%2];" : "=r"(r0), "=r"(r1) : "r"(a) : "memory");
}
__device__ __forceinline__ void ldm2t(uint32_t a, uint32_t& r0, uint32_t& r1) {
    asm volatile("ldmatrix.sync.aligned.m8n8.x2.trans.shared.b16 {%0,%1}, [%2];" : "=r"(r0), "=r"(r1) : "r"(a) : "memory");
}
__device__ __forceinline__ void stm4(uint32_t a, uint32_t r0, uint32_t r1, uint32_t r2, uint32_t r3) {
    asm volatile("stmatrix.sync.aligned.m8n8.x4.shared.b16 [%0], {%1,%2,%3,%4};" ::"r"(a), "r"(r0), "r"(r1), "r"(r2), "r"(r3) : "memory");
}
__device__ __forceinline__ void stm4t(uint32_t a, uint32_t r0, uint32_t r1, uint32_t r2, uint32_t r3) {
    asm volatile("stmatrix.sync.aligned.m8n8.x4.trans.shared.b16 [%0], {%1,%2,%3,%4};" ::"r"(a), "r"(r0), "r"(r1), "r"(r2), "r"(r3) : "memory");
}
__device__ __forceinline__ void stm2t(uint32_t a, uint32_t r0, uint32_t r1) {
    asm volatile("stmatrix.sync.aligned.m8n8.x2.trans.shared.b16 [%0], {%1,%2};" ::"r"(a), "r"(r0), "r"(r1) : "memory");
}
__device__ __forceinline__ uint32_t movm(uint32_t a) { uint32_t d; asm volatile("movmatrix.sync.aligned.m8n8.trans.b16 %0, %1;" : "=r"(d) : "r"(a)); return d; }
__device__ __forceinline__ void mma_bf(float (&c)[4], uint32_t a0, uint32_t a1, uint32_t a2, uint32_t a3, uint32_t b0, uint32_t b1) {
    asm volatile("mma.sync.aligned.m16n8k16.row.col.f32.bf16.bf16.f32 {%0,%1,%2,%3},{%4,%5,%6,%7},{%8,%9},{%0,%1,%2,%3};"
                 : "+f"(c[0]), "+f"(c[1]), "+f"(c[2]), "+f"(c[3]) : "r"(a0), "r"(a1), "r"(a2), "r"(a3), "r"(b0), "r"(b1));
}
__device__ __forceinline__ void mma_bf8(float (&c)[4], uint32_t a0, uint32_t a1, uint32_t b0) {
    asm volatile("mma.sync.aligned.m16n8k8.row.col.f32.bf16.bf16.f32 {%0,%1,%2,%3},{%4,%5},{%6},{%0,%1,%2,%3};"
                 : "+f"(c[0]), "+f"(c[1]), "+f"(c[2]), "+f"(c[3]) : "r"(a0), "r"(a1), "r"(b0));
}
__device__ __forceinline__ void mma_h(float (&c)[4], uint32_t a0, uint32_t a1, uint32_t a2, uint32_t a3, uint32_t b0, uint32_t b1) {
    asm volatile("mma.sync.aligned.m16n8k16.row.col.f32.f16.f16.f32 {%0,%1,%2,%3},{%4,%5,%6,%7},{%8,%9},{%0,%1,%2,%3};"
                 : "+f"(c[0]), "+f"(c[1]), "+f"(c[2]), "+f"(c[3]) : "r"(a0), "r"(a1), "r"(a2), "r"(a3), "r"(b0), "r"(b1));
}
__device__ __forceinline__ void mma_h8(float (&c)[4], uint32_t a0, uint32_t a1, uint32_t b0) {
    asm volatile("mma.sync.aligned.m16n8k8.row.col.f32.f16.f16.f32 {%0,%1,%2,%3},{%4,%5},{%6},{%0,%1,%2,%3};"
                 : "+f"(c[0]), "+f"(c[1]), "+f"(c[2]), "+f"(c[3]) : "r"(a0), "r"(a1), "r"(b0));
}
template <int LIM>
__device__ __forceinline__ void mma_hp(int n, float (&d)[4], const float (&c)[4], uint32_t a0, uint32_t a1, uint32_t a2, uint32_t a3, uint32_t b0, uint32_t b1) {
    asm volatile("{.reg .pred p; setp.gt.s32 p, %14, %15;\n"
                 "@p mma.sync.aligned.m16n8k16.row.col.f32.f16.f16.f32 {%0,%1,%2,%3},{%4,%5,%6,%7},{%8,%9},{%10,%11,%12,%13};}"
                 : "+f"(d[0]), "+f"(d[1]), "+f"(d[2]), "+f"(d[3])
                 : "r"(a0), "r"(a1), "r"(a2), "r"(a3), "r"(b0), "r"(b1), "f"(c[0]), "f"(c[1]), "f"(c[2]), "f"(c[3]), "r"(n), "n"(LIM));
}
template <int LIM>
__device__ __forceinline__ void mma_hq(int n, float (&d)[4], uint32_t a0, uint32_t a1, uint32_t a2, uint32_t a3, uint32_t b0, uint32_t b1) {
    asm volatile("{.reg .pred p; setp.gt.s32 p, %10, %11;\n"
                 "@p mma.sync.aligned.m16n8k16.row.col.f32.f16.f16.f32 {%0,%1,%2,%3},{%4,%5,%6,%7},{%8,%9},{%0,%1,%2,%3};}"
                 : "+f"(d[0]), "+f"(d[1]), "+f"(d[2]), "+f"(d[3]) : "r"(a0), "r"(a1), "r"(a2), "r"(a3), "r"(b0), "r"(b1), "r"(n), "n"(LIM));
}
__device__ __forceinline__ void mma_hc(float (&d)[4], const float (&c)[4], uint32_t a0, uint32_t a1, uint32_t a2, uint32_t a3, uint32_t b0, uint32_t b1) {
    asm volatile("mma.sync.aligned.m16n8k16.row.col.f32.f16.f16.f32 {%0,%1,%2,%3},{%4,%5,%6,%7},{%8,%9},{%10,%11,%12,%13};"
                 : "=f"(d[0]), "=f"(d[1]), "=f"(d[2]), "=f"(d[3]) : "r"(a0), "r"(a1), "r"(a2), "r"(a3), "r"(b0), "r"(b1), "f"(c[0]), "f"(c[1]), "f"(c[2]), "f"(c[3]));
}
__device__ __forceinline__ uint32_t pack_bf(float lo, float hi) { uint32_t r; asm("cvt.rn.bf16x2.f32 %0, %1, %2;" : "=r"(r) : "f"(hi), "f"(lo)); return r; }
__device__ __forceinline__ uint32_t pack_h(float lo, float hi) { uint32_t r; asm("cvt.rn.f16x2.f32 %0, %1, %2;" : "=r"(r) : "f"(hi), "f"(lo)); return r; }
__device__ __forceinline__ float bf_lo(uint32_t w) { return __uint_as_float(w << 16); }
__device__ __forceinline__ float bf_hi(uint32_t w) { return __uint_as_float(w & 0xFFFF0000u); }
__device__ __forceinline__ float bf_round(float x) { return __uint_as_float(pack_bf(0.f, x)); }
__device__ __forceinline__ uint32_t badd(uint32_t a, uint32_t b) { uint32_t r; asm("add.rn.bf16x2 %0, %1, %2;" : "=r"(r) : "r"(a), "r"(b)); return r; }
__device__ __forceinline__ uint32_t bsub(uint32_t a, uint32_t b) { uint32_t r; asm("sub.rn.bf16x2 %0, %1, %2;" : "=r"(r) : "r"(a), "r"(b)); return r; }
__device__ __forceinline__ uint32_t bmul(uint32_t a, uint32_t b) { uint32_t r; asm("mul.rn.bf16x2 %0, %1, %2;" : "=r"(r) : "r"(a), "r"(b)); return r; }
__device__ __forceinline__ uint32_t bfma(uint32_t a, uint32_t b, uint32_t c) { uint32_t r; asm("fma.rn.bf16x2 %0, %1, %2, %3;" : "=r"(r) : "r"(a), "r"(b), "r"(c)); return r; }
__device__ __forceinline__ uint32_t hadd(uint32_t a, uint32_t b) { uint32_t r; asm("add.rn.f16x2 %0, %1, %2;" : "=r"(r) : "r"(a), "r"(b)); return r; }
__device__ __forceinline__ uint32_t prmt(uint32_t a, uint32_t b, uint32_t s) { uint32_t r; asm("prmt.b32 %0, %1, %2, %3;" : "=r"(r) : "r"(a), "r"(b), "r"(s)); return r; }
__device__ __forceinline__ uint32_t lop_ne(uint32_t a, uint32_t b, uint32_t c) { uint32_t r; asm("lop3.b32 %0, %1, %2, %3, 0x7E;" : "=r"(r) : "r"(a), "r"(b), "r"(c)); return r; }
__device__ __forceinline__ float ex2f(float x) { float r; asm("ex2.approx.ftz.f32 %0, %1;" : "=f"(r) : "f"(x)); return r; }
__device__ __forceinline__ float rcpf(float x) { float r; asm("rcp.approx.ftz.f32 %0, %1;" : "=f"(r) : "f"(x)); return r; }
__device__ __forceinline__ float sqrt_ap(float x) { float r; asm("sqrt.approx.ftz.f32 %0, %1;" : "=f"(r) : "f"(x)); return r; }
__device__ __forceinline__ float tanh_ap(float x) { float r; asm("tanh.approx.f32 %0, %1;" : "=f"(r) : "f"(x)); return r; }
__device__ __forceinline__ float sigm(float x) { return rcpf(1.f + ex2f(-1.4426950408889634f * x)); }
__device__ __forceinline__ float silu_half(float h) { return fmaf(h, tanh_ap(h), h); }
__device__ __forceinline__ uint32_t clk32() { uint32_t c; asm volatile("mov.u32 %0, %%clock;" : "=r"(c)); return c; }
__device__ __forceinline__ void spin_until(uint32_t t0, int dt) {
#pragma unroll 1
    while ((int)(clk32() - t0) < dt) __nanosleep(32);
}
__device__ __forceinline__ void cp16(uint32_t dst, const void* src) { asm volatile("cp.async.cg.shared.global [%0], [%1], 16;" ::"r"(dst), "l"(src) : "memory"); }

__device__ __forceinline__ uint32_t xslot(int s, int h) { return XX + 32 * (s & ~1) + 16 * ((2 * h + (s & 1)) ^ ((s >> 1) & 2)); }

struct cf { float x, y; };
__device__ __forceinline__ cf cmul(cf a, cf b) { return {a.x * b.x - a.y * b.y, a.x * b.y + a.y * b.x}; }
__device__ __forceinline__ cf csq(cf a) { return {a.x * a.x - a.y * a.y, (a.x + a.x) * a.y}; }
__device__ __forceinline__ cf cpow_direct(float zr2, float zi, float l) {
    const float mag = ex2f(zr2 * l), th = zi * l;
    return {mag * __cosf(th), mag * __sinf(th)};
}
struct hp { uint32_t re, im; };
struct hm { __half2 v; };
__device__ __forceinline__ __half2 as_h2(uint32_t v) { return *reinterpret_cast<__half2*>(&v); }
__device__ __forceinline__ uint32_t as_u32(__half2 v) { return *reinterpret_cast<uint32_t*>(&v); }
__device__ __forceinline__ hp mk2(cf a, cf b) { return {pack_h(a.x, b.x), pack_h(a.y, b.y)}; }
__device__ __forceinline__ hm mk1(cf a) { return {as_h2(pack_h(a.x, a.y))}; }
__device__ __forceinline__ hp his(hp a, hp b) { return {prmt(a.re, b.re, 0x7632), prmt(a.im, b.im, 0x7632)}; }
__device__ __forceinline__ hp operator*(hp a, hm b) {
    const __half2 c = __low2half2(b.v), s = __high2half2(b.v), x = as_h2(a.re), y = as_h2(a.im);
    return {as_u32(__hfma2(x, c, __hneg2(__hmul2_rn(y, s)))), as_u32(__hfma2(x, s, __hmul2_rn(y, c)))};
}
__device__ __forceinline__ hp operator*(hp a, hp b) {
    const __half2 c = as_h2(b.re), s = as_h2(b.im), x = as_h2(a.re), y = as_h2(a.im);
    return {as_u32(__hfma2(x, c, __hneg2(__hmul2_rn(y, s)))), as_u32(__hfma2(x, s, __hmul2_rn(y, c)))};
}
struct KParams { uint32_t are, aim, bre, bim, cre, cim, ldt, dsk, sa, la, lb, sb, sm, lm, l3, l4; };

__device__ __forceinline__ void kgen_addr(KParams& kp, uint32_t scr, int lane) {
    const int g = lane >> 2, t = lane & 3, mi = lane >> 3, j = lane & 7;
    kp.sa = keep(scr + 16 * lane);
    kp.sb = keep(scr + 128 * t + 16 * (g ^ (2 * t)));
    kp.la = keep(scr + 512 * (mi & 1) + 128 * (mi >> 1) + 16 * (j ^ (mi & 2)));
    kp.lb = keep((kp.la ^ 64) + 256);
    kp.sm = keep(scr + 2048 + 144 * mi + 16 * j);
    kp.lm = keep(scr + 2048 + 16 * mi);
    kp.l3 = keep(kp.lm + 144 * (j & 1));
    kp.l4 = keep(kp.lm + 288 - 72 * (j & 2));
}

__device__ __forceinline__ uint32_t kgen(KParams kp, uint32_t scr, uint32_t oth, int bar, int lane, float (&d)[5][4], float& k0, int nc, uint32_t pause, uint32_t zero) {
    const float dt = bf_round(ex2f(bf_lo(kp.ldt) * 1.4426950408889634f));
    cf w = cmul({bf_lo(kp.cre), bf_lo(kp.cim)}, {dt * bf_lo(kp.bre), dt * bf_lo(kp.bim)});
    cf w1 = cmul({bf_hi(kp.cre), bf_hi(kp.cim)}, {dt * bf_hi(kp.bre), dt * bf_hi(kp.bim)});
    const float dk = bf_lo(kp.dsk), dt2 = dt * 1.4426950408889634f;
    uint32_t z = prmt(kp.are, kp.aim, 0x5410), z1 = prmt(kp.are, kp.aim, 0x7632);
    uint32_t eb = __reduce_max_sync(~0u, __float_as_uint(fmaxf(fmaxf(fmaxf(fabsf(w.x), fabsf(w.y)), fmaxf(fabsf(w1.x), fabsf(w1.y))), fabsf(dk) * 0x1p-20f)));
    k0 = w.x + w1.x;
    const uint32_t sa = kp.sa, la = kp.la, lb = kp.lb;
    sts128(oth + 2048 + 16 * lane, __float_as_uint(w1.x), __float_as_uint(w1.y), z1, __float_as_uint(k0));
    sts32(oth + 2560, eb);
    bar_sync(bar, 64);
    const uint4 ov = lds128(sa + 2048);
    eb = min(max(max(eb, lds32(scr + 2560)) & 0x7F800000u, 0x00800000u), 0x7A000000u);
    const float sc = __uint_as_float(0x7B000000u - eb);
    k0 = fmaf(dk, sc, 0x1p-28f * __reduce_add_sync(~0u, __float2int_rn((k0 + __uint_as_float(ov.w)) * sc * 0x1p28f)));
#pragma unroll
    for (int i = 0; i < 5; i++) d[i][0] = d[i][1] = d[i][2] = d[i][3] = 0.f;
    const uint32_t sb = kp.sb, sm = kp.sm, lm = kp.lm, l3 = kp.l3, l4 = kp.l4;
    auto st = [&](int grp, hp a, hp b, hp c, hp e) { sts128v(sb + 1024 * grp, a.re, b.re, c.re, e.re); sts128v(sb + 1024 * grp + 512, a.im, b.im, c.im, e.im); };
#pragma unroll 1
    do {
        const float zr2 = dt2 * bf_lo(z), zi = dt * bf_hi(z);
        const cf ws = {w.x * sc, w.y * sc};
        z = z1; w = w1;
        z1 = ov.z; w1 = {__uint_as_float(ov.x), __uint_as_float(ov.y)};
        const cf a1 = cpow_direct(zr2, zi, 1.f), a256 = cpow_direct(zr2, zi, 256.f), b1 = cpow_direct(-zr2, zi, -16.f);
        const cf b2 = csq(b1), b4 = csq(b2), a2 = csq(a1), a4 = csq(a2), a512 = csq(a256), a514 = cmul(a512, a2), c1 = cmul(ws, a1);
        const hm n4 = mk1(b4), m8 = mk1(csq(a4));
        const hp u0 = mk2({1.f, 0.f}, b1), u1 = u0 * mk1(b2), v0 = mk2(c1, cmul(c1, a2)), v1 = v0 * mk1(a4);
        __syncwarp();
        stm4t(sm, as_u32(mk1(cmul(a514, a256)).v), as_u32(mk1(a512).v), as_u32(mk1(csq(a514)).v), as_u32(mk1(a256).v));
        stm2t(sm + 576, as_u32(mk1(csq(b4)).v), as_u32(mk1(a1).v));
        st(0, u0, u1, u0 * n4, u1 * n4);
        st(1, v0, v1, v0 * m8, v1 * m8);
        __syncwarp();
#pragma unroll
        for (int h = 0; h < 2; h++) {
            if (h && pause) { mbar_wait(pause, 0); pause = 0; }
            uint32_t a[4], b[4], q[5][4];
            ldm4t(h ? lb : la, a);
            ldm4t((h ? lb : la) + 1024, b);
#pragma unroll
            for (int e = 0; e < 5; e++) ldm4((e == 3 ? l3 : (e == 4 ? l4 : lm + (e == 2 ? 432 : 576 + 144 * e))) + 64 * h, q[e][0], q[e][1], q[e][2], q[e][3]);
#pragma unroll
            for (int e = 0; e < 4; e += 2) {
                auto mul = [&](int i) { return hp{q[i][e], q[i][e + 1]}; };
                const hp y0 = {b[e], b[e + 1]}, y1 = y0 * mul(1), y2 = y1 * mul(2), y3 = y1 * mul(3), y4 = y3 * mul(4), x1 = hp{a[e], a[e + 1]} * mul(0);
                const uint32_t a0 = a[e] | zero, a2 = a[e + 1] | zero;
                mma_h(d[0], a0, x1.re, a2, x1.im, y0.re, y0.im);
                mma_h(d[1], a0, x1.re, a2, x1.im, y1.re, y1.im);
                mma_h(d[2], a0, x1.re, a2, x1.im, y2.re, y2.im);
                mma_h(d[3], a0, x1.re, a2, x1.im, y3.re, y3.im);
                mma_h(d[4], a0, x1.re, a2, x1.im, y4.re, y4.im);
            }
        }
    } while (--nc);
    return eb;
}

__device__ __forceinline__ void near_lags(uint32_t S, int k, uint32_t yo, uint32_t eb, const uint32_t (&xa)[8], uint32_t step  ) {
    const int lane = threadIdx.x & 31, g = lane >> 2, t = lane & 3, mi = lane >> 3, j = lane & 7, warp = k;
    const uint32_t cb = S + SM_CH + k * CH;
    uint32_t R[66];
#pragma unroll
    for (int i = 0; i < 66; i++) R[i] = lds32(cb + TAB + 4 * (7 + g - 2 * t) + 32 * i);
    bar_arrive(1 + k, 64);
    float w[5][4];
#pragma unroll
    for (int i = 0; i < 5; i++) w[i][0] = w[i][1] = w[i][2] = w[i][3] = 0.f;
    uint32_t xo = cb;
    uint32_t fa = xa[0], idm = 0;
    uint32_t ya[2], yb[2];
#pragma unroll
    for (int e = 0; e < 2; e++) {
        yb[e] = mapa(S + B_Y * 8, 4 * e + (g >> 1));
        ya[e] = yb[e] - B_Y * 8 + SM_CH + k * CH + YIN + (yo ^ (8 * j));
    }
    const uint32_t sc = prmt(eb + 0x04800000u, 0, 0x3232);
    uint32_t z = lds32(cb + XX + 4 * lane);
    mbar_wait(S + B_X * 8, 0);
    uint32_t A[3][4], x[5];
    ldm4(xo + xa[0], x[1], x[2], x[0], x[3]);
    ldm2(xo + xa[1], x[3], x[4]);
    auto send = [&](int e) { st_async2(ya[e], bmul(pack_bf(w[0][0], w[0][1]), sc), bmul(pack_bf(w[0][2], w[0][3]), sc), yb[e]); };
    auto tile = [&](auto nj, auto l4, auto par) {
        constexpr int NJ = decltype(nj)::value, L4 = decltype(l4)::value, P = decltype(par)::value;
        asm volatile("" : "+r"(z), "+r"(xo));
        uint32_t f0, f1;
        if (P < 2) ldm2(xo + fa, f0, f1);
        if (P < 2) send(P);
#pragma unroll
        for (int q = 1; q <= 8; q++) {
            const uint32_t ad = xo + xa[(q + 1) & 7] + 32 * ((q + 1) & 8);
            if (!L4) {
                A[0][0] = x[1]; A[0][1] = x[2]; A[0][2] = x[0] | z; A[0][3] = x[1] | z;
                x[0] = x[2]; x[1] = x[3]; x[2] = x[4];
                ldm2(ad, x[3], x[4]);
            } else {
                ldm4(ad, A[2][0], A[2][1], A[2][2], A[2][3]);
            }
            const float zero[4] = {0.f, 0.f, 0.f, 0.f};
#pragma unroll
            for (int i = 0; i < (NJ < 4 ? NJ : 4); i++) {
                const int s = 16 * i + 16 - 2 * q;
                if (q == 1) mma_hc(w[i], w[i + 1], A[0][0], A[0][1], A[0][2], A[0][3], R[s], R[s + 1]);
                else mma_h(w[i], A[0][0], A[0][1], A[0][2], A[0][3], R[s], R[s + 1]);
            }
            if (q == 4 && P < 2) mma_h8(w[1], f0, f1, idm);
            if (q == 7 && P < 2) {
                const uint32_t zz = A[0][0] & z;
                ya[P & 1] += 512 + zz; yb[P & 1] += 8 + zz;
            }
            if (q == 8 && NJ == 5) mma_hc(w[4], zero, A[0][0], A[0][1], A[0][2], A[0][3], R[64], R[65]);
#pragma unroll
            for (int e = 0; e < 4 * L4; e++) { A[0][e] = A[1][e]; A[1][e] = A[2][e]; }
        }
        xo += step;
    };
    tile(Int<5>(), Int<0>(), Int<2>());
    int n = 17, c = 1;
#pragma unroll 1
    do {
#pragma unroll 1
        do {
            tile(Int<5>(), Int<0>(), Int<0>());
            tile(Int<5>(), Int<0>(), Int<1>());
        } while (--c);
        n -= 4; c = 2;
        const int lane = laneid(), g = lane >> 2, t = lane & 3;
        fa = TAB - 768 + 16 * (lane & 15);
        idm = g == 2 * t ? 0x3C00u : (g == 2 * t + 1 ? 0x3C000000u : 0u);
#pragma unroll 1
        while (lds32v(S + SM_PROG + 4 * k) >= n) __nanosleep(40);
    } while (n > 5);
    ldm4(xo + xa[0], A[0][0], A[0][1], A[0][2], A[0][3]);
    ldm4(xo + xa[1], A[1][0], A[1][1], A[1][2], A[1][3]);
    tile(Int<5>(), Int<1>(), Int<0>());
    tile(Int<4>(), Int<1>(), Int<1>());
    tile(Int<3>(), Int<1>(), Int<0>());
    {
        uint32_t B[16][4], f0, f1;
        ldm2(xo + fa, f0, f1);
        send(1);
#pragma unroll
        for (int e = 0; e < 4; e++) { B[0][e] = A[0][e]; B[1][e] = A[1][e]; }
        const uint32_t x2 = xo + step;
#pragma unroll
        for (int q = 0; q < 8; q++) {
            ldm4(x2 + xa[q], B[8 + q][0], B[8 + q][1], B[8 + q][2], B[8 + q][3]);
            if (q < 6) ldm4(xo + xa[q + 2], B[q + 2][0], B[q + 2][1], B[q + 2][2], B[q + 2][3]);
        }
        w[3][0] = w[3][1] = w[3][2] = w[3][3] = 0.f;
        mma_h8(w[3], f0, f1, idm);
#pragma unroll
        for (int q = 0; q < 8; q++) {
            mma_h(w[1], B[q][0], B[q][1], B[q][2], B[q][3], R[14 - 2 * q], R[15 - 2 * q]);
            mma_h(w[2], B[q][0], B[q][1], B[q][2], B[q][3], R[30 - 2 * q], R[31 - 2 * q]);
            mma_h(w[3], B[8 + q][0], B[8 + q][1], B[8 + q][2], B[8 + q][3], R[14 - 2 * q], R[15 - 2 * q]);
        }
        ya[1] += 512; yb[1] += 8;
#pragma unroll
        for (int e = 0; e < 4; e++) w[0][e] = w[1][e];
        send(0);
#pragma unroll
        for (int e = 0; e < 4; e++) w[0][e] = w[2][e] + w[3][e];
        send(1);
    }
}

__global__ void __cluster_dims__(8, 1, 1) __launch_bounds__(NTHREADS, 1) fused_kernel(const __grid_constant__ Hot p, const __grid_constant__ Maps m) {
    extern __shared__ __align__(1024) char smem[];
    const uint32_t t0 = clk32();
    const int tid = threadIdx.x, lane = tid & 31, bx = blockIdx.x;
    {
        const uint32_t a = min(tid >> 5, 5), ln = 10 * bx + lane;
        const void* pa = at256(p.u + ln * 64, (&p.bre)[a]);
        asm volatile("{.reg .pred p; setp.lt.u32 p, %1, 10; setp.lt.and.u32 p, %2, 192, p; setp.lt.and.u32 p, %3, 1152, p;\n@p prefetch.global.L2 [%0];}"
                     ::"l"(pa), "r"(lane), "r"(tid), "r"(ln) : "memory");
    }
    const int g = lane >> 2, t = lane & 3, mi = lane >> 3, j = lane & 7;
    const uint32_t role = __shfl_sync(~0u, (tid >> 5) | ((uint32_t)((bx < 24 ? 0x5776666632103210ull : 0x5436666621043210ull) >> ((tid >> 3) & 60)) & 15) << 8 |
                                               max(4 * (bx >> 3), 5 * (bx >> 3) - 3) << 16 | bx << 24, 0);
    const int warp = role & 255, k = (role >> 8) & 255, cbase = (role >> 13) & 0x7F8, bid = role >> 24, r = bid & 7, cl = role >> 27;
    const int pair = cl > 2, nch = 4 + pair;
    uint32_t S = smem_u32(smem);
    asm volatile("" : "+r"(S));

    const int half = warp >= nch;
    const bool two = cl == 1 || cl == 2, extra = two && k == 7, svcwarp = (warp >> 2) == 2;
    KParams kp;
    uint32_t epoch, pre[8];
    if (k < nch) {
        const uint32_t ch = cbase + 8 * k + r;
        const char* pb = (const char*)p.u + (ch * 256 + half * 128 + lane * 4);
        kp.bre = ldg1(at256(pb, p.bre)); kp.bim = ldg1(at256(pb, p.bim));
        kp.cre = ldg1(at256(pb, p.cre)); kp.cim = ldg1(at256(pb, p.cim));
        kp.ldt = ldg16(at256(p.u + ch, lane & 1 ? p.dskip : p.logdt));
        kp.are = ldg1(at256(pb, p.are)); kp.aim = ldg1(at256(pb, p.aim));
        sts128(S + SM_CH + k * CH + 16 * lane + (half ? FT : (lane < 2 ? TAB : (lane < 8 ? TAB + 2048 : FT + 384))), 0u, 0u, 0u, 0u);
        sts32(S + SM_PROG + 4 * k, 13);
        kgen_addr(kp, S + SM_CH + k * CH + BOX + 3072 * half, lane);
        if (half) {
            const uint32_t a0 = BOX + 16 + 576 * (j & 1) + 16 * (j >> 1);
            pre[0] = keep(a0 + (mi == 1 ? 1152 : (mi == 2 ? 1136 : 0)));
            pre[1] = keep(a0 + 2304 + 1152 * (mi & 1) + 64 * (mi >> 1));
            pre[2] = keep(BOX + 16 + 4608 + 576 * (mi & 1) + 128 * (mi >> 1) + 16 * j);
            pre[3] = keep(BOX + 16 + (lane < 2 ? 1152 + 576 * lane : 2896));
            pre[4] = keep(xslot(8 + lane, 0));
            pre[5] = keep(xslot(7 + lane, 0));
            pre[6] = keep(FT + 504 - 128 * (t & 1) + 4 * g + (t & 2));
            pre[7] = keep(g == 2 * t ? 0x4432 : (g == 2 * t + 1 ? 0x3244 : 0x4444));
        } else {
            const uint32_t v = xslot(lane & 15, lane >> 4);
#pragma unroll
            for (int i = 0; i < 8; i++) pre[i] = __shfl_sync(~0u, v, j + i + (mi == 1 ? 17 : (mi == 2 ? 16 : 1)));
        }
    } else if (warp == 12) {
        if (elect()) {
            mbar_init(S + B_WR * 8, 1);
            mbar_init(S + B_ROWS * 8, 1);
            mbar_expect(S + B_WR * 8, 1152);
            bulk_g2s(S + SM_B + 2048, (const char*)p.u + p.wr * 256ll, 1152, S + B_WR * 8);
            while ((int)(clk32() - t0) < p.tn.t_rows) {}
            mbar_expect(S + B_ROWS * 8, two ? 36864 : 18432);
            const __nv_bfloat16* src = p.u + (8 * (cl & 14) + 2 * r + (cl & 1)) * 9216;
            bulk_g2s(S + SM_TOTAL - 18432, src, 18432, S + B_ROWS * 8);
            if (two) bulk_g2s(S + SM_CH + 4 * CH - 128, p.u + (113 + 2 * r) * 9216, 18432, S + B_ROWS * 8);
        }
    } else if (svcwarp) {
        if (elect()) {
#pragma unroll
            for (int i = 0; i < 16; i++) mbar_init(S + (warp & 3) * 128 + i * 8, warp > (i < 14 ? 10 : 9) ? 4 : 1);
            asm volatile("fence.mbarrier_init.release.cluster;" ::: "memory");
        }
        __syncwarp();
        sts128(S + SM_B + 16 * tid, 0x3F803F80u, 0x3F803F80u, 0x3F803F80u, 0x3F803F80u);
        if (tid < 256 + B_RAW) mbar_expect(S + lane * 8, (uint32_t)(0x0808480101180804ull >> (8 * max(lane - 7, 0)) & 255) * (lane < B_TOP ? 128 * nch : 128));
    }
    if (svcwarp || extra) epoch = ld_rlx(at256(p.u + bid * 16, p.ep));
    __syncthreads();
    asm volatile("barrier.cluster.arrive.relaxed.aligned;" ::: "memory");
    const uint2* sp = &p.s->stat[256 * r + 2 * (tid & 127)];
    uint4 sw;
    if (svcwarp) sw = ld_rlx4(sp);
    if (svcwarp || extra) {
        const uint32_t tag = ~epoch & 1;
        const int tile = extra ? 15 : cl, wj = extra ? warp + 2 * cl - 15 : warp & 3;
        float d2[4] = {0, 0, 0, 0}, d3[4] = {0, 0, 0, 0}, d4[4] = {0, 0, 0, 0}, d5[4] = {0, 0, 0, 0}, d6[4] = {0, 0, 0, 0}, d7[4] = {0, 0, 0, 0};
        const uint32_t xa = S + (extra ? SM_CH + 4 * CH - 128 : SM_TOTAL - 18432) + (8 * (mi >> 1) + 2 * wj + (mi & 1)) * 1152 + 16 * j;
        const uint32_t wa = S + SM_B + 4104 - 2056 * (g & 1) + 64 * (g >> 2) + 16 * t + 2 * (g & 2), ones = 0x3F803F80u;
        uint32_t wv[18];
        mbar_wait_short(S + B_WR * 8);
#pragma unroll
        for (int i = 0; i < 18; i++) wv[i] = lds32(wa + 128 * (i >> 1) + 8 * (i & 1));
        spin_until(t0, p.tn.t_mma);
#pragma unroll
        for (int i = 0; i < 9; i++) mma_bf(d5, ones, ones, ones, ones, wv[2 * i], wv[2 * i + 1]);
        float wsum = d5[1] + __shfl_xor_sync(~0u, d5[1], 1);
        wsum += __shfl_xor_sync(~0u, wsum, 2);
        mbar_wait_short((S + B_ROWS * 8) | (__float_as_uint(wsum) & p.tn.zero));
        __syncwarp();
#pragma unroll
        for (int i = 0; i < 9; i++) {
            const uint4 x = lds128(xa + 128 * i);
            mma_bf8(d3, x.x, x.y, x.x);
            mma_bf8(d4, x.x, x.y, x.y);
            mma_bf8(d6, x.z, x.w, x.z);
            mma_bf8(d7, x.z, x.w, x.w);
            mma_bf(d2, x.x, x.y, x.z, x.w, wv[2 * i], wv[2 * i + 1]);
        }
        float sx = d2[0] + d2[2], sq = (g & 1) ? (d3[1] + d4[3]) + (d6[1] + d7[3]) : (d3[0] + d4[2]) + (d6[0] + d7[2]);
        float dot = (t & 1) ? d2[3] : d2[1];
        sx += __shfl_xor_sync(~0u, sx, 4);
        sq = __shfl_sync(~0u, sq, 9 * mi) + __shfl_sync(~0u, sq, 9 * mi + 4);
        dot += __shfl_xor_sync(~0u, dot, 1);
        dot += __shfl_xor_sync(~0u, dot, 6);
        const float mean = sx * (1.f / 576.f), var = fmaxf(sq * (1.f / 576.f) - mean * mean, 0.f);
        const float mu = bf_round(mean), sd = bf_round(sqrt_ap(bf_round(bf_round(var) + 1e-5f)));
        const uint32_t idx = 2047 - (128 * (tile & 14) + 32 * r + 16 * (tile & 1) + 8 * (mi >> 1) + 2 * wj + (mi & 1));
        const uint32_t rb = pack_bf(0.f, (dot - mu * wsum) * rcpf(sd));
        uint2 v = make_uint2((__float_as_uint(mu) >> 16) | __float_as_uint(sd), (((rb ^ (((int)rb >> 31) | 0x80000000u)) >> 1) & 0x7FFF8000u) | (tag << 31) | idx);
        uint2* const dst = &p.s->stat[256 * r + 16 * tile];
        if (extra) {
            if (j == 0) st_rlx2(dst + 4 * wj + mi, v.x, v.y);
            bar_arrive(13, 224);
        } else {
        const uint32_t ga = S + SM_B + 3200 + 32 * wj;
        if (j == 0) sts64(ga + 8 * mi, v.x, v.y);
        bar_sync(15, 128);
        if (tid < 272) {
            v = lds64(ga + 8 * lane);
            st_rlx2(dst + lane, v.x, v.y);
        }
        if (lane == 0) mbar_arrive(S + (B_EMPTY + 10) * 8);
        }
    }

    if (k < nch) {
        const uint32_t cb = S + SM_CH + k * CH, scr = cb + BOX + 3072 * half, oth = cb + BOX + 3072 - 3072 * half;
        float d[5][4], k0;
        kp.dsk = __shfl_sync(~0u, kp.ldt, 1);
        kp.ldt = __shfl_sync(~0u, kp.ldt, 0);
        const uint32_t eb = kgen(kp, scr, oth, 1 + k, lane, d, k0, k > 7 - nch ? 3 - 2 * half : 2, ((p.tn.stag >> warp) & 1) ? S + (B_EMPTY + 10) * 8 : 0, p.tn.zero);
        __syncwarp();
#pragma unroll
        for (int i = 0; i < 5; i++)
            if (half == (i < 3)) sts128f(kp.sa + i * 512, d[i][0], d[i][1], d[i][2], d[i][3]);
        bar_sync(1 + k, 64);
        auto both = [&](int i) {
            const uint4 v = lds128(oth + i * 512 + lane * 16);
            d[i][0] += __uint_as_float(v.x); d[i][1] += __uint_as_float(v.y); d[i][2] += __uint_as_float(v.z); d[i][3] += __uint_as_float(v.w);
        };
        if (half) {
            both(3); both(4);
            const uint32_t o = cb + FT + 56 + 2 * lane, q = cb + pre[6];
#pragma unroll
            for (int e = 0; e < 2; e++) {
                const uint32_t a = pack_h(d[3][e], d[3][2 + e]), b = pack_h(d[4][e], d[4][2 + e]);
                sts16(o + 128 - 128 * e, a); sts16(o + 192 - 128 * e, a >> 16);
                sts16(q + 64 - 64 * e, b); sts16(q + 96 - 64 * e, b >> 16);
            }
            bar_sync(1 + k, 64);
        } else {
            {
                both(0); both(1); both(2);
                const uint32_t a[2] = {pack_h(d[0][0], d[1][0]), pack_h(d[0][2], d[1][2])}, b[2] = {pack_h(d[0][1], d[1][1]), pack_h(d[0][3], d[1][3])};
                const uint32_t c[2] = {pack_h(d[2][0], d[2][1]), pack_h(d[2][2], d[2][3])};
                uint32_t last = pack_h(k0, k0);
                const uint32_t o = cb + TAB + 32 + 16 * lane;
                sts16(cb + TAB + 28, last);
#pragma unroll
                for (int h = 0; h < 4; h++) {
                    const uint32_t e = h < 2 ? b[h] : c[h - 2], pv = __shfl_sync(~0u, lane == 31 ? last : e, lane - 1);
                    if (h < 2) sts128(o + 512 * h, prmt(a[h], pv, 0x7610), prmt(a[h], 0, 0x1032), prmt(e, a[h], 0x7610), prmt(e, 0, 0x1032));
                    else sts128(o + 512 * h, prmt(pv, 0, 0x3232), prmt(e, pv, 0x7610), prmt(e, 0, 0x1032), prmt(e, 0, 0x3232));
                    last = e;
                }
                if (lane == 31) sts128(o + 1552, prmt(last, 0, 0x3232), prmt(last, 0, 0x3232), last & 0xFFFF0000u, 0u);
                __syncwarp();
            }
            near_lags(S, k, 64 * r + 16 * ((2 * k + (cbase >> 2) + (r >> 2)) & 3), eb, pre, p.tn.c256);
            return;
        }
    }

    const int ph0 = pair & ~r, f0 = pair ? 32 * (bid & ~1) + 768 : 64 * bid;
    if (k == 7) {
        spin_until(t0, p.tn.t_pf);
#pragma unroll 1
        for (int e = tid - 224; e < 576; e += 64) {
            asm volatile("prefetch.global.L2 [%0];" ::"l"(p.wg + e * F_ + f0) : "memory");
            __nanosleep(100);
        }
        return;
    }
    if (warp == 12) {
        if (elect()) {
            asm volatile("prefetch.tensormap [%0];" ::"l"(m.w + ph0) : "memory");
            asm volatile("prefetch.tensormap [%0];" ::"l"(&m.u) : "memory");
            spin_until(t0, p.tn.t_tile);
            auto raw = [&]() {
                mbar_expect(S + B_RAW * 8, 256 * PITCH);
                asm volatile("cp.async.bulk.tensor.5d.shared::cluster.global.mbarrier::complete_tx::bytes [%0], [%1, {%3, 0, %4, 0, 0}], [%2];"
                             ::"r"(S + SM_RAW), "l"(&m.u), "r"(S + B_RAW * 8), "r"(cbase), "r"(4 * r) : "memory");
            };
            raw();
            uint32_t bar = S + B_FULL * 8, dst = S + SM_W, em = 0x1249400u, wm = pair ? p.tn.win5 : p.tn.win4, wb = bar;
#pragma unroll 1
            for (int ph = ph0; ph < 3; ph += 1 + (pair & r)) {
                const int c0 = ph < 2 ? f0 : cbase, c1 = ph < 2 ? 0 : 576 * r;
#pragma unroll 1
                for (int n = 0; n < 576; n += 64) {
                    if (wm & 3) { wb += 8 * (wm & 3); mbar_wait(wb - 8, 0); }
                    if (em & 1) mbar_wait(bar + 8 * (B_EMPTY - B_FULL), 0);
                    mbar_expect(bar, ph < 2 ? 8192 : 128 * 40);
                    tma2d(dst, m.w + ph, c0, c1 + n, bar);
                    bar += 8; em >>= 1; wm = wm >> 2 | 0x40000000u;
                    dst = dst == S + SM_W + (NRING - 1) * 8192 ? S + SM_W : dst + 8192;
                }
            }
        }
        return;
    }

    if (warp == 15) {
        asm volatile("barrier.cluster.wait.aligned;" ::: "memory");
        sts32(S + SM_SKIP + 4 * j, 0u);
        const uint32_t ob = mapa(S, g);
        bar_sync(13, two ? 224 : 160);
        const uint4 ka = lds128(S + SM_B + 256 + 16 * lane), kb = lds128(S + SM_B + 768 + 16 * lane);
        uint32_t k0 = ka.x, k1 = ka.y, mine = 0, c = 0;
        int rank = lane;
#pragma unroll 1
        for (int pass = 0;; pass++) {
#pragma unroll 1
            for (int n = 0; n < (pass < 2 ? 4 : 8); n++) {
                const uint32_t a = __viaddmin_u32(k0, c, __viaddmin_u32(k1, c, ka.z + c)), b = __viaddmin_u32(ka.w, c, __viaddmin_u32(kb.x, c, kb.y + c));
                c += ~__reduce_min_sync(~0u, __vimin3_u32(a, b, __viaddmin_u32(kb.z, c, kb.w + c)));
                if ((pass < 2 ? t : j) == n) mine = c;
            }
            if (pass == 2) break;
            asm volatile("st.async.shared::cluster.mbarrier::complete_tx::bytes.b32 [%0], %1, [%2];" ::"r"(ob + SM_CAND + 128 * pass + 16 * r + 4 * t), "r"(~mine), "r"(ob + (B_TOP + pass) * 8) : "memory");
            mbar_wait_short(S + (B_TOP + pass) * 8);
            const uint32_t v = lds32(S + SM_CAND + 4 * lane);
            if (pass) {
                k0 = v; k1 = lds32(S + SM_CAND + 128 + 4 * lane); c = 0;
            } else {
                uint32_t cn[4] = {0, 0, 0, 0};
#pragma unroll 4
                for (int e = 0; e < 128; e += 16) {
                    const uint4 o = lds128(S + SM_CAND + e);
                    cn[0] += (o.x - v) >> 31; cn[1] += (o.y - v) >> 31; cn[2] += (o.z - v) >> 31; cn[3] += (o.w - v) >> 31;
                }
                const int rk = (cn[0] + cn[1]) + (cn[2] + cn[3]);
                if (!__any_sync(~0u, t == 3 && rk < 8)) { rank = rk; mine = ~v; break; }
            }
        }
        const uint32_t row = ~mine & 2047, ix = (row & 0xE0) * 8 + ((row >> 3) & 0xE0) + (row & 0x11) + ((row >> 2) & 2) + (row & 6) * 2;
        const uint32_t mr = __reduce_or_sync(~0u, rank == r ? row : 0u);
        if (elect()) {
            bulk_mc(S + SM_B + BP * r, p.u + mr * D_, 1152, S + B_XS * 8);
        }
        const bool own = rank < 8 && (ix >> 8) == r;
        const uint32_t m2 = 2 * mine, rb = (m2 ^ ((~(int)m2 >> 31) | 0x80000000u)) & 0xFFFF0000u;
        if (rank < 8) sts64(S + SM_SEL + 8 * rank, ix | rb, row | ((row & 0x700) + 32 * (row & 6) + 2 * (row & 24) + 8 * (row & 1)) << 16);
        if (own) asm volatile("red.shared.or.b32 [%0], %1;" ::"r"(S + SM_SKIP + 4 * (ix & 7)), "r"(1u << ((ix >> 3) & 31)) : "memory");
        const int no = __popc(__ballot_sync(~0u, own));
        if (lane < 2) mbar_expect(S + (B_FIN + lane) * 8, lane ? 0 : no * (nch - 2) * 256);
        __syncwarp();
        const uint2 sv = lds64(S + SM_SEL + 8 * j);
        float sa, sb;
        asm volatile("ld.shared::cluster.v2.f32 {%0, %1}, [%2];" : "=f"(sa), "=f"(sb) : "r"(mapa(S + SM_ST + (sv.y >> 16), (sv.x >> 8) & 7)) : "memory");
        const float m1 = -sb * rcpf(sa);
        sts32(S + SM_PROG + 32 + 4 * (lane & 15), mi & 1 ? pack_bf(m1, m1) : __float_as_uint(sa + sa));
        bar_arrive(14, 160);
    }

    if (svcwarp) {
        const uint32_t tag = ~epoch & 1;
        const int fw = warp & 3, i = tid & 127;
        uint32_t xbar = mapa(S + B_X * 8, g), xd = keep(xbar - B_X * 8 + SM_CH + xslot(8 + 2 * r + (t >> 1), t & 1) + 256 * (fw & 2));
        uint32_t ra = keep(S + SM_RAW + (64 * mi + j + 4 * (fw & 2)) * PITCH), sa = keep(S + SM_ST + 16 * t + 128 * (fw & 2));
        const uint32_t ta = keep(S + SM_ST + 16 * (i & 0x71) + 32 * (i & 6) + 4 * (i & 8));
        asm volatile("barrier.cluster.wait.aligned;" ::: "memory");
        mbar_wait_short(S + B_RAW * 8);
#pragma unroll 1
        for (int it = 0; it < SPIN_LIMIT && (int)((sw.y ^ -tag) | (sw.w ^ -tag)) < 0; it++) sw = ld_rlx4(sp);
        sts64(S + SM_B + 256 + 8 * i, ~sw.y, ~sw.w);
        {
            const float r0 = 0.5f * rcpf(bf_hi(sw.x)), r1 = 0.5f * rcpf(bf_hi(sw.z));
            sts128f(ta, r0, -bf_lo(sw.x) * r0, r1, -bf_lo(sw.z) * r1);
        }
        bar_sync(13, two ? 224 : 160);
        if (i == 0) st_rlx(&p.s->ep[bid * 8], epoch + 1);
        {
#pragma unroll 1
            for (int u = fw; u < fw + 4; u++) {
                uint4 s[4];
#pragma unroll
                for (int e = 0; e < 4; e++) s[e] = lds128(sa + 64 * e);
#pragma unroll 1
                for (int n = u & 1; n < nch; n += 2) {
                    uint32_t a[4];
                    ldm4t(ra + 16 * n, a);
#pragma unroll
                    for (int e = 0; e < 4; e++)
                        a[e] = pack_h(fmaf(bf_lo(a[e]), __uint_as_float(s[e].x), __uint_as_float(s[e].y)), fmaf(bf_hi(a[e]), __uint_as_float(s[e].z), __uint_as_float(s[e].w)));
                    st_async4(xd + n * CH, a[0], a[1], a[2], a[3], xbar);
                }
                xd += 1024; ra += 16 * PITCH; sa += 512; xbar |= 8;
            }
        }
        const int mt = (fw + 3) & 3;
        const uint32_t aa = keep(S + SM_W + 2048 * fw + (8 * (mi >> 1) + j) * 128 + (((mi & 1) ^ j) << 4)), rd = S + SM_B + 16 * lane;
        uint32_t bar = keep(S + B_FULL * 8 + 8 * min(lane, 2)), of = 0, b[18], k0, k1;
        auto fetch = [&](auto nt, uint32_t (&a)[12][4]) {
            mbar_wait(bar, 0);
            __syncwarp();
#pragma unroll
            for (int e = 0; e < 3 * nt.value; e++) ldm4t((aa ^ (32 * (e % nt.value))) + of + 8192 * (e / nt.value), a[e]);
            if (nt.value == 4 && lane == 0) mbar_arrive(min(bar + (B_EMPTY + NRING - B_FULL) * 8, S + 63 * 8) | (a[11][0] & p.tn.zero));
            bar += 24;
            of = of == 8192 * (NRING - 3) ? 0 : of + 24576;
        };
        float d[4][4];
        auto mul = [&](auto nt, int n, const uint32_t (&a)[12][4]) {
#pragma unroll
            for (int e = 0; e < 3 * nt.value; e++) mma_bf(d[e % nt.value], a[e][0], a[e][1], a[e][2], a[e][3], b[6 * n + 2 * (e / nt.value)], b[6 * n + 2 * (e / nt.value) + 1]);
        };
        auto sum = [&](auto nt, float r0, float r1) {
            bar_sync(15, 128);
#pragma unroll
            for (int e = 0; e < nt.value; e++) sts128f(rd + 2048 * e + 512 * fw, d[e][0], d[e][1], d[e][2], d[e][3]);
            bar_sync(15, 128);
            uint4 v[4];
#pragma unroll
            for (int e = 0; e < 4; e++) v[e] = lds128(rd + 2048 * mt + 512 * e);
#define F4(c) ((__uint_as_float(v[0].c) + __uint_as_float(v[1].c)) + (__uint_as_float(v[2].c) + __uint_as_float(v[3].c)))
            k0 = pack_bf(F4(x) * r0, F4(y) * r1); k1 = pack_bf(F4(z) * r0, F4(w) * r1);
        };
        uint32_t a0[12][4], a1[12][4];
        fetch(Int<4>(), a0);
        bar_sync(14, 160);
        const uint2 sv = lds64(S + SM_SEL + 8 * j);
        {
            const uint32_t mu = lds32(S + SM_PROG + 64 + 4 * g), ba = S + SM_B + BP * j + 32 * fw + 16 * (mi & 1) + 128 * (mi >> 1);
            mbar_wait_short(S + B_XS * 8);
#pragma unroll
            for (int e = 0; e < 4; e++) ldm4(ba + 256 * e, b[4 * e], b[4 * e + 1], b[4 * e + 2], b[4 * e + 3]);
            ldm2(ba + 1024, b[16], b[17]);
#pragma unroll
            for (int e = 0; e < 18; e++) b[e] = bsub(b[e], mu);
        }
        const uint32_t tx = clk32();
#pragma unroll 1
        for (int ph = ph0;; ph++) {
#pragma unroll
            for (int e = 0; e < 4; e++) d[0][e] = d[1][e] = d[2][e] = d[3][e] = 0.f;
            mul(Int<4>(), 0, a0);
            fetch(Int<4>(), a0);
            mul(Int<4>(), 1, a0);
            fetch(Int<4>(), a0);
            mul(Int<4>(), 2, a0);
            if (!pair && !ph) fetch(Int<4>(), a0);
            const uint2 ri = lds64(S + SM_PROG + 32 + 8 * t);
            sum(Int<4>(), __uint_as_float(ri.x), __uint_as_float(ri.y));
            const uint32_t ea = SM_FIN + 6144 + 8 * i, eb = B_UP * 8;
            if (ph == 0) {
                const uint32_t ob = mapa(S, r & ~pair);
                st_async2(ob + ea, k0, k1, ob + eb);
                if (pair) break;
            } else {
                k0 = pack_bf(silu_half(0.5f * bf_lo(k0)), silu_half(0.5f * bf_hi(k0))); k1 = pack_bf(silu_half(0.5f * bf_lo(k1)), silu_half(0.5f * bf_hi(k1)));
                mbar_wait_short((S + eb) | (k0 & k1 & p.tn.zero));
                const uint2 v = lds64(S + ea);
                __syncwarp();
                st_rlx2(p.s->h + 4 * f0 + 64 * mt + 2 * lane, (movm(bmul(k0, v.x)) & ~1u) | tag, movm(bmul(k1, v.y)));
                break;
            }
        }
        {
            fetch(Int<3>(), a0);
            fetch(Int<3>(), a1);
            spin_until(tx, p.tn.da);
            const uint32_t* const hp = p.s->h + 2304 * r + 2 * i;
#pragma unroll 1
            for (int it = 0; it < SPIN_LIMIT; it++) {
#pragma unroll
                for (int e = 0; e < 9; e++) { const uint2 v = ld_rlx2(hp + 256 * e); b[2 * e] = v.x; b[2 * e + 1] = v.y; }
                const uint32_t tm = -tag;
                if (!(((lop_ne(b[0], b[2], tm) | lop_ne(b[4], b[6], tm) | lop_ne(b[8], b[10], tm)) | lop_ne(b[12], b[14], tm) | (b[16] ^ tm)) & 1)) break;
            }
            __syncwarp();
#pragma unroll
            for (int e = 0; e < 4; e++) d[0][e] = d[1][e] = d[2][e] = 0.f;
            mul(Int<3>(), 0, a0);
            fetch(Int<3>(), a0);
            mul(Int<3>(), 1, a1);
            mul(Int<3>(), 2, a0);
            sum(Int<3>(), 1.f, 1.f);
            if (mt < nch - 2) {
                const uint32_t ob = mapa(S, (__shfl_sync(~0u, sv.x, g) >> 8) & 7);
                st_async2(ob + SM_FIN + 768 * g + 96 * r + 32 * mt + 8 * t, movm(k0), movm(k1), ob + B_FIN * 8);
            }
        }
        const int l = min(lane, 4 * nch - 1);
        int n = fw;
#pragma unroll 1
        for (uint32_t own = __ballot_sync(~0u, ((sv.x >> 8) & 7) == r) & 255; own; own &= own - 1) {
            if (n-- & 3) continue;
            const int tk = __ffs(own) - 1;
            const uint2 e = lds64(S + SM_SEL + 8 * tk), st = lds64(S + SM_ST + (e.y >> 16));
            const uint32_t ix = e.x, x = lds32(S + SM_RAW + (16 * (ix & 12) + ((ix >> 2) & 60) + (ix & 3)) * PITCH + 4 * l);
            const uint32_t yb = S + SM_CH + YIN + (l >> 2) * CH + 16 * (ix & 0xE0) + 128 * (l & 3) + 16 * (((ix >> 3) ^ ((l >> 1) + (cbase >> 2))) & 3) + 2 * (ix & 7);
            const float sg = 0.5f * sigm(bf_hi(ix));
            const uint32_t hx = pack_bf(fmaf(bf_lo(x), __uint_as_float(st.x), __uint_as_float(st.y)), fmaf(bf_hi(x), __uint_as_float(st.x), __uint_as_float(st.y))), sg2 = pack_bf(sg, sg);
            mbar_wait((S + B_FIN * 8) | (hx & sg2 & p.tn.zero), 0);
            float a[2] = {0.f, 0.f}, b[2] = {0.f, 0.f};
#pragma unroll
            for (int q = 0; q < 8; q++) {
                const uint32_t v = lds32(S + SM_FIN + 768 * tk + 96 * q + 4 * (l & 24) + 8 * (l & 3) + (l & 4));
                a[q & 1] += bf_lo(v); b[q & 1] += bf_hi(v);
            }
            const uint32_t hv = badd(hx, bmul(pack_bf(a[0] + a[1], b[0] + b[1]), sg2)), gt = pack_bf(silu_half(bf_lo(hv)), silu_half(bf_hi(hv)));
            mbar_wait((S + B_Y * 8 + ((ix >> 2) & 56)) | (gt & p.tn.zero), 0);
            *(uint32_t*)(p.out + (e.y & 2047) * D_ + cbase + 2 * l) = bfma(lds16(yb) | (lds16(yb + 64) << 16), gt, x);
        }
        return;
    }

    mbar_wait(S + B_X * 8, 0);
    if (k < nch) {
        const uint32_t cb = S + SM_CH + k * CH, bx = cb + BOX + 16;
        float u[4][4], v[4][4], w[4][4];
#pragma unroll
        for (int i = 0; i < 4; i++) v[i][0] = v[i][1] = v[i][2] = v[i][3] = w[i][0] = w[i][1] = w[i][2] = w[i][3] = 0.f;
        uint2 T4[10];
        const uint32_t ta = cb + FT + 4 * (g - t);
#pragma unroll
        for (int e = 0; e < 10; e++) T4[e] = lds64(ta + 24 + 32 * e + 4 * (g - t));
        const uint32_t tb = prmt(lds32(cb + FT + 308), 0, pre[7]);
        const uint32_t a4 = cb + pre[0], a8 = cb + pre[1], at = cb + pre[2], hb = cb + pre[3], o = bx + 16 * lane;
        uint32_t xi = cb + pre[4], xp = cb + pre[5], hs = cb + XX;
#pragma unroll 1
        for (int n = 9; n > 0; n -= 4) {
            {
                const uint4 hv = lds128(hs);
                hs = hb + 496;
                const uint2 v0 = lds64(xp + 8);
                const uint4 v1 = lds128(xp ^ 32), v2 = lds128(xi), v3 = lds128(xi ^ 32);
                xi += 1024; xp += 1024;
                __syncwarp();
                if (lane < 3) sts128(hb - 16, hv.x, hv.y, hv.z, hv.w);
                const uint32_t P[13] = {v0.x, v0.y, v1.x, v1.y, v1.z, v1.w, v2.x, v2.y, v2.z, v2.w, v3.x, v3.y, v3.z};
                uint32_t Q[12], s2[12], s4[10], b3[11], b5[9];
#pragma unroll
                for (int e = 0; e < 12; e++) { Q[e] = prmt(P[e], P[e + 1], 0x5432); s2[e] = hadd(P[e], Q[e]); }
#pragma unroll
                for (int e = 0; e < 11; e++) b3[e] = hadd(Q[e], s2[e + 1]);
#pragma unroll
                for (int e = 0; e < 10; e++) s4[e] = hadd(s2[e], s2[e + 1]);
#pragma unroll
                for (int e = 0; e < 9; e++) b5[e] = hadd(s4[e + 1], P[e + 3]);
                sts128(o, b3[3], b3[4], b3[5], b3[6]);
                sts128(o + 1152, b3[7], b3[8], b3[9], b3[10]);
                sts128(o + 576, b5[0], b5[1], b5[2], b5[3]);
                sts128(o + 1728, b5[4], b5[5], b5[6], b5[7]);
                if (n > 4) {
                    sts128(o + 4608, s2[4], s2[5], s2[6], s2[7]);
                    sts128(o + 5184, s2[8], s2[9], s2[10], s2[11]);
                    sts128(o + 2304, hadd(b3[0], s4[2]), hadd(b3[1], s4[3]), hadd(b3[2], s4[4]), hadd(b3[3], s4[5]));
                    sts128(o + 3456, hadd(b3[4], s4[6]), hadd(b3[5], s4[7]), hadd(b3[6], s4[8]), hadd(b3[7], s4[9]));
                    sts128(o + 4032, hadd(s4[0], b5[1]), hadd(s4[1], b5[2]), hadd(s4[2], b5[3]), hadd(s4[3], b5[4]));
                    sts128(o + 2896, hadd(s4[4], b5[5]), hadd(s4[5], b5[6]), hadd(s4[6], b5[7]), hadd(s4[7], b5[8]));
                }
                __syncwarp();
            }
            uint32_t A[8][4];
#pragma unroll
            for (int e = 0; e < 8; e++) ldm4t(a4 + 64 * e, A[e]);
#pragma unroll
            for (int e = 0; e < 8; e++)
#pragma unroll
                for (int b = 3; b >= e / 2; b--) {
                    const uint2 T = T4[2 * (b - e / 2) + 1 - (e & 1)];
                    if (e == 0) mma_hc(u[b], v[b], A[e][0], A[e][1], A[e][2], A[e][3], T.x, T.y);
                    else mma_h(u[b], A[e][0], A[e][1], A[e][2], A[e][3], T.x, T.y);
                }
            if (n == 9) mbar_wait_short(S + (B_X + 1) * 8);
#pragma unroll
            for (int e = 0; e < 2; e++)
                stm4t(cb + TAB + 2304 - 256 * n + 512 * e + 16 * lane, pack_h(u[2 * e][0], u[2 * e][1]), pack_h(u[2 * e][2], u[2 * e][3]),
                      pack_h(u[2 * e + 1][0], u[2 * e + 1][1]), pack_h(u[2 * e + 1][2], u[2 * e + 1][3]));
            __syncwarp();
            sts32v(S + SM_PROG + 4 * k, n);
            if (n == 1) break;
            uint32_t C[4][4], E[2][4], T8[16];
#pragma unroll
            for (int e = 0; e < 4; e++) ldm4t(a8 + 128 * e, C[e]);
#pragma unroll
            for (int e = 0; e < 2; e++) ldm4t(at + 256 * e, E[e]);
#pragma unroll
            for (int e = 0; e < 8; e++) T8[e] = lds32(ta + 376 + 32 * (e >> 1) - 16 * (e & 1));
#pragma unroll
            for (int e = 7; e >= 0; e--)
#pragma unroll
                for (int b = 0; b <= e / 2; b++) {
                    const uint2 T = T4[2 * (4 + b - e / 2) + 1 - (e & 1)];
                    if (e == 7) mma_hc(v[b], w[b], A[e][0], A[e][1], A[e][2], A[e][3], T.x, T.y);
                    else mma_h(v[b], A[e][0], A[e][1], A[e][2], A[e][3], T.x, T.y);
                }
#pragma unroll
            for (int e = 3; e >= 0; e--) {
                mma_h8(v[e], E[e >> 1][2 * (e & 1)], E[e >> 1][2 * (e & 1) + 1], tb);
#pragma unroll
                for (int b = 3; b >= e; b--) mma_h(v[b], C[e][0], C[e][1], C[e][2], C[e][3], T8[2 * (b - e)], T8[2 * (b - e) + 1]);
            }
            if (n == 9) {
#pragma unroll
                for (int e = 8; e < 16; e++) T8[e] = lds32(ta + 376 + 32 * (e >> 1) - 16 * (e & 1));
#pragma unroll
                for (int e = 3; e >= 0; e--)
#pragma unroll
                    for (int b = 0; b < 4; b++) mma_h(w[b], C[e][0], C[e][1], C[e][2], C[e][3], T8[2 * (4 + b - e)], T8[2 * (4 + b - e) + 1]);
            }
        }
    }

  {
    int lane;
    asm volatile("mov.u32 %0, %%laneid;" : "=r"(lane));
    const int g = lane >> 2, t = lane & 3, mi = lane >> 3, j = lane & 7, sh = (cbase >> 3) & 1;
    mbar_wait_short(S + B_SEL * 8);
    if (k < nch - 2 || k == 5) {
        const int one = k == 2, st = k == 5 ? 1 : 2, kk = one ? 4 - 4 * sh : sh + 2 * st - 2;
        const int q0 = k == 1, qx = q0 + (one & (t >> 1)), cx = 16 * kk + 8 * (one ? t & 1 : t);
        uint32_t xa = S + SM_RAW + (16 * (g & 4) + (g & 3) + 8 * qx) * PITCH + cx, sa = S + SM_ST + 16 * (g & 4) + 8 * (g & 3) + 256 * qx, bar = S + (B_Y + qx) * 8;
        uint32_t ya = S + SM_CH + YIN + kk * CH + (j >> 2) * (one ? 512 : CH) + 128 * (j & 2) + 128 * (mi & 1) + 64 * (j & 1) + 512 * q0 +
                      16 * ((mi >> 1) ^ (one ? 2 * sh + ((j >> 1) & 1) : j >> 1));
        uint32_t sk = lds32(S + SM_SKIP + 4 * g) >> (4 * qx);
        char* o = (char*)p.out + ((256 * qx + 32 * r + 4 * (g & 2) + 2 * (g >> 2) + (g & 1)) * D_ + cbase) * 2 + cx;
#pragma unroll 1
        for (int n = 0; n < 8; n += st) {
            uint2 x[4];
            uint32_t gt[8], y[2][4];
#pragma unroll
            for (int e = 0; e < 4; e++) {
                x[e] = lds64(xa + (128 * (e & 1) + 2 * (e & 2)) * PITCH);
                const uint2 s = lds64(sa + 128 * (e & 1) + 16 * (e & 2));
                const float a = __uint_as_float(s.x), b = __uint_as_float(s.y);
                gt[2 * e] = pack_bf(silu_half(fmaf(bf_lo(x[e].x), a, b)), silu_half(fmaf(bf_hi(x[e].x), a, b)));
                gt[2 * e + 1] = pack_bf(silu_half(fmaf(bf_lo(x[e].y), a, b)), silu_half(fmaf(bf_hi(x[e].y), a, b)));
            }
            mbar_wait(bar | (((gt[0] | gt[1] | gt[2]) | (gt[3] | gt[4] | gt[5]) | (gt[6] | gt[7])) & p.tn.zero), 0);
            __syncwarp();
            ldm4t(ya, y[0]);
            ldm4t(ya ^ 32, y[1]);
#pragma unroll
            for (int e = 0; e < 4; e++)
                asm volatile("{.reg .pred p; setp.eq.u32 p, %3, 0;\n@p st.global.v2.u32 [%0], {%1, %2};}" ::"l"(o + (8 * (e & 1) + 16 * (e & 2)) * D_),
                             "r"(bfma(y[e >> 1][2 * (e & 1)], gt[2 * e], x[e].x)), "r"(bfma(y[e >> 1][2 * (e & 1) + 1], gt[2 * e + 1], x[e].y)), "r"(sk & (1 << e)) : "memory");
            xa += 8 * PITCH * st; sa += 256 * st; ya += 512 * st; bar += 8 * st; sk >>= 4 * st; o += 512 * D_ * st;
        }
    }
  }
}

typedef CUresult (*EncodeFn)(CUtensorMap*, CUtensorMapDataType, cuuint32_t, void*, const cuuint64_t*, const cuuint64_t*, const cuuint32_t*,
                             const cuuint32_t*, CUtensorMapInterleave, CUtensorMapSwizzle, CUtensorMapL2promotion, CUtensorMapFloatOOBfill);

static void make2d(EncodeFn enc, CUtensorMap* m, const void* base, uint64_t cols, uint64_t rows, uint32_t bc = 64) {
    cuuint64_t gd[2] = {cols, rows};
    cuuint64_t gs[1] = {cols * 2};
    cuuint32_t bd[2] = {bc, 64}, es[2] = {1, 1};
    enc(m, CU_TENSOR_MAP_DATA_TYPE_BFLOAT16, 2, const_cast<void*>(base), gd, gs, bd, es, CU_TENSOR_MAP_INTERLEAVE_NONE, CU_TENSOR_MAP_SWIZZLE_128B,
        CU_TENSOR_MAP_L2_PROMOTION_L2_128B, CU_TENSOR_MAP_FLOAT_OOB_FILL_NONE);
}

static void make5d(EncodeFn enc, CUtensorMap* m, const void* base, uint32_t cols, CUtensorMapSwizzle sw) {
    cuuint64_t gd[5] = {D_, 2, 32, 8, 4};
    cuuint64_t gs[4] = {D_ * 2, D_ * 16, D_ * 512, D_ * 4};
    cuuint32_t bd[5] = {cols, 2, 4, 8, 4}, es[5] = {1, 1, 1, 1, 1};
    enc(m, CU_TENSOR_MAP_DATA_TYPE_BFLOAT16, 5, const_cast<void*>(base), gd, gs, bd, es, CU_TENSOR_MAP_INTERLEAVE_NONE, sw,
        CU_TENSOR_MAP_L2_PROMOTION_NONE, CU_TENSOR_MAP_FLOAT_OOB_FILL_NONE);
}

static Tune g_tune = {2000, 231, 256, 1431655440, 1431635200, 650, 4800, 4000, 2100, 0};

static int max_clusters() {
    cudaFuncSetAttribute(fused_kernel, cudaFuncAttributeMaxDynamicSharedMemorySize, SM_TOTAL);
    cudaLaunchConfig_t cfg = {};
    cudaLaunchAttribute at[1];
    at[0].id = cudaLaunchAttributeClusterDimension;
    at[0].val.clusterDim.x = 8; at[0].val.clusterDim.y = 1; at[0].val.clusterDim.z = 1;
    cfg.gridDim = dim3(NCTA); cfg.blockDim = dim3(NTHREADS); cfg.dynamicSmemBytes = SM_TOTAL; cfg.attrs = at; cfg.numAttrs = 1;
    int n = 0;
    if (cudaOccupancyMaxActiveClusters(&n, fused_kernel, &cfg) != cudaSuccess) { cudaGetLastError(); n = 0; }
    return n;
}

static bool launch(void* const* d_in, void* d_out) {
    static EncodeFn enc = nullptr;
    static Scratch* gs = nullptr;
    if (!enc) {
        void* fn = nullptr;
        cudaDriverEntryPointQueryResult qr;
        cudaGetDriverEntryPoint("cuTensorMapEncodeTiled", &fn, cudaEnableDefault, &qr);
        enc = (EncodeFn)fn;
        cudaFuncSetAttribute(fused_kernel, cudaFuncAttributeMaxDynamicSharedMemorySize, SM_TOTAL);
        cudaGetSymbolAddress((void**)&gs, g_s);
    }
    Hot p;
    Maps m;
    auto in = [&](int i) { return (const __nv_bfloat16*)d_in[i]; };
    bool ok = true;
    auto off = [&](const void* q) {
        const long long d = (const char*)q - (const char*)d_in[0];
        ok = ok && d / 256 * 256 == d && (int)(d / 256) == d / 256;
        return (int)(d / 256);
    };
    p.u = in(0); p.are = off(in(1)); p.aim = off(in(2)); p.bre = off(in(3)); p.bim = off(in(4)); p.cre = off(in(5)); p.cim = off(in(6));
    p.logdt = off(in(7)); p.dskip = off(in(8)); p.wr = off(in(10)); p.ep = off(gs->ep);
    if (!ok) return false;
    p.out = (__nv_bfloat16*)d_out;
    p.wg = in(11);
    p.tn = g_tune;
    p.s = gs;
    make2d(enc, &m.w[0], in(12), F_, D_);
    make2d(enc, &m.w[1], in(11), F_, D_);
    make2d(enc, &m.w[2], in(13), D_, F_, 40);
    make5d(enc, &m.u, in(0), 40, CU_TENSOR_MAP_SWIZZLE_NONE);
    fused_kernel<<<NCTA, NTHREADS, SM_TOTAL>>>(p, m);
    return true;
}

}

namespace v2 {

constexpr int L_ = 2048, D_ = 576, F_ = 4608;
constexpr int NDOWN = 72, NMAIN = 128, NCTA = 132, NTHREADS = 512;
constexpr int SPIN_LIMIT = 1 << 16;
constexpr uint32_t SLOT_FREE = 0x7FFFABCDu;

constexpr int SM_PART = 544;
constexpr int SM_RED = SM_PART;
constexpr int SM_STA = 2080;
constexpr int SM_ONES = 2176;
constexpr int SM_KINF = 2192;
constexpr int SM_RP = 2272;
constexpr int SM_XS = 2704;
constexpr int KR_STRIDE = 1296;
constexpr int SM_X0 = 12080, X0_STRIDE = 4512, X0_ODD = 2240;
constexpr int SM_KT = 30128, KT_STRIDE = 3584, KT_P4 = 2144, KT_P8 = 2896;
constexpr int SM_FAR = 44544, FAR_STRIDE = 11328;
constexpr int FB5 = 0, FB3 = 3328, FB9E = 6656, FB9O = 7824, FB7E = 8992, FB7O = 10160;
constexpr int SM_ROWS = SM_FAR, ROW_STRIDE = 1168;
constexpr int SM_STG = SM_FAR + 19968;
constexpr int KG_SCR = 3072;
constexpr int SM_EX = 89856;
constexpr int EX_KT = SM_EX + X0_STRIDE, EX_FAR = EX_KT + KT_STRIDE, EX_HAND = 109312;
constexpr int SM_W_DOWN = 90112, SM_W_BIG = 121856, STAGE = 6144;
constexpr int SM_W_LAST = 12288;
constexpr int SM_TOTAL = 232448;
constexpr int SM_EPOCH = 2528, SM_SKIP = 2536;
static_assert(SM_STG + 8 * KG_SCR <= SM_EX && SM_STG % 128 == 0 && EX_HAND % 128 == 0 && EX_FAR + FAR_STRIDE <= EX_HAND && EX_HAND + 12288 <= SM_W_BIG, "scratch");

enum { B_ROWS = 0, B_KG, B_X0, B_X1, B_BOX  , B_TAB, B_EM = 6, B_SP = 10, B_OUT = 14, B_H = 15, B_RED = 16, B_TAB1 = 17, B_XS = 18, B_GX = 19, B_YIN = 22, B_P1 = 26, B_FD, B_GU = 28, B_W = 34, B_COUNT = 58 };

struct Tune { short f_start, f_t3, w2, w2b, w3, t_xs, t_svc, t_marg, f_t2, w1, zero, pad; };

struct Scratch {
    uint32_t x[144 * 4096];
    uint32_t y[128 * 4608];
    uint32_t h[2][F_ * 4];
    uint32_t key[L_];
    uint32_t stat[L_];
    uint32_t sel[4][32];
    uint32_t cnt[17 * 32];
};
__device__ __align__(1024) Scratch g_s;

struct Hot {
    const __nv_bfloat16* u;
    Scratch* s;
    const __nv_bfloat16 *wr, *are, *aim, *bre, *bim, *cre, *cim, *logdt;
    Tune tn;
    const __nv_bfloat16 *dskip, *pwg, *pwu, *pwd;
    __nv_bfloat16* out;
};
struct Maps { CUtensorMap wg, wu, wd; };

__device__ __forceinline__ uint32_t smem_u32(const void* p) { return (uint32_t)__cvta_generic_to_shared(p); }
__device__ __forceinline__ void mbar_init(uint32_t b, int c) { asm volatile("mbarrier.init.shared::cta.b64 [%0], %1;" ::"r"(b), "r"(c) : "memory"); }
__device__ __forceinline__ void mbar_expect(uint32_t b, int bytes) { asm volatile("mbarrier.arrive.expect_tx.shared::cta.b64 _, [%0], %1;" ::"r"(b), "r"(bytes) : "memory"); }
__device__ __forceinline__ void mbar_arrive(uint32_t b) { asm volatile("mbarrier.arrive.shared::cta.b64 _, [%0];" ::"r"(b) : "memory"); }
__device__ __forceinline__ bool elect() { uint32_t d; asm volatile("{.reg .pred p; elect.sync _|p, 0xffffffff; selp.u32 %0,1,0,p;}" : "=r"(d)); return d; }
__device__ __forceinline__ bool mbar_test(uint32_t b, int par) {
    uint32_t d;
    asm volatile("{.reg .pred p; mbarrier.test_wait.parity.shared::cta.b64 p, [%1], %2; selp.u32 %0,1,0,p;}" : "=r"(d) : "r"(b), "r"(par) : "memory");
    return d;
}
#define WAIT_LOOP(ins) "{\n.reg .pred p;\n.reg .u32 n;\nmov.u32 n, 0;\nLW:\n" ins " p, [%0], %1;\n@p bra LD;\nadd.u32 n, n, 1;\nsetp.lt.u32 p, n, 16384;\n@p bra LW;\nLD:\n}"
__device__ __forceinline__ void mbar_wait(uint32_t b, int par) { asm volatile(WAIT_LOOP("mbarrier.try_wait.parity.shared::cta.b64")::"r"(b), "r"(par) : "memory"); }
__device__ __forceinline__ uint32_t mapa(uint32_t a, uint32_t rank) { uint32_t d; asm("mapa.shared::cluster.u32 %0, %1, %2;" : "=r"(d) : "r"(a), "r"(rank)); return d; }
__device__ __forceinline__ void bulk_g2s(uint32_t dst, const void* src, int bytes, uint32_t bar) {
    asm volatile("cp.async.bulk.shared::cluster.global.mbarrier::complete_tx::bytes [%0], [%1], %2, [%3];" ::"r"(dst), "l"(src), "r"(bytes), "r"(bar) : "memory");
}
__device__ __forceinline__ void tma2d(uint32_t dst, const CUtensorMap* m, int c0, int c1, uint32_t bar) {
    asm volatile("cp.async.bulk.tensor.2d.shared::cluster.global.mbarrier::complete_tx::bytes [%0], [%1, {%3, %4}], [%2];" ::"r"(dst), "l"(m), "r"(bar), "r"(c0), "r"(c1) : "memory");
}
__device__ __forceinline__ void pf_tmap(const CUtensorMap* m) { asm volatile("prefetch.tensormap [%0];" ::"l"(m) : "memory"); }
__device__ __forceinline__ void bar_sync(int id, int n) { asm volatile("bar.sync %0, %1;" ::"r"(id), "r"(n) : "memory"); }
__device__ __forceinline__ uint4 ld_rlx4(const void* p) { uint4 v; asm volatile("ld.relaxed.gpu.global.v4.u32 {%0,%1,%2,%3}, [%4];" : "=r"(v.x), "=r"(v.y), "=r"(v.z), "=r"(v.w) : "l"(p) : "memory"); return v; }
__device__ __forceinline__ uint32_t ld_rlx(const void* p) { uint32_t v; asm volatile("ld.relaxed.gpu.global.u32 %0, [%1];" : "=r"(v) : "l"(p) : "memory"); return v; }
__device__ __forceinline__ void st_rlx(void* p, uint32_t v) { asm volatile("st.relaxed.gpu.global.u32 [%0], %1;" ::"l"(p), "r"(v) : "memory"); }
__device__ __forceinline__ uint32_t lds32(uint32_t a) { uint32_t v; asm volatile("ld.shared.u32 %0, [%1];" : "=r"(v) : "r"(a) : "memory"); return v; }
__device__ __forceinline__ uint32_t lds32v(uint32_t a) { uint32_t v; asm volatile("ld.volatile.shared.u32 %0, [%1];" : "=r"(v) : "r"(a) : "memory"); return v; }
__device__ __forceinline__ uint4 lds128v(uint32_t a) { uint4 v; asm volatile("ld.volatile.shared.v4.u32 {%0,%1,%2,%3}, [%4];" : "=r"(v.x), "=r"(v.y), "=r"(v.z), "=r"(v.w) : "r"(a) : "memory"); return v; }
__device__ __forceinline__ uint32_t lds16(uint32_t a) { uint16_t v; asm volatile("ld.shared.u16 %0, [%1];" : "=h"(v) : "r"(a) : "memory"); return v; }
__device__ __forceinline__ uint2 lds64(uint32_t a) { uint2 v; asm volatile("ld.shared.v2.u32 {%0,%1}, [%2];" : "=r"(v.x), "=r"(v.y) : "r"(a) : "memory"); return v; }
__device__ __forceinline__ uint4 lds128(uint32_t a) { uint4 v; asm volatile("ld.shared.v4.u32 {%0,%1,%2,%3}, [%4];" : "=r"(v.x), "=r"(v.y), "=r"(v.z), "=r"(v.w) : "r"(a) : "memory"); return v; }
__device__ __forceinline__ void sts16(uint32_t a, uint32_t v) { asm volatile("st.shared.u16 [%0], %1;" ::"r"(a), "h"((uint16_t)v) : "memory"); }
__device__ __forceinline__ void sts32(uint32_t a, uint32_t v) { asm volatile("st.shared.u32 [%0], %1;" ::"r"(a), "r"(v) : "memory"); }
__device__ __forceinline__ void sts64(uint32_t a, uint32_t x, uint32_t y) { asm volatile("st.shared.v2.u32 [%0], {%1,%2};" ::"r"(a), "r"(x), "r"(y) : "memory"); }
__device__ __forceinline__ void sts128(uint32_t a, uint32_t x, uint32_t y, uint32_t z, uint32_t w) { asm volatile("st.shared.v4.u32 [%0], {%1,%2,%3,%4};" ::"r"(a), "r"(x), "r"(y), "r"(z), "r"(w) : "memory"); }
__device__ __forceinline__ void st_async32(uint32_t a, uint32_t v, uint32_t bar) {
    asm volatile("st.async.shared::cluster.mbarrier::complete_tx::bytes.b32 [%0], %1, [%2];" ::"r"(a), "r"(v), "r"(bar) : "memory");
}
__device__ __forceinline__ void ldm4(uint32_t a, uint32_t& r0, uint32_t& r1, uint32_t& r2, uint32_t& r3) {
    asm volatile("ldmatrix.sync.aligned.m8n8.x4.shared.b16 {%0,%1,%2,%3}, [%4];" : "=r"(r0), "=r"(r1), "=r"(r2), "=r"(r3) : "r"(a) : "memory");
}
__device__ __forceinline__ void ldm4t(uint32_t a, uint32_t& r0, uint32_t& r1, uint32_t& r2, uint32_t& r3) {
    asm volatile("ldmatrix.sync.aligned.m8n8.x4.trans.shared.b16 {%0,%1,%2,%3}, [%4];" : "=r"(r0), "=r"(r1), "=r"(r2), "=r"(r3) : "r"(a) : "memory");
}
__device__ __forceinline__ void ldm2(uint32_t a, uint32_t& r0, uint32_t& r1) {
    asm volatile("ldmatrix.sync.aligned.m8n8.x2.shared.b16 {%0,%1}, [%2];" : "=r"(r0), "=r"(r1) : "r"(a) : "memory");
}
__device__ __forceinline__ void stm4(uint32_t a, uint32_t r0, uint32_t r1, uint32_t r2, uint32_t r3) {
    asm volatile("stmatrix.sync.aligned.m8n8.x4.shared.b16 [%0], {%1,%2,%3,%4};" ::"r"(a), "r"(r0), "r"(r1), "r"(r2), "r"(r3) : "memory");
}
__device__ __forceinline__ void mma_bf(float& c0, float& c1, float& c2, float& c3, uint32_t a0, uint32_t a1, uint32_t a2, uint32_t a3, uint32_t b0, uint32_t b1) {
    asm volatile("mma.sync.aligned.m16n8k16.row.col.f32.bf16.bf16.f32 {%0,%1,%2,%3},{%4,%5,%6,%7},{%8,%9},{%0,%1,%2,%3};"
                 : "+f"(c0), "+f"(c1), "+f"(c2), "+f"(c3) : "r"(a0), "r"(a1), "r"(a2), "r"(a3), "r"(b0), "r"(b1));
}
__device__ __forceinline__ void mma_bf(float (&c)[4], uint32_t a0, uint32_t a1, uint32_t a2, uint32_t a3, uint32_t b0, uint32_t b1) { mma_bf(c[0], c[1], c[2], c[3], a0, a1, a2, a3, b0, b1); }
__device__ __forceinline__ void mma_h(float (&c)[4], uint32_t a0, uint32_t a1, uint32_t a2, uint32_t a3, uint32_t b0, uint32_t b1) {
    asm volatile("mma.sync.aligned.m16n8k16.row.col.f32.f16.f16.f32 {%0,%1,%2,%3},{%4,%5,%6,%7},{%8,%9},{%0,%1,%2,%3};"
                 : "+f"(c[0]), "+f"(c[1]), "+f"(c[2]), "+f"(c[3]) : "r"(a0), "r"(a1), "r"(a2), "r"(a3), "r"(b0), "r"(b1));
}
__device__ __forceinline__ void mma_bf8(float (&c)[4], uint32_t a0, uint32_t a1, uint32_t b0) {
    asm volatile("mma.sync.aligned.m16n8k8.row.col.f32.bf16.bf16.f32 {%0,%1,%2,%3},{%4,%5},{%6},{%0,%1,%2,%3};"
                 : "+f"(c[0]), "+f"(c[1]), "+f"(c[2]), "+f"(c[3]) : "r"(a0), "r"(a1), "r"(b0));
}
__device__ __forceinline__ uint32_t pack_bf(float lo, float hi) { uint32_t r; asm("cvt.rn.bf16x2.f32 %0, %1, %2;" : "=r"(r) : "f"(hi), "f"(lo)); return r; }
__device__ __forceinline__ uint32_t pack_h(float lo, float hi) { uint32_t r; asm("cvt.rn.f16x2.f32 %0, %1, %2;" : "=r"(r) : "f"(hi), "f"(lo)); return r; }
__device__ __forceinline__ float bf_lo(uint32_t w) { return __uint_as_float(w << 16); }
__device__ __forceinline__ float bf_hi(uint32_t w) { return __uint_as_float(w & 0xFFFF0000u); }
__device__ __forceinline__ float bf_round(float x) { return bf_lo(pack_bf(x, 0.f)); }
__device__ __forceinline__ uint32_t badd(uint32_t a, uint32_t b) { uint32_t r; asm("add.rn.bf16x2 %0, %1, %2;" : "=r"(r) : "r"(a), "r"(b)); return r; }
__device__ __forceinline__ uint32_t bsub(uint32_t a, uint32_t b) { uint32_t r; asm("sub.rn.bf16x2 %0, %1, %2;" : "=r"(r) : "r"(a), "r"(b)); return r; }
__device__ __forceinline__ uint32_t bmul(uint32_t a, uint32_t b) { uint32_t r; asm("mul.rn.bf16x2 %0, %1, %2;" : "=r"(r) : "r"(a), "r"(b)); return r; }
__device__ __forceinline__ uint32_t bfma(uint32_t a, uint32_t b, uint32_t c) { uint32_t r; asm("fma.rn.bf16x2 %0, %1, %2, %3;" : "=r"(r) : "r"(a), "r"(b), "r"(c)); return r; }
__device__ __forceinline__ uint32_t prmt(uint32_t a, uint32_t b, uint32_t s) { uint32_t r; asm("prmt.b32 %0, %1, %2, %3;" : "=r"(r) : "r"(a), "r"(b), "r"(s)); return r; }
__device__ __forceinline__ float ex2f(float x) { float r; asm("ex2.approx.ftz.f32 %0, %1;" : "=f"(r) : "f"(x)); return r; }
__device__ __forceinline__ float rcpf(float x) { float r; asm("rcp.approx.ftz.f32 %0, %1;" : "=f"(r) : "f"(x)); return r; }
__device__ __forceinline__ float silu_f(float x) { return x * rcpf(1.f + ex2f(-1.4426950408889634f * x)); }
__device__ __forceinline__ uint32_t norm2(uint32_t x, uint32_t m, uint32_t hi, uint32_t lo) { uint32_t d = bsub(x, m); return bfma(d, hi, bmul(d, lo)); }
__device__ __forceinline__ uint32_t clk32() { uint32_t c; asm volatile("mov.u32 %0, %%clock;" : "=r"(c)); return c; }
__device__ __forceinline__ void spin_until(uint32_t t0, int dt) {
#pragma unroll 1
    while ((int)(clk32() - t0) < dt) __nanosleep(32);
}
__device__ __forceinline__ float sqrt_ap(float x) { float r; asm("sqrt.approx.ftz.f32 %0, %1;" : "=f"(r) : "f"(x)); return r; }

__device__ __forceinline__ void cp16(uint32_t dst, const void* src) { asm volatile("cp.async.cg.shared.global [%0], [%1], 16;" ::"r"(dst), "l"(src) : "memory"); }
__device__ __forceinline__ void pf_l2(const void* p) { asm volatile("cp.async.bulk.prefetch.L2.global [%0], 16;" ::"l"(p) : "memory"); }
__device__ __forceinline__ void bulk_s2g(void* dst, uint32_t src, int bytes) {
    asm volatile("cp.async.bulk.global.shared::cta.bulk_group [%0], [%1], %2;" ::"l"(dst), "r"(src), "r"(bytes) : "memory");
}
__device__ __forceinline__ uint32_t ld_acq(const void* p) { uint32_t v; asm volatile("ld.acquire.gpu.global.u32 %0, [%1];" : "=r"(v) : "l"(p) : "memory"); return v; }
__device__ __forceinline__ void red_add(void* p) { asm volatile("red.relaxed.gpu.global.add.u32 [%0], 1;" ::"l"(p) : "memory"); }
__device__ __forceinline__ void fence_async() { asm volatile("fence.proxy.async.shared::cta;" ::: "memory"); }
__device__ __forceinline__ void fence_async_g() { asm volatile("fence.proxy.async.global;" ::: "memory"); }
__device__ __forceinline__ void red_rel(void* p) { asm volatile("red.release.gpu.global.add.u32 [%0], 1;" ::"l"(p) : "memory"); }
__device__ __forceinline__ void wait_count(const uint32_t* p, uint32_t want) {
#pragma unroll 1
    for (int it = 0; it < SPIN_LIMIT && ld_rlx(p) != want; it++) __nanosleep(20);
}
__device__ __forceinline__ uint32_t ld_stat(const uint32_t* p, uint32_t tag) {
    uint32_t v = 0;
#pragma unroll 1
    for (int it = 0; it < SPIN_LIMIT; it++) {
        v = ld_rlx(p);
        if ((v >> 31) == tag) break;
    }
    return v & 0x7FFFFFFFu;
}
__device__ __forceinline__ uint32_t hadd(uint32_t a, uint32_t b) { uint32_t r; asm("add.rn.f16x2 %0, %1, %2;" : "=r"(r) : "r"(a), "r"(b)); return r; }
__device__ __forceinline__ float h_lo(uint32_t w) { return __half2float(__ushort_as_half((unsigned short)w)); }
__device__ __forceinline__ float h_hi(uint32_t w) { return __half2float(__ushort_as_half((unsigned short)(w >> 16))); }
__device__ __forceinline__ uint32_t x0_chunk(uint32_t xb, int c) { return xb + ((c & 1) ? X0_ODD + 120 : 128) + 8 * c; }

struct cf { float x, y; };
__device__ __forceinline__ cf cmul(cf a, cf b) { return {a.x * b.x - a.y * b.y, a.x * b.y + a.y * b.x}; }
__device__ __forceinline__ cf csq(cf a) { return {a.x * a.x - a.y * a.y, (a.x + a.x) * a.y}; }
__device__ __forceinline__ cf cpow_direct(float zr2, float zi, float l) {
    const float mag = ex2f(zr2 * l), th = zi * l;
    return {mag * __cosf(th), mag * __sinf(th)};
}
__device__ __forceinline__ __half2 as_h2(uint32_t v) { return *reinterpret_cast<__half2*>(&v); }
__device__ __forceinline__ uint32_t as_u32(__half2 v) { return *reinterpret_cast<uint32_t*>(&v); }
struct hm { uint32_t v, s; };
__device__ __forceinline__ hm mk_hm(cf a) {
    const uint32_t v = pack_h(a.x, a.y);
    return {v, prmt(v, v, 0x1032) ^ 0x8000u};
}
__device__ __forceinline__ uint32_t hcmul(uint32_t x, hm y) {
    const __half2 xx = as_h2(x);
    return as_u32(__hfma2(__high2half2(xx), as_h2(y.s), __hmul2(__low2half2(xx), as_h2(y.v))));
}

struct KParams { uint32_t are, aim, bre, bim, cre, cim, ldt; };
__device__ __forceinline__ KParams kgen_load(const Hot& p, int ch, int half, int lane) {
    const uint32_t po = ch * 64 + half * 32 + lane;
    KParams k;
    k.are = __ldg((const uint32_t*)p.are + po); k.aim = __ldg((const uint32_t*)p.aim + po);
    k.bre = __ldg((const uint32_t*)p.bre + po); k.bim = __ldg((const uint32_t*)p.bim + po);
    k.cre = __ldg((const uint32_t*)p.cre + po); k.cim = __ldg((const uint32_t*)p.cim + po);
    k.ldt = __ldg((const uint16_t*)p.logdt + ch + (lane & p.tn.zero));
    return k;
}

__device__ __forceinline__ void kgen(KParams kp, uint32_t scr, uint32_t os, int c0, int c1, uint32_t pause) {
    const int lane = threadIdx.x & 31;
    const float dt = bf_round(ex2f(bf_lo(kp.ldt) * 1.4426950408889634f));
    const cf w0 = cmul({bf_lo(kp.cre), bf_lo(kp.cim)}, {dt * bf_lo(kp.bre), dt * bf_lo(kp.bim)});
    const cf w1 = cmul({bf_hi(kp.cre), bf_hi(kp.cim)}, {dt * bf_hi(kp.bre), dt * bf_hi(kp.bim)});
    uint32_t eb = __reduce_max_sync(~0u, __float_as_uint(fmaxf(fmaxf(fabsf(w0.x), fabsf(w0.y)), fmaxf(fabsf(w1.x), fabsf(w1.y))))) & 0x7F800000u;
    eb = min(max(eb, 0x00800000u), 0x7E800000u);
    const float sc = __uint_as_float(0x7F000000u - eb);
    float k0 = c0 ? 0.f : w0.x + w1.x;
#pragma unroll
    for (int o = 16; o > 0; o >>= 1) k0 += __shfl_xor_sync(~0u, k0, o);
    float d[5][4];
#pragma unroll
    for (int i = 0; i < 5; i++) d[i][0] = d[i][1] = d[i][2] = d[i][3] = 0.f;
    const int mi = lane >> 3, j = lane & 7;
    const uint32_t st0 = scr + mi * 128 + ((j ^ mi) << 4), st1 = st0 ^ 64;
    const uint32_t la = scr + (lane & 15) * 128 + (((lane >> 4) ^ j) << 4), lb = scr + j * 128 + ((mi ^ j) << 4);
    auto st = [&](int row, uint32_t a, uint32_t b, uint32_t c, uint32_t e) { stm4(((row & 4) ? st1 : st0) + row * 128, a, b, c, e); };
#pragma unroll 1
    for (int c = c0; c < c1; c++) {
        if (c > c0 && pause) mbar_wait(pause, 0);
        const float zr2 = dt * (c ? bf_hi(kp.are) : bf_lo(kp.are)) * 1.4426950408889634f;
        const float zi = dt * (c ? bf_hi(kp.aim) : bf_lo(kp.aim));
        const cf w = {(c ? w1.x : w0.x) * sc, (c ? w1.y : w0.y) * sc};
        const cf a1 = cpow_direct(zr2, zi, 1.f), a256 = cpow_direct(zr2, zi, 256.f);
        uint32_t a[4][4];
        {
            const cf a16 = cpow_direct(-zr2, zi, -16.f);
            const cf a32 = csq(a16), a48 = cmul(a32, a16), a64 = csq(a32), a128 = csq(a64), a192 = cmul(a128, a64);
            const uint32_t p1 = pack_h(a16.x, a16.y), p2 = pack_h(a32.x, a32.y), p3 = pack_h(a48.x, a48.y);
            const hm q1 = mk_hm(a64), q2 = mk_hm(a128), q3 = mk_hm(a192);
            __syncwarp();
            st(0, 0x00003C00u, p1, p2, p3);
            st(4, q1.v, hcmul(p1, q1), hcmul(p2, q1), hcmul(p3, q1));
            st(8, q2.v, hcmul(p1, q2), hcmul(p2, q2), hcmul(p3, q2));
            st(12, q3.v, hcmul(p1, q3), hcmul(p2, q3), hcmul(p3, q3));
            __syncwarp();
#pragma unroll
            for (int k = 0; k < 4; k++) ldm4(la ^ (k * 32), a[k][0], a[k][1], a[k][2], a[k][3]);
        }
        auto tile = [&](int T, int row) {
#pragma unroll
            for (int kp2 = 0; kp2 < 2; kp2++) {
                uint32_t b0, b1, b2, b3;
                ldm4((lb ^ (kp2 * 64)) + row * 128, b0, b1, b2, b3);
                mma_h(d[T], a[2 * kp2][0], a[2 * kp2][1], a[2 * kp2][2], a[2 * kp2][3], b0, b1);
                mma_h(d[T], a[2 * kp2 + 1][0], a[2 * kp2 + 1][1], a[2 * kp2 + 1][2], a[2 * kp2 + 1][3], b2, b3);
            }
        };
        const cf a2 = csq(a1), a4 = csq(a2), a8 = csq(a4), a12 = cmul(a8, a4);
        const cf u1 = cmul(w, a1), u2 = cmul(w, a2), u3 = cmul(u2, a1), u4 = cmul(w, a4);
        uint32_t v[16];
        v[0] = pack_h(u1.x, u1.y); v[1] = pack_h(u2.x, u2.y); v[2] = pack_h(u3.x, u3.y); v[3] = pack_h(u4.x, u4.y);
        const hm m4 = mk_hm(a4), m8 = mk_hm(a8), m12 = mk_hm(a12);
#pragma unroll
        for (int i = 0; i < 4; i++) { v[4 + i] = hcmul(v[i], m4); v[8 + i] = hcmul(v[i], m8); v[12 + i] = hcmul(v[i], m12); }
        const hm m256 = mk_hm(a256);
        __syncwarp();
#pragma unroll
        for (int i = 0; i < 4; i++) st(4 * i, v[4 * i], v[4 * i + 1], v[4 * i + 2], v[4 * i + 3]);
        st(16, hcmul(v[1], m256), hcmul(v[3], m256), hcmul(v[5], m256), hcmul(v[7], m256));
        st(20, hcmul(v[9], m256), hcmul(v[11], m256), hcmul(v[13], m256), hcmul(v[15], m256));
        __syncwarp();
        tile(0, 0); tile(1, 8); tile(2, 16);
        const cf a512 = csq(a256), a768 = cmul(a512, a256), a1024 = csq(a512);
        const cf a1280 = cmul(a1024, a256), a1536 = csq(a768), a1792 = cmul(a1024, a768);
        const hm m512 = mk_hm(a512), m768 = mk_hm(a768);
        const hm n0 = mk_hm(a1024), n1 = mk_hm(a1280), n2 = mk_hm(a1536), n3 = mk_hm(a1792);
        __syncwarp();
        st(0, hcmul(v[3], m512), hcmul(v[7], m512), hcmul(v[11], m512), hcmul(v[15], m512));
        st(4, hcmul(v[3], m768), hcmul(v[7], m768), hcmul(v[11], m768), hcmul(v[15], m768));
        st(8, hcmul(v[7], n0), hcmul(v[15], n0), hcmul(v[7], n1), hcmul(v[15], n1));
        st(12, hcmul(v[7], n2), hcmul(v[15], n2), hcmul(v[7], n3), hcmul(v[15], n3));
        __syncwarp();
        tile(3, 0); tile(4, 8);
    }
    __syncwarp();
#pragma unroll
    for (int i = 0; i < 5; i++) sts128(os + i * 512 + lane * 16, __float_as_uint(d[i][0]), __float_as_uint(d[i][1]), __float_as_uint(d[i][2]), __float_as_uint(d[i][3]));
    sts64(os + 2560, eb, __float_as_uint(k0));
}

__device__ __forceinline__ void ktables(uint32_t os, int ostep, int np, uint32_t kr, uint32_t kt, uint32_t kinf, int part) {
    const int lane = threadIdx.x & 31, g = lane >> 2, t = lane & 3;
    uint32_t eb = 0;
    float k0 = 0.f, f[4];
#pragma unroll
    for (int q = 0; q < 4; q++) {
        uint2 v = make_uint2(0u, 0u);
        if (q < np) v = lds64(os + q * ostep + 2560);
        eb = max(eb, v.x);
        k0 += __uint_as_float(v.y);
        f[q] = __uint_as_float(v.x);
    }
    const float rs = __uint_as_float(0x7F000000u - eb);
#pragma unroll
    for (int q = 0; q < 4; q++) f[q] *= rs;
#pragma unroll 1
    for (int i = (part & 1) ? 0 : 2; i < ((part & 2) ? 5 : 3); i++) {
        float a0 = 0.f, a1 = 0.f, a2 = 0.f, a3 = 0.f;
        uint4 v[4];
#pragma unroll
        for (int q = 0; q < 4; q++) {
            v[q] = make_uint4(0u, 0u, 0u, 0u);
            if (q < np) v[q] = lds128(os + q * ostep + i * 512 + lane * 16);
        }
#pragma unroll
        for (int q = 0; q < 4; q++) { a0 += __uint_as_float(v[q].x) * f[q]; a1 += __uint_as_float(v[q].y) * f[q]; a2 += __uint_as_float(v[q].z) * f[q]; a3 += __uint_as_float(v[q].w) * f[q]; }
        const int sg = 32 >> max(i - 1, 0);
        const uint32_t o = kr + 4 + (i < 2 ? 16 * i : 256 * i) + sg * g + (i < 3 ? 8 : 128) * (t >> 1) + (i < 4 ? 4 : 64) * (t & 1);
        sts32(o, pack_h(a0, a1));
        sts32(o + 8 * sg, pack_h(a2, a3));
    }
    sts32(kr, pack_h(0.f, k0 * rs));
    __syncwarp();
    if (part & 1) {
        uint32_t w0[4], w1[4], a[2], b[2];
#pragma unroll
        for (int r = 0; r < 4; r++) { w0[r] = lds32(kr + 4 * lane + 128 * r); w1[r] = lds32(kr + 4 * lane + 128 * r + 4); }
#pragma unroll
        for (int r = 0; r < 2; r++) { a[r] = lds32(kr + 512 + 4 * lane + 128 * r); b[r] = lds32(kr + 516 + 4 * lane + 128 * r); }
#pragma unroll
        for (int r = 0; r < 4; r++) sts64(kt + 8 * lane + 256 * r + 32, prmt(w0[r], w0[r], 0x1032), prmt(w0[r], w1[r], 0x3254));
        if (lane == 31) b[1] = pack_h(h_lo(b[1]) - h_hi(b[1]), 0.f);
#pragma unroll
        for (int r = 0; r < 2; r++)
            sts128(kt + 4 * 264 + 16 * lane + 512 * r, prmt(a[r], a[r], (r == 0 && lane == 0) ? 0x1032 : 0x3232), prmt(a[r], a[r], 0x3232), prmt(a[r], b[r], 0x3254), prmt(b[r], b[r], 0x1032));
        if (lane < 24) sts32(kt + 4 * (lane < 8 ? lane : 512 + lane), 0u);
    }
    if (part & 2) {
        const uint32_t k512 = lds16(kr + 2 * 385), k1024 = lds16(kr + 2 * 513);
        if (lane == 0) {
            sts128(kinf, eb, __float_as_uint(h_lo(k512)), k1024, 0u);
            sts16(kr + 2 * 512, pack_h(h_lo(lds16(kr + 2 * 512)) - h_lo(k1024), 0.f));
        }
#pragma unroll
        for (int r = 0; r < 3; r++)
            if (r < 2 || lane < 26) sts128(kt + KT_P4 + 16 * lane + 512 * r, 0u, 0u, 0u, 0u);
        __syncwarp();
        uint32_t x0[5], x1[5], y0[5], y1[5];
#pragma unroll
        for (int r = 0; r < 5; r++) {
            const int m = min(126 + lane + 32 * r, 256);
            x0[r] = lds16(kr + 2 * (257 + m)); x1[r] = lds16(kr + 2 * (259 + m)); y0[r] = lds16(kr + 2 * (385 + m)); y1[r] = lds16(kr + 2 * (387 + m));
        }
#pragma unroll
        for (int r = 0; r < 5; r++) {
            const int m = 126 + lane + 32 * r;
            if (m < 128) x0[r] = y0[r] = 0;
            if (m > 253) x1[r] = 0;
            if (m > 254) y1[r] = 0;
            if (m < 256) sts32(kt + KT_P4 + 4 * (((m - 96) & ~3) | ((m & 1) << 1) | ((m >> 1) & 1)), x0[r] | (x1[r] << 16));
            if (m < 257) sts32(kt + KT_P8 + 4 * (m - 96), y0[r] | (y1[r] << 16));
        }
    }
    __syncwarp();
}

__device__ __forceinline__ void mma_hc(float (&d)[4], const float (&c)[4], uint32_t a0, uint32_t a1, uint32_t a2, uint32_t a3, uint32_t b0, uint32_t b1) {
    asm volatile("mma.sync.aligned.m16n8k16.row.col.f32.f16.f16.f32 {%0,%1,%2,%3},{%4,%5,%6,%7},{%8,%9},{%10,%11,%12,%13};"
                 : "=f"(d[0]), "=f"(d[1]), "=f"(d[2]), "=f"(d[3]) : "r"(a0), "r"(a1), "r"(a2), "r"(a3), "r"(b0), "r"(b1), "f"(c[0]), "f"(c[1]), "f"(c[2]), "f"(c[3]));
}
template <int Q0, int Q1>
__device__ __forceinline__ void sweep_steps(float (&w)[5][4], const uint32_t (&R)[66], uint32_t xa, uint32_t (&x)[5], uint32_t z) {
#pragma unroll
    for (int q = Q0; q <= Q1; q++) {
        uint32_t n0, n1;
        ldm2(xa + 16 * (q + 1), n0, n1);
        const uint32_t a2 = x[0] | z, a3 = x[1] | z;
#pragma unroll
        for (int j = 0; j < 4; j++) {
            const int s = 8 * j + 8 - q;
            if (q == 1) mma_hc(w[j], w[j + 1], x[1], x[2], a2, a3, R[2 * s], R[2 * s + 1]);
            else mma_h(w[j], x[1], x[2], a2, a3, R[2 * s], R[2 * s + 1]);
        }
        if (q == 8) {
            const float zero[4] = {0.f, 0.f, 0.f, 0.f};
            mma_hc(w[4], zero, x[1], x[2], a2, a3, R[64], R[65]);
        }
        x[0] = x[2]; x[1] = x[3]; x[2] = x[4]; x[3] = n0; x[4] = n1;
    }
}

__device__ __forceinline__ void box_round(uint32_t xb, uint32_t fa, int rho, int lane) {
    if (rho == 6) {
        const int a = lane >> 3, j = lane & 7;
        sts128(fa + 3328 * (lane >> 4) + 16 * ((lane & 15) < 15 ? (lane & 15) : 207), 0u, 0u, 0u, 0u);
        sts128(fa + FB9E + 1168 * a + 16 * (j < 7 ? j : 71 + (a & 1)), 0u, 0u, 0u, 0u);
        __syncwarp();
    }
    const int c = rho < 6 ? 32 * rho + lane : -1;
    const uint4 pv = lds128(x0_chunk(xb, c - 1)), ow = lds128(x0_chunk(xb, c));
    const uint2 nx = lds64(x0_chunk(xb, c + 1));
    const uint32_t P[9] = {pv.y, pv.z, pv.w, ow.x, ow.y, ow.z, ow.w, nx.x, nx.y};
    uint32_t Q[8], b3[6], b5[4];
#pragma unroll
    for (int k = 0; k < 8; k++) Q[k] = prmt(P[k], P[k + 1], 0x5432);
#pragma unroll
    for (int k = 0; k < 6; k++) b3[k] = hadd(hadd(Q[k], Q[k + 1]), P[k + 1]);
#pragma unroll
    for (int k = 0; k < 4; k++) b5[k] = hadd(b3[k + 2], hadd(P[k + 2], P[k + 4]));
    sts128(fa + FB5 + 240 + 16 * c, b5[0], b5[1], b5[2], b5[3]);
    sts128(fa + FB3 + 240 + 16 * c, b3[0], b3[1], b3[2], b3[3]);
    if (rho < 4 || rho == 6) {
        uint32_t b7[4], b9[4];
#pragma unroll
        for (int k = 0; k < 4; k++) {
            b7[k] = hadd(b5[k], hadd(Q[k + 1], Q[k + 4]));
            b9[k] = hadd(b7[k], hadd(P[k + 1], P[k + 5]));
        }
        const uint32_t ad = fa + ((c & 1) ? FB9O + 120 : FB9E + 112) + 8 * c;
        sts128(ad, b9[0], b9[1], b9[2], b9[3]);
        sts128(ad + (FB7E - FB9E), b7[0], b7[1], b7[2], b7[3]);
    }
}

__global__ void __cluster_dims__(2, 1, 1) __launch_bounds__(NTHREADS, 1) fused_kernel(const Hot p, const __grid_constant__ Maps m) {
    extern __shared__ __align__(1024) char smem[];
    const uint32_t t0 = clk32();
    const int tid = (threadIdx.x + 32 * 0) & (NTHREADS - 1), lane = tid & 31, warp = __shfl_sync(~0u, tid >> 5, 0), bid = blockIdx.x;
    const uint32_t S = smem_u32(smem), z = (uint32_t)p.tn.zero;
    const bool down = bid < NDOWN, rowcta = bid < NMAIN, big = rowcta && !down;
    const int xd = rowcta ? bid : 142 + ((bid - NMAIN) >> 1);
    const int slot = warp < 8 ? (warp & 3) : 4;
    const bool has = warp < 8 ? (rowcta || (slot >> 1) == (bid & 1)) : (big && warp < 12);
    const int ch = slot < 4 ? 4 * xd + slot : 512 + bid - NDOWN;
    KParams kp;
    if (has) kp = kgen_load(p, ch, warp < 8 ? warp >> 2 : (warp >> 1) & 1, lane);
    if (elect()) {
#pragma unroll 1
        for (int i = warp; i < B_COUNT; i += 16) {
            const uint32_t c = i < 16 ? (uint32_t)((big ? 0x1411115555412290ull : 0x1411114444412290ull) >> (4 * i)) & 15 : 1;
            mbar_init(S + i * 8, c ? c : NTHREADS);
        }
        asm volatile("fence.mbarrier_init.release.cluster;" ::: "memory");
    }
    if (rowcta) {
#pragma unroll 1
        for (int i = tid; i < 1224; i += NTHREADS)
            cp16(S + SM_ROWS + 16 * (i + min((i * 911) >> 16, 16)), i < 1152 ? (const uint4*)p.u + bid * 1152 + i : (const uint4*)p.wr + (i - 1152));
    }
    if (tid >= 256 && tid < 336) {
        const int i = tid - 256;
        if (i < 64 || big) sts128(S + (i < 64 ? SM_X0 + (i >> 4) * X0_STRIDE : SM_EX) + ((i & 8) ? X0_ODD : 0) + 16 * (i & 7), 0u, 0u, 0u, 0u);
    }
    if (tid == 447) sts128(S + SM_ONES, 0x3F803F80u, 0x3F803F80u, 0x3F803F80u, 0x3F803F80u);
    __syncthreads();
    if (rowcta) asm volatile("cp.async.mbarrier.arrive.noinc.shared::cta.b64 [%0];" ::"r"(S + B_ROWS * 8) : "memory");
    if (warp == 15 && lane < 4) mbar_expect(S + (lane < 3 ? B_GX + lane : B_RED) * 8, 256);
    asm volatile("barrier.cluster.arrive.relaxed.aligned;" ::: "memory");
    const int g = lane >> 2, t = lane & 3, mi = lane >> 3, j = lane & 7;
    const uint32_t SW = S + (down ? SM_W_DOWN : SM_W_BIG);
    const int pr = bid >> 1, r = bid & 1, nsl = pr >= 54 ? 3 : 2, sl0 = pr < 54 ? 2 * pr : 3 * pr - 54;

    if (warp == 12) {
        if (elect()) {
            const int ng = 6 * nsl, ns = down ? 24 : ng;
            const CUtensorMap* mg = r ? &m.wu : &m.wg;
            pf_tmap(mg);
            if (down) pf_tmap(&m.wd);
            const uint32_t epoch = ld_rlx(&p.s->cnt[16 * 32]) + 1;
            spin_until(t0, p.tn.f_start);
            int done = 0;
#pragma unroll 1
            for (int s = 0; s < ns; s++) {
                if (s == ng) spin_until(t0, p.tn.f_t3);
                #pragma unroll 1
                for (int it = 0; it < SPIN_LIMIT; it++) {
                    const int w = s >= ng ? p.tn.w3 : ((int)(clk32() - t0) < p.tn.f_t2 ? p.tn.w1 : (nsl == 3 ? p.tn.w2b : p.tn.w2));
                    if (s - done < w) break;
                    if (mbar_test(S + (B_W + done) * 8, 0)) done++;
                    else __nanosleep(32);
                }
                const uint32_t bar = S + (B_W + s) * 8;
                uint32_t dst = SW + s * STAGE;
                if (s == 23) { mbar_wait(S + B_EM * 8, 0); fence_async(); dst = S + SM_W_LAST; }
                mbar_expect(bar, STAGE);
                const int u = (s * 43) >> 8;
                if (s < ng) tma2d(dst, mg, 32 * (sl0 + u), 96 * (s - 6 * u), bar);
                else tma2d(dst, &m.wd, 16 * pr, r * 2304 + 192 * (s - 12), bar);
            }
            if (rowcta) {
                mbar_wait(S + B_FD * 8, 0);
                fence_async();
#pragma unroll 1
                for (int q = 0; q < 4; q++) {
                    wait_count(&p.s->cnt[(8 + q) * 32], epoch * (uint32_t)D_);
                    fence_async_g();
                    mbar_expect(S + (B_YIN + q) * 8, 4608);
                    bulk_g2s(S + SM_STG + q * 4608, p.s->y + (32 * q + (bid >> 2)) * 4608 + (bid & 3) * 1152, 4608, S + (B_YIN + q) * 8);
                }
            }
        }
        return;
    }

    uint32_t epoch = 0;
    if (warp >= 8 || !rowcta) epoch = ld_rlx(&p.s->cnt[16 * 32] + (lane & z)) + 1;
    const uint32_t tag = epoch & 1;
    const int hw = warp < 12 ? warp - 8 : warp - 9;

    if (rowcta && warp >= 8 && warp < 15) {
        const uint32_t ad = S + SM_ROWS + (lane & 15) * ROW_STRIDE + 192 * hw + 16 * (lane >> 4);
        uint32_t wd = j ? S + SM_ROWS + 16 * ROW_STRIDE + 192 * hw + 16 * mi : S + SM_ONES;
        const uint32_t wstep = j ? 64 : 0, ones = 0x3F803F80u | z;
        float d1[4] = {0, 0, 0, 0}, d2[4] = {0, 0, 0, 0}, d3[4] = {0, 0, 0, 0}, d4[4] = {0, 0, 0, 0};
        mbar_wait(S + B_ROWS * 8, 0);
#pragma unroll
        for (int kk = 0; kk < 3; kk++) {
            uint32_t w[4];
            ldm4(wd, w[0], w[1], w[2], w[3]);
            wd += wstep;
#pragma unroll
            for (int e = 0; e < 2; e++) {
                uint32_t a0, a1, a2, a3;
                ldm4(ad + 64 * kk + 32 * e, a0, a1, a2, a3);
                mma_bf(d1, a0, a1, a2, a3, w[2 * e], w[2 * e + 1]);
                mma_bf(d2, a0, a1, a2, a3, a0, a2);
                mma_bf(d3, a0, a1, a2, a3, a1, a3);
                mma_bf(d4, ones, ones ^ z, ones + z, ones - z, w[2 * e], w[2 * e + 1]);
            }
        }
        float* part = (float*)(smem + SM_PART + hw * 256) + g * 4;
        if (t == 0) {
            *(float2*)part = make_float2(d1[0], d1[1]);
            *(float2*)(part + 32) = make_float2(d1[2], d1[3]);
            part[3] = d4[1];
            part[35] = d4[1];
        }
        if (t == (g >> 1)) {
            part[2] = (g & 1) ? d2[1] : d2[0];
            part[34] = (g & 1) ? d3[3] : d3[2];
        }
        bar_sync(1, 192);
        if (hw == 0 && lane < 16) {
            float4 s = *(const float4*)(smem + SM_PART + lane * 16);
#pragma unroll
            for (int w = 1; w < 6; w++) {
                const float4 v = *(const float4*)(smem + SM_PART + w * 256 + lane * 16);
                s.x += v.x; s.y += v.y; s.z += v.z; s.w += v.w;
            }
            const float mean = s.x * (1.f / 576.f);
            const float var = fmaxf(s.z * (1.f / 576.f) - mean * mean, 0.f);
            const uint32_t mm = pack_bf(mean, mean);
            const float mu = bf_lo(mm), sd = bf_round(sqrt_ap(bf_round(bf_round(var) + 1e-5f))), ri = rcpf(sd);
            const uint32_t hi = pack_bf(ri, ri);
            const float rl = ri - bf_lo(hi);
            sts16(S + SM_STA + 2 * lane, mm); sts16(S + SM_STA + 32 + 2 * lane, hi); sts16(S + SM_STA + 64 + 2 * lane, pack_bf(rl, rl));
            const uint32_t rb = pack_bf(0.f, (s.y - mu * s.w) * ri);
            const int row = bid * 16 + lane;
            p.s->stat[row] = (mm & 0xFFFFu) | __float_as_uint(sd) | (tag << 31);
            p.s->key[row] = ((rb ^ (((int)rb >> 31) | 0x80000000u)) & 0xFFFF0000u) | (tag << 15) | (2047 - row);
        }
        bar_sync(1, 192);
        if (tid == 256) mbar_arrive(S + B_P1 * 8);
        {
            const uint2 sm = lds64(S + SM_STA + 8 * t), sh = lds64(S + SM_STA + 32 + 8 * t), sl = lds64(S + SM_STA + 64 + 8 * t);
            const uint32_t at = S + SM_ROWS + (4 * (j >> 1) + (j & 1) + 2 * (mi & 1)) * ROW_STRIDE + 32 * hw + 16 * (mi >> 1);
            uint2* dst = (uint2*)p.s->x + (4 * hw + (g >> 2)) * 2048 + bid * 16 + (g & 3) * 4 + t;
            uint32_t r4[6][4];
#pragma unroll
            for (int n = 5; n >= 0; n--) ldm4t(at + 192 * n, r4[n][0], r4[n][1], r4[n][2], r4[n][3]);
#pragma unroll
            for (int n = 5; n >= 0; n--) {
                uint32_t o[4];
#pragma unroll
                for (int e = 0; e < 4; e++) {
                    const uint32_t v = (e & 1) ? norm2(r4[n][e], sm.y, sh.y, sl.y) : norm2(r4[n][e], sm.x, sh.x, sl.x);
                    o[e] = pack_h(bf_lo(v), bf_hi(v));
                }
                dst[n * 49152] = make_uint2((o[0] & ~1u) | tag, o[1]);
                dst[n * 49152 + 4096] = make_uint2((o[2] & ~1u) | tag, o[3]);
            }
        }
        bar_sync(1, 192);
    }

    if (has) {
        asm volatile("" : "+r"(kp.ldt), "+r"(kp.are), "+r"(kp.aim), "+r"(kp.bre), "+r"(kp.bim), "+r"(kp.cre), "+r"(kp.cim));

        const uint32_t scr = warp < 8 ? S + SM_STG + warp * KG_SCR : S + EX_HAND + hw * KG_SCR;
        kgen(kp, scr, warp < 8 ? scr : S + EX_FAR + hw * 2576, warp < 8 ? 0 : warp & 1, warp < 8 ? 2 : (warp & 1) + 1, rowcta ? S + B_P1 * 8 : 0);
        if (warp >= 8) { __syncwarp(); if (lane == 0) mbar_arrive(S + B_TAB * 8); }
    }
    if (warp < 8 || warp == 15) {
        if (warp < 8 ? has : big) {
            if (warp < 8) bar_sync(4 + slot, 64); else mbar_wait(S + B_TAB * 8, 0);
            ktables(warp < 8 ? S + SM_STG + slot * KG_SCR : S + EX_FAR, warp < 8 ? 4 * KG_SCR : 2576, warp < 8 ? 2 : 4, S + SM_XS + slot * KR_STRIDE,
                    S + (warp < 8 ? SM_KT + slot * KT_STRIDE : EX_KT), S + SM_KINF + slot * 16, warp < 8 ? 1 + (warp >> 2) : 3);
        }
        if (lane == 0) { mbar_arrive(S + B_KG * 8); if (warp == 15) mbar_arrive(S + B_TAB1 * 8); }
    }

    if (!rowcta && warp < 8 && !has) {
        const int w4 = (warp >> 2) * 2 + (warp & 1), i = 32 * w4 + lane;
#pragma unroll 1
        for (int pass = 1; pass < 2; pass++) {
        uint4 k[4];
        if (pass) spin_until(t0, p.tn.t_svc - 1500);
#pragma unroll 1
        for (int it = 0; it < SPIN_LIMIT; it++) {
            if (!pass) {
#pragma unroll
                for (int q = 0; q < 4; q++) k[q] = make_uint4(16 * i + 4 * q, 16 * i + 4 * q + 1, 16 * i + 4 * q + 2, 16 * i + 4 * q + 3);
                break;
            }
            uint32_t bad = 0;
#pragma unroll
            for (int q = 0; q < 4; q++) k[q] = ld_rlx4(&p.s->key[4 * i + 512 * q]);
#pragma unroll
            for (int q = 0; q < 4; q++) bad |= tag ? ~(k[q].x & k[q].y & k[q].z & k[q].w) : (k[q].x | k[q].y | k[q].z | k[q].w);
            if (!(bad & 0x8000u)) break;
            __nanosleep(100);
        }
        const uint32_t sc = S + SM_XS + ((bid & 1) ? 0 : 2) * KR_STRIDE;
        auto pk = [](uint32_t v) { return ((v >> 16) << 11) | (v & 2047u); };
        auto gt = [](uint32_t a, uint32_t b) { return (b - a) >> 31; };
        uint32_t mx = 0;
#pragma unroll
        for (int q = 0; q < 4; q++) {
            k[q] = make_uint4(pk(k[q].x), pk(k[q].y), pk(k[q].z), pk(k[q].w));
            mx = max(max(mx, max(k[q].x, k[q].y)), max(k[q].z, k[q].w));
        }
        bar_sync(1, 128);
        sts32(sc + 4 * i, mx);
        if (i == 0) sts32(sc + 1024, 0u);
        bar_sync(1, 128);
        int rank;
        {
            int c[8] = {0, 0, 0, 0, 0, 0, 0, 0};
#pragma unroll 1
            for (int q = 0; q < 32; q += 4) {
                uint4 v[4];
#pragma unroll
                for (int e = 0; e < 4; e++) v[e] = lds128(sc + 16 * (q + e));
#pragma unroll
                for (int e = 0; e < 4; e++) {
                    c[(2 * e) & 7] += gt(v[e].x, mx); c[(2 * e + 1) & 7] += gt(v[e].y, mx);
                    c[(2 * e + 4) & 7] += gt(v[e].z, mx); c[(2 * e + 5) & 7] += gt(v[e].w, mx);
                }
            }
            rank = ((c[0] + c[1]) + (c[2] + c[3])) + ((c[4] + c[5]) + (c[6] + c[7]));
        }
        if (rank == 7) sts32(sc + 1028, mx);
        bar_sync(1, 128);
        if (rank < 8) {
            const uint32_t lb = lds32(sc + 1028);
            int cq[4];
#pragma unroll
            for (int q = 0; q < 4; q++) cq[q] = (gt(lb, k[q].x) + gt(lb, k[q].y)) + (gt(lb, k[q].z) + gt(lb, k[q].w));
            const int c = 16 - ((cq[0] + cq[1]) + (cq[2] + cq[3]));
            uint32_t pos;
            asm volatile("atom.shared.add.u32 %0, [%1], %2;" : "=r"(pos) : "r"(sc + 1024), "r"(c) : "memory");
            pos = sc + 512 + 4 * pos;
#pragma unroll
            for (int q = 0; q < 4; q++) {
                if (k[q].x >= lb) { sts32(pos, k[q].x); pos += 4; }
                if (k[q].y >= lb) { sts32(pos, k[q].y); pos += 4; }
                if (k[q].z >= lb) { sts32(pos, k[q].z); pos += 4; }
                if (k[q].w >= lb) { sts32(pos, k[q].w); pos += 4; }
            }
        }
        bar_sync(1, 128);
        const int n = lds32(sc + 1024);
        if (i < n) {
            const uint32_t mine = lds32(sc + 512 + 4 * i);
            rank = 0;
#pragma unroll 1
            for (int q = 0; q < n; q += 4) {
                const uint4 v = lds128(sc + 512 + 4 * q);
                rank += ((v.x > mine) + (q + 1 < n && v.y > mine)) + ((q + 2 < n && v.z > mine) + (q + 3 < n && v.w > mine));
            }
            const uint32_t k32 = (mine >> 11) << 16, rb = (k32 ^ ((~(int)k32 >> 31) | 0x80000000u)) & 0xFFFF0000u;
            if (rank < 8 && pass) st_rlx(&p.s->sel[bid - NMAIN][rank], (2047 - (mine & 2047)) | (tag << 15) | (pack_bf(rcpf(1.f + ex2f(-1.4426950408889634f * __uint_as_float(rb))), 0.f) << 16));
        }
        }
    }

    if (warp == 13 || warp == 14) {
        const int i = tid - 416;
        if (i == 0) sts32(S + SM_EPOCH, tag);
        if (rowcta) {
            if (p.tn.t_marg <= 600) {
                const uint32_t back = ld_rlx(p.s->x + 2 * ((4 * hw + 2 + (g >> 2)) * 2048 + bid * 16 + (g & 3) * 4 + t));
                if (back == 0xFFFFFFFFu) __nanosleep(20);
            }
            spin_until(clk32(), p.tn.t_marg);
        } else {
            spin_until(t0, p.tn.t_svc);
        }
        const uint4* xa = (const uint4*)p.s->x + xd * 1024 + i;
        const int e = bid - NDOWN;
        const uint4* xe = (const uint4*)p.s->x + (128 + (e >> 2)) * 1024 + (i >> 1) * 8 + (e & 3) * 2 + (i & 1);
        const uint32_t da = S + SM_X0 + ((i >> 1) & 3) * X0_STRIDE + ((i & 1) ? X0_ODD : 0) + 128 + 16 * (i >> 3);
        const uint32_t de = S + SM_EX + ((i & 1) ? X0_ODD : 0) + 128 + 16 * (i >> 1);
        uint4 v[2][10];
        auto fetch = [&](int half) {
#pragma unroll
            for (int k = 0; k < 10; k++) {
                v[half][k].x = v[half][k].z = tag;
                if (k < 8 || big) v[half][k] = ld_rlx4(k < 8 ? xa + 512 * half + 64 * k : xe + 512 * half + 256 * (k - 8));
            }
        };
        fetch(0); fetch(1);
#pragma unroll
        for (int half = 0; half < 2; half++) {
#pragma unroll 1
            for (int it = 0; it < SPIN_LIMIT; it++) {
                uint32_t bad = 0;
#pragma unroll
                for (int k = 0; k < 10; k++) bad |= (v[half][k].x ^ tag) | (v[half][k].z ^ tag);
                if (!(bad & 1)) break;
                __nanosleep(60);
                fetch(half);
            }
#pragma unroll
            for (int k = 0; k < 10; k++)
                if (k < 8 || big) sts128(k < 8 ? da + 1024 * half + 128 * k : de + 1024 * half + 512 * (k - 8), v[half][k].x & ~1u, v[half][k].y, v[half][k].z & ~1u, v[half][k].w);
            __syncwarp();
            if (lane == 0) mbar_arrive(S + (B_X0 + half) * 8);
        }
    }

    if (warp < 12) {
        const bool cw = warp >= 8;
        if (has) {
            const uint32_t xb = S + (cw ? SM_EX : SM_X0 + slot * X0_STRIDE), kt = S + (cw ? EX_KT : SM_KT + slot * KT_STRIDE);
            const int g0 = cw ? warp - 8 : 0, g1 = cw ? warp - 7 : 4;
            const uint32_t park = (cw ? S + EX_HAND + g0 * 2048 : kt) + lane * 16;
            if (cw) mbar_wait(S + B_TAB1 * 8, 0);
            const uint4 ki = lds128(S + SM_KINF + slot * 16);
            const float inv = __uint_as_float(ki.x);
            if (warp >= 4) {
                const uint32_t fa = S + (cw ? EX_FAR : SM_FAR + slot * FAR_STRIDE);
                mbar_wait(S + (cw ? B_X1 : B_X0) * 8, 0);
                mbar_wait(S + B_KG * 8, 0);
#pragma unroll 1
                for (int rho = cw ? g0 : 0; rho < (cw ? 7 : 4); rho += cw ? 4 : 1) box_round(xb, fa, (!cw && rho == 3) ? 6 : rho, lane);
                if (cw) bar_sync(2, 128); else __syncwarp();
                const int dd = g - 2 * t, gf = g0 ? g0 : 1;
                const uint32_t tb0 = dd == -5 ? ki.z : (dd == -4 ? ki.z << 16 : 0u), tb1 = dd == 3 ? ki.z : (dd == 4 ? ki.z << 16 : 0u);
                uint32_t tad = xb + (mi == 1 ? 144 : mi == 2 ? 128 : X0_ODD + 128) + 16 * j + 512 * gf - 1024;
                uint32_t ad8 = fa + (mi == 0 ? FB9E : mi == 1 ? FB7O : mi == 2 ? FB9O + 16 : FB7E) + 112 - 16 * j + 512 * gf - 768;
                uint32_t ad4 = fa + ((mi & 1) ? FB3 : FB5) + 240 + 16 * (8 * (mi >> 1) - j) + 1024 * gf - 640;
                const uint32_t p4 = kt + KT_P4 + 16 * (g + t), p8 = kt + KT_P8 + 8 * (g + 2 * t);
#pragma unroll 1
                for (int grp = gf; grp < g1; grp++) {
                    float a[4][4], e[2][4], o[2][4];
#pragma unroll
                    for (int k = 0; k < 4; k++) a[0][k] = a[1][k] = a[2][k] = a[3][k] = e[0][k] = e[1][k] = o[0][k] = o[1][k] = 0.f;
                    {
                        if (!cw && grp == 2) {
                            mbar_wait(S + B_X1 * 8, 0);
#pragma unroll 1
                            for (int rho = 3; rho < 6; rho++) box_round(xb, fa, rho, lane);
                            __syncwarp();
                        }
                        {
                            uint4 A4[10];
#pragma unroll
                            for (int s = 0; s < 10; s++) A4[s] = lds128(p4 + 64 * s);
                            auto s4 = [&](int m) {
                                uint32_t b[4];
                                ldm4t(ad4 - 256 * m, b[0], b[1], b[2], b[3]);
#pragma unroll
                                for (int h = 1; h >= 0; h--)
#pragma unroll
                                    for (int i = 0; i < 4; i++) {
                                        const int s = 2 * m - 2 + 2 * i + (1 - h), k = m + (i & 2);
                                        if (k <= 5 && k >= ((i & 1) ? 0 : 1) && !((i & 1) && k == 5)) mma_h(a[i], A4[s >= 0 && s < 10 ? s : 0].x, A4[s >= 0 && s < 10 ? s : 0].y, A4[s >= 0 && s < 10 ? s : 0].z, A4[s >= 0 && s < 10 ? s : 0].w, b[2 * h], b[2 * h + 1]);
                                    }
                            };
                            auto tap = [&](int i) {
                                uint32_t b[4];
                                ldm4(tad + 128 * i, b[0], b[1], b[2], b[3]);
                                mma_h(a[i], b[0], b[1], b[2], b[3], tb1, tb0);
                            };
                            s4(1); s4(0); s4(2); s4(-1); tap(3); s4(-2);
                            if (grp >= 2) { s4(3); tap(0); s4(4); tap(1); s4(5); tap(2); }
                        }
                        {
                            uint32_t A8[9][4];
#pragma unroll
                            for (int k = 0; k < 9; k++) { A8[k][0] = lds32(p8 + 64 * k); A8[k][1] = lds32(p8 + 64 * k + 64); A8[k][2] = lds32(p8 + 64 * k + 4); A8[k][3] = lds32(p8 + 64 * k + 68); }
                            auto s8 = [&](int m) {
                                uint32_t b[4];
                                ldm4t(ad8 - 128 * m, b[0], b[1], b[2], b[3]);
                                mma_h(e[1], A8[m + 2][0], A8[m + 2][1], A8[m + 2][2], A8[m + 2][3], b[0], b[1]);
                                mma_h(o[1], A8[m + 2][0], A8[m + 2][1], A8[m + 2][2], A8[m + 2][3], b[2], b[3]);
                                if (m >= 0) {
                                    mma_h(e[0], A8[m >= 0 ? m : 0][0], A8[m >= 0 ? m : 0][1], A8[m >= 0 ? m : 0][2], A8[m >= 0 ? m : 0][3], b[0], b[1]);
                                    mma_h(o[0], A8[m >= 0 ? m : 0][0], A8[m >= 0 ? m : 0][1], A8[m >= 0 ? m : 0][2], A8[m >= 0 ? m : 0][3], b[2], b[3]);
                                }
                            };
                            s8(-2);
                            if (grp >= 2) {
                                s8(-1); s8(0); s8(1); s8(2);
                                if (grp >= 3) { s8(3); s8(4); s8(5); s8(6); }
                            }
                        }
                    }
                    tad += 512; ad8 += 512; ad4 += 1024;
#pragma unroll
                    for (int pp = 0; pp < 2; pp++) {
                        if (!cw) {
#pragma unroll 1
                            for (int it = 0; it < SPIN_LIMIT && !__all_sync(~0u, lds32v(park + (2 * pp + 1) * 512) == SLOT_FREE); it++) __nanosleep(32);
                        }
#pragma unroll
                        for (int i = 0; i < 2; i++)
                            sts128(park + (2 * pp + i) * 512, __float_as_uint((a[2 * pp + i][0] + e[pp][2 * i]) * inv), __float_as_uint((a[2 * pp + i][1] + e[pp][2 * i + 1]) * inv),
                                   __float_as_uint((a[2 * pp + i][2] + o[pp][2 * i]) * inv), __float_as_uint((a[2 * pp + i][3] + o[pp][2 * i + 1]) * inv));
                    }
                }
            }
            if ((warp & 12) != 4) {
                uint32_t R[66], x[5];
#pragma unroll
                for (int i = 0; i < 66; i++) R[i] = lds32(kt + 4 * (8 + g - 2 * t) + 32 * i);
                float w[5][4];
#pragma unroll
                for (int i = 0; i < 5; i++) w[i][0] = w[i][1] = w[i][2] = w[i][3] = 0.f;
                uint32_t xa = xb + ((lane & 8) ? X0_ODD + 16 : 16) + 16 * j + 512 * g0;
                uint2* yo = (uint2*)p.s->y + (32 * g0 + g) * 2304 + ch * 4 + t;
                mbar_wait(S + B_X0 * 8, 0);
                const uint32_t ytag = lds32(S + SM_EPOCH);
                if (g0 == 0) {
                    const uint32_t x01 = lds32(xb + 128);
                    const float c0 = lane == 31 ? __uint_as_float(ki.y) * inv * h_lo(x01) : 0.f, c1 = lane == 31 ? c0 + __uint_as_float(ki.y) * inv * h_hi(x01) : 0.f;
                    __syncwarp();
#pragma unroll
                    for (int i = 0; i < 4; i++) sts128(park + i * 512, 0u, 0u, i == 3 ? __float_as_uint(c0) : 0u, i == 3 ? __float_as_uint(c1) : 0u);
                }
                ldm2(xa - 16, x[1], x[0]);
                ldm2(xa, x[1], x[2]);
                ldm2(xa + 16, x[3], x[4]);
                uint32_t zz = z, pk = park;
                float sc = inv;
                const bool direct = g0 == 0;
                uint32_t dir = direct;
                asm volatile("" : "+r"(pk));
#pragma unroll 1
                for (int gq = g0; gq < g1; gq++) {
                    uint32_t pa = pk;
#pragma unroll 1
                    for (int n = 4; n > 0; n--) {
                        asm volatile("" : "+r"(zz), "+f"(sc), "+r"(pa), "+r"(dir));
                        sweep_steps<1, 5>(w, R, xa, x, zz);
                        uint4 v = lds128v(pa | (x[4] & zz));
                        sweep_steps<6, 8>(w, R, xa, x, zz);
                        xa += 128;
                        if (__any_sync(~0u, v.x == SLOT_FREE)) {
#pragma unroll 1
                            for (int it = 0; it < SPIN_LIMIT; it++) {
                                v = lds128v(pa);
                                if (!__any_sync(~0u, v.x == SLOT_FREE)) break;
                            }
                        }
                        const float y0 = fmaf(w[0][0], sc, __uint_as_float(v.x)), y1 = fmaf(w[0][1], sc, __uint_as_float(v.y));
                        const float y2 = fmaf(w[0][2], sc, __uint_as_float(v.z)), y3 = fmaf(w[0][3], sc, __uint_as_float(v.w));
                        if (dir) {
                            *yo = make_uint2((pack_bf(y0, y1) & ~1u) | ytag, pack_bf(y2, y3));
                            sts32(pa, SLOT_FREE);
                        } else {
                            sts128(pa, __float_as_uint(y0), __float_as_uint(y1), __float_as_uint(y2), __float_as_uint(y3));
                        }
                        yo += 18432;
                        pa += 512;
                    }
                    if (direct && lane == 0) red_add(&p.s->cnt[(8 + gq) * 32]);
                }
                __syncwarp();
                if (lane == 0) mbar_arrive(S + (direct ? B_EM : B_SP + g0) * 8);
                if (cw && g0 < 3) {
                    mbar_wait(S + (B_SP + g0 + 1) * 8, 0);
#pragma unroll
                    for (int i = 0; i < 4; i++) {
                        const uint4 v = lds128(park + 2048 + i * 512);
                        yo[i * 18432] = make_uint2((pack_bf(fmaf(w[i + 1][0], inv, __uint_as_float(v.x)), fmaf(w[i + 1][1], inv, __uint_as_float(v.y))) & ~1u) | ytag,
                                                   pack_bf(fmaf(w[i + 1][2], inv, __uint_as_float(v.z)), fmaf(w[i + 1][3], inv, __uint_as_float(v.w))));
                    }
                    if (lane == 0) red_add(&p.s->cnt[(8 + g0 + 1) * 32]);
                }
            }
        }
        if (rowcta && (warp & 12) == 4) {
            bar_sync(10, 128);
            const int i = tid - 128, rb0 = 16 * (bid >> 2), c0 = 144 * (bid & 3);
            if (i == 0) mbar_arrive(S + B_FD * 8);
#pragma unroll 3
            for (int v = i; v < 1152; v += 128) {
                const int row = (v * 3641) >> 16, vv = v - 18 * row;
                cp16(S + SM_ROWS + row * 304 + 16 * vv, (const uint4*)(p.u + (size_t)(512 * (row >> 4) + rb0 + (row & 15)) * D_ + c0) + vv);
            }
            if (i < 64) {
                const uint32_t sw = ld_stat(&p.s->stat[512 * (i >> 4) + rb0 + (i & 15)], lds32(S + SM_EPOCH));
                const float ri = rcpf(bf_hi(sw));
                const uint32_t hi = pack_bf(ri, ri);
                const float rl = ri - bf_lo(hi);
                sts128(S + SM_KT + KT_P4 + 16 * i, prmt(sw, sw, 0x1010), hi, pack_bf(rl, rl), 0u);
            }
            asm volatile("cp.async.wait_all;" ::: "memory");
            __syncwarp();
            if (lane == 0) mbar_arrive(S + B_OUT * 8);
        }
        if (!rowcta) return;

        const int rb0 = 16 * (bid >> 2), c0 = 144 * (bid & 3);
        mbar_wait(S + B_OUT * 8, 0);
        mbar_wait(S + B_XS * 8, 0);
        const uint32_t otag = lds32(S + SM_EPOCH) * 0x00010001u;
        const uint2 skip = lds64(S + SM_SKIP);
        const int pi_g = (g & 1) + 8 * ((g >> 1) & 1) + 2 * (g >> 2), pi_j = (j & 1) + 8 * ((j >> 1) & 1) + 2 * (j >> 2);
#pragma unroll 1
        for (int un = warp; un < 36; un += 12) {
            const int q = (un * 57) >> 9, cu = un - 9 * q;
            const uint32_t rw = S + SM_ROWS + 16 * q * 304 + 32 * cu;
            const uint32_t ad = rw + (pi_j + 4 * (mi & 1)) * 304 + 16 * (mi >> 1);
            const uint32_t dk0 = __ldg((const uint32_t*)p.dskip + (c0 >> 1) + 8 * cu + t), dk1 = __ldg((const uint32_t*)p.dskip + (c0 >> 1) + 8 * cu + 4 + t);
            const uint4 sa = lds128(S + SM_KT + KT_P4 + 16 * (16 * q + pi_g)), sb = lds128(S + SM_KT + KT_P4 + 16 * (16 * q + 4 + pi_g));
            uint32_t x[4], tt[4], gt[4], y[4];
            ldm4(ad, x[0], x[1], x[2], x[3]);
#pragma unroll
            for (int e = 0; e < 4; e++) {
                const uint4 s = (e & 1) ? sb : sa;
                const uint32_t xn = norm2(x[e], s.x, s.y, s.z);
                tt[e] = bmul(xn, e < 2 ? dk0 : dk1);
                gt[e] = pack_bf(silu_f(bf_lo(xn)), silu_f(bf_hi(xn)));
            }
            mbar_wait(S + (B_YIN + q) * 8, 0);
            const uint32_t yb = S + SM_STG + q * 4608 + 512 * cu;
#pragma unroll 1
            for (int it = 0; it < SPIN_LIMIT; it++) {
                ldm4t(yb + (8 * (mi >> 1) + j) * 32 + 16 * (mi & 1), y[0], y[1], y[2], y[3]);
                const uint32_t bad = ((y[0] ^ otag) | (y[1] ^ otag) | (y[2] ^ otag) | (y[3] ^ otag)) & 0x00010001u;
                if (!__any_sync(~0u, (g & 3) == 0 && bad)) break;
                const uint4 v = ld_rlx4((const uint4*)(p.s->y + (32 * q + (bid >> 2)) * 4608 + (bid & 3) * 1152 + 128 * cu) + lane);
                __syncwarp();
                sts128(yb + 16 * lane, v.x, v.y, v.z, v.w);
                __syncwarp();
            }
#pragma unroll
            for (int e = 0; e < 4; e++) y[e] = badd(x[e], bmul(badd(y[e], tt[e]), gt[e]));
            stm4(ad, y[0], y[1], y[2], y[3]);
            __syncwarp();
            const int row = lane >> 1;
            const uint4 o = lds128(rw + row * 304 + 16 * (lane & 1));
            if (!((((q & 2) ? skip.y : skip.x) >> (16 * (q & 1) + row)) & 1))
                *((uint4*)(p.out + (size_t)(512 * q + rb0 + row) * D_ + c0 + 16 * cu) + (lane & 1)) = o;
        }
        return;
    }

    {
        const int fw = warp - 13;
        if (fw < nsl) {
            st_rlx(&p.s->h[tag ^ 1][(32 * (sl0 + fw) + 16 * r) * 4 + lane], 0u);
            st_rlx(&p.s->h[tag ^ 1][(32 * (sl0 + fw) + 16 * r) * 4 + 32 + lane], 0u);
        }
        if (fw == 2) {
            spin_until(t0, p.tn.t_xs);
            uint32_t sv = 0;
#pragma unroll 1
            for (int it = 0; it < SPIN_LIMIT; it++) {
                sv = ld_rlx(&p.s->sel[bid & 3][j]);
                if (__all_sync(~0u, ((sv >> 15) & 1) == tag)) break;
                __nanosleep(40);
            }
            mbar_wait(S + B_KG * 8, 0);
            if (lane == 0) { fence_async(); mbar_expect(S + B_BOX * 8, 8 * 1152); }
            __syncwarp();
            if (lane < 8) bulk_g2s(S + SM_XS + lane * ROW_STRIDE, p.u + (size_t)(sv & 2047) * D_, 1152, S + B_BOX * 8);
            const uint32_t st = ld_stat(&p.s->stat[sv & 2047], tag);
            const float ri = rcpf(bf_hi(st));
            const uint32_t hi = pack_bf(ri, ri);
            const float rl = ri - bf_lo(hi);
            if (lane == 0) sts64(S + SM_SKIP, 0u, 0u);
            __syncwarp();
            if (lane < 8) {
                const int row = sv & 2047;
                if (((row >> 4) & 31) == (bid >> 2)) asm volatile("red.shared.or.b32 [%0], %1;" ::"r"(S + SM_SKIP + 4 * (row >> 10)), "r"(1u << (16 * ((row >> 9) & 1) + (row & 15))) : "memory");
                sts32(S + SM_XS + 8 * ROW_STRIDE + 4 * lane, sv);
                sts128(S + SM_RP + 16 * lane, prmt(st, st, 0x1010), hi, pack_bf(rl, rl), 0u);
            }
        }
        asm volatile("barrier.cluster.wait.aligned;" ::: "memory");
        bar_sync(9, 96);
        mbar_wait(S + B_BOX * 8, 0);
#pragma unroll
        for (int k = 0; k < 6; k++) {
            const int v = tid - 416 + 96 * k, tk = (v * 911) >> 16;
            const uint4 x = lds128(S + SM_XS + 16 * (v + tk)), st = lds128(S + SM_RP + 16 * tk);
            sts128(S + SM_XS + 16 * (v + tk), norm2(x.x, st.x, st.y, st.z), norm2(x.y, st.x, st.y, st.z), norm2(x.z, st.x, st.y, st.z), norm2(x.w, st.x, st.y, st.z));
        }
        bar_sync(9, 96);
        if (tid == 416) mbar_arrive(S + B_XS * 8);
        const uint32_t ob = mapa(S, r ^ 1);
        if (fw == 2) {
            if (elect()) {
#pragma unroll 1
                for (int st = 0; st < (down ? 24 : 6 * nsl); st++) {
                    if (st == 12 && down) break;
                    mbar_wait(S + (B_W + st) * 8, 0);
                    if (st % 3 == 2) mbar_arrive(S + (B_GU + st / 3) * 8);
                }
            }
            __syncwarp();
        }
        if (fw < 2) {
            const uint32_t bad = S + SM_XS + j * ROW_STRIDE + mi * 16;
            uint32_t aad = (SW + (8 * (mi >> 1) + j) * 64 + 16 * ((mi & 1) ^ (j >> 1))) ^ ((r ^ fw) * 32);
            uint32_t b[18][4];
#pragma unroll
            for (int k = 0; k < 18; k++) ldm4(bad + 64 * k, b[k][0], b[k][1], b[k][2], b[k][3]);
#pragma unroll 1
            for (int u = 0; u < nsl; u++) {
                float d[4][4];
#pragma unroll
                for (int i = 0; i < 4; i++) d[i][0] = d[i][1] = d[i][2] = d[i][3] = 0.f;
#pragma unroll
                for (int hf = 0; hf < 2; hf++) {
                    mbar_wait(S + (B_GU + 2 * u + hf) * 8, 0);
#pragma unroll
                    for (int sub = 0; sub < 3; sub++) {
                        uint32_t a[6][4];
#pragma unroll
                        for (int k = 0; k < 6; k++) ldm4t(aad + 1024 * k, a[k][0], a[k][1], a[k][2], a[k][3]);
#pragma unroll
                        for (int k = 0; k < 6; k++) {
                            const int kb = 9 * hf + 3 * sub + (k >> 1);
                            mma_bf(d[k & 3], a[k][0], a[k][1], a[k][2], a[k][3], b[kb][2 * (k & 1)], b[kb][2 * (k & 1) + 1]);
                        }
                        aad += STAGE;
                    }
                }
                const uint32_t k0 = pack_bf((d[0][0] + d[1][0]) + (d[2][0] + d[3][0]), (d[0][1] + d[1][1]) + (d[2][1] + d[3][1]));
                const uint32_t k1 = pack_bf((d[0][2] + d[1][2]) + (d[2][2] + d[3][2]), (d[0][3] + d[1][3]) + (d[2][3] + d[3][3]));
                if (fw == 1) {
                    asm volatile("st.async.shared::cluster.mbarrier::complete_tx::bytes.v2.b32 [%0], {%1, %2}, [%3];" ::"r"(ob + SM_PART + u * 256 + lane * 8), "r"(k0), "r"(k1), "r"(ob + (B_GX + u) * 8) : "memory");
                } else {
                    mbar_wait(S + (B_GX + u) * 8, 0);
                    const uint2 o = lds64(S + SM_PART + u * 256 + lane * 8);
#pragma unroll
                    for (int i = 0; i < 2; i++) {
                        const uint32_t mine = i ? k1 : k0, other = i ? o.y : o.x, gb = r ? other : mine, ub = r ? mine : other;
                        uint32_t hv = bmul(pack_bf(silu_f(bf_lo(gb)), silu_f(bf_hi(gb))), ub);
                        if ((hv & 0xFFFFu) == 0) hv |= 0x8000u;
                        if ((hv >> 16) == 0) hv |= 0x80000000u;
                        st_rlx(&p.s->h[tag][(32 * (sl0 + u) + 16 * r) * 4 + 32 * i + lane], hv);
                    }
                    __syncwarp();
                    if (lane < 8) red_add(&p.s->cnt[lane * 32]);
                }
            }
        }
        if (!down) return;

        const int fi = 32 * fw + lane, tok = 4 * r + ((fi >> 4) & 3), cc = 16 * pr + (fi & 15);
        const uint32_t sel = lds32(S + SM_XS + 8 * ROW_STRIDE + 4 * tok);
        const int row = sel & 2047;
        const uint32_t* ya = p.s->y + (row >> 4) * 4608 + cc * 8 + (row & 6);
        const float xraw = __bfloat162float(p.u[(size_t)row * D_ + cc]), dsk = __bfloat162float(p.dskip[cc]);
        const float xn = bf_lo(lds16(S + SM_XS + tok * ROW_STRIDE + 2 * cc));
        if (fw == 0) {
#pragma unroll 1
            for (int st = 12; st < 24; st++) mbar_wait(S + (B_W + st) * 8, 0);
        }
        if (fw == 2 && elect()) wait_count(&p.s->cnt[(bid & 7) * 32], epoch * 288u);
        bar_sync(9, 96);
        float dn[4][4];
        uint2 yv2 = make_uint2(tag ^ 1, 0u);
#pragma unroll 1
        for (int ph = 0; ph < 64; ph++) {
            if (fw == 2 && elect()) {
                fence_async();
                fence_async_g();
                mbar_expect(S + B_H * 8, 36864);
                bulk_g2s(SW, (const char*)p.s->h[tag] + r * 36864, 36864, S + B_H * 8);
            }
            asm volatile("ld.relaxed.gpu.global.v2.u32 {%0,%1}, [%2];" : "=r"(yv2.x), "=r"(yv2.y) : "l"(ya) : "memory");
            mbar_wait(S + B_H * 8, ph & 1);
#pragma unroll
            for (int i = 0; i < 4; i++) dn[i][0] = dn[i][1] = dn[i][2] = dn[i][3] = 0.f;
            uint32_t bq[4] = {~0u, ~0u, ~0u, ~0u};
            const int fr = j + 8 * (mi >> 1);
            uint32_t wa = SW + 12 * STAGE + fw * 2048 + fr * 32 + (((mi & 1) ^ ((fr >> 2) & 1)) << 4), ha = SW + fw * 1024 + lane * 16;
#pragma unroll 1
            for (int s0 = 0; s0 < 12; s0 += 3) {
                uint32_t a[6][8], b[6][4];
#pragma unroll
                for (int s = 0; s < 3; s++) {
                    if (s == 2 && s0 == 9) wa += S + SM_W_LAST - (SW + 23 * STAGE);
#pragma unroll
                    for (int e = 0; e < 2; e++) {
                        ldm4t(ha + e * 512, b[2 * s + e][0], b[2 * s + e][1], b[2 * s + e][2], b[2 * s + e][3]);
                        ldm4t(wa + e * 1024, a[2 * s + e][0], a[2 * s + e][1], a[2 * s + e][2], a[2 * s + e][3]);
                        ldm4t(wa + e * 1024 + 512, a[2 * s + e][4], a[2 * s + e][5], a[2 * s + e][6], a[2 * s + e][7]);
                    }
                    wa += STAGE; ha += 3072;
                }
#pragma unroll
                for (int k = 0; k < 6; k++) {
                    mma_bf(dn[2 * (k & 1)], a[k][0], a[k][1], a[k][2], a[k][3], b[k][0], b[k][1]);
                    mma_bf(dn[2 * (k & 1) + 1], a[k][4], a[k][5], a[k][6], a[k][7], b[k][2], b[k][3]);
#pragma unroll
                    for (int q = 0; q < 4; q++) bq[q] = __vminu2(bq[q], b[k][q]);
                }
            }
            const uint32_t bm = __vminu2(__vminu2(bq[0], bq[1]), __vminu2(bq[2], bq[3])), bd = (bm - 0x00010001u) & ~bm;
            uint32_t anybad;
            asm volatile("{.reg .pred p, q; setp.ne.u32 p, %1, 0; bar.red.or.pred q, 9, 96, p; selp.u32 %0, 1, 0, q;}" : "=r"(anybad) : "r"(bd & 0x80008000u) : "memory");
            if (!anybad) break;
        }
        float* red = (float*)(smem + SM_RED + fw * 512);
        red[(2 * t) * 16 + g] = (dn[0][0] + dn[1][0]) + (dn[2][0] + dn[3][0]);
        red[(2 * t + 1) * 16 + g] = (dn[0][1] + dn[1][1]) + (dn[2][1] + dn[3][1]);
        red[(2 * t) * 16 + g + 8] = (dn[0][2] + dn[1][2]) + (dn[2][2] + dn[3][2]);
        red[(2 * t + 1) * 16 + g + 8] = (dn[0][3] + dn[1][3]) + (dn[2][3] + dn[3][3]);
        bar_sync(9, 96);
        if (fw < 2) {
            const float* rs = (const float*)(smem + SM_RED);
            const int mine = 64 * r + fi, other = mine ^ 64;
            st_async32(ob + SM_RP + 4 * fi, __float_as_uint(rs[other] + rs[128 + other] + rs[256 + other]), ob + B_RED * 8);
            const float s = rs[mine] + rs[128 + mine] + rs[256 + mine];
#pragma unroll 1
            for (int it = 0; it < SPIN_LIMIT && (yv2.x & 1) != tag; it++)
                asm volatile("ld.relaxed.gpu.global.v2.u32 {%0,%1}, [%2];" : "=r"(yv2.x), "=r"(yv2.y) : "l"(ya) : "memory");
            const uint32_t yw = (row & 8) ? yv2.y : yv2.x;
            const float sg = bf_round(((row & 1) ? bf_hi(yw) : bf_lo(yw)) + bf_round(xn * dsk));
            mbar_wait(S + B_RED * 8, 0);
            const float o = *(const float*)(smem + SM_RP + 4 * fi);
            const float yv = bf_round(bf_round(r == 0 ? s + o : o + s) * bf_hi(sel));
            p.out[(size_t)row * D_ + cc] = __float2bfloat16(xraw + bf_round(sg * bf_round(silu_f(bf_round(xn + yv)))));
            if (bid == 0 && fi == 0) st_rlx(&p.s->cnt[16 * 32], epoch);
        }
    }
}

typedef CUresult (*EncodeFn)(CUtensorMap*, CUtensorMapDataType, cuuint32_t, void*, const cuuint64_t*, const cuuint64_t*, const cuuint32_t*,
                             const cuuint32_t*, CUtensorMapInterleave, CUtensorMapSwizzle, CUtensorMapL2promotion, CUtensorMapFloatOOBfill);

static void make2d(EncodeFn enc, CUtensorMap* m, const void* base, uint64_t cols, uint64_t rows, uint32_t bc, uint32_t br, CUtensorMapSwizzle sw) {
    cuuint64_t gd[2] = {cols, rows};
    cuuint64_t gs[1] = {cols * 2};
    cuuint32_t bd[2] = {bc, br}, es[2] = {1, 1};
    enc(m, CU_TENSOR_MAP_DATA_TYPE_BFLOAT16, 2, const_cast<void*>(base), gd, gs, bd, es, CU_TENSOR_MAP_INTERLEAVE_NONE, sw,
        CU_TENSOR_MAP_L2_PROMOTION_L2_128B, CU_TENSOR_MAP_FLOAT_OOB_FILL_NONE);
}

static Tune g_tune = {2000, 9000, 3, 5, 8, 5000, 7500, 0, 9000, 1, 0, 0};


static void launch(void* const* d_in, void* d_out) {
    static EncodeFn enc = nullptr;
    static Scratch* gs = nullptr;
    if (!enc) {
        void* fn = nullptr;
        cudaDriverEntryPointQueryResult qr;
        cudaGetDriverEntryPoint("cuTensorMapEncodeTiled", &fn, cudaEnableDefault, &qr);
        enc = (EncodeFn)fn;
        cudaFuncSetAttribute(fused_kernel, cudaFuncAttributeMaxDynamicSharedMemorySize, SM_TOTAL);
        cudaGetSymbolAddress((void**)&gs, g_s);
    }
    Hot p;
    Maps m;
    auto in = [&](int i) { return (const __nv_bfloat16*)d_in[i]; };
    p.u = in(0); p.are = in(1); p.aim = in(2); p.bre = in(3); p.bim = in(4); p.cre = in(5); p.cim = in(6);
    p.logdt = in(7); p.dskip = in(8); p.wr = in(10); p.pwg = in(11); p.pwu = in(12); p.pwd = in(13);
    p.out = (__nv_bfloat16*)d_out;
    p.tn = g_tune;
    p.s = gs;
    make2d(enc, &m.wg, p.pwg, F_, D_, 32, 96, CU_TENSOR_MAP_SWIZZLE_64B);
    make2d(enc, &m.wu, p.pwu, F_, D_, 32, 96, CU_TENSOR_MAP_SWIZZLE_64B);
    make2d(enc, &m.wd, p.pwd, D_, F_, 16, 192, CU_TENSOR_MAP_SWIZZLE_32B);
    fused_kernel<<<NCTA, NTHREADS, SM_TOTAL>>>(p, m);
}

}

extern "C" void kernel_launch(void* const* d_in, const int* in_sizes, int n_in, void* d_out, int out_size) {
    static int clusters = -1;
    if (clusters < 0) clusters = v3::max_clusters();
    if (clusters < 15 || !v3::launch(d_in, d_out)) v2::launch(d_in, d_out);
}
```

```cpp
#include <cuda_runtime.h>
#include <cuda_bf16.h>
#include <cuda_fp16.h>
#include <cuda.h>
#include <stdint.h>
#include <stddef.h>
#include <type_traits>


namespace v3 {

template <int N> using Int = std::integral_constant<int, N>;

constexpr int D_ = 576, F_ = 4608;
constexpr int NCTA = 120, NTHREADS = 512;
constexpr int SPIN_LIMIT = 1 << 16;

enum { B_Y = 0, B_X = 8, B_TOP = 12, B_XS = 14, B_UP = 15, B_FULL = 16, B_FIN = 43, B_SEL = 44, B_RAW = 45, B_EMPTY = 38  , B_ROWS = 66, B_WR = 67 };
constexpr int SM_SKIP = 544, SM_SEL = 576;
constexpr int SM_ST = 640;
constexpr int SM_RAW = 2688, PITCH = 80;
constexpr int SM_CH = SM_RAW + 256 * PITCH, CH = 18304;
constexpr int TAB = 0, FT = 3072, XX = 3712, BOX = 8064, YIN = 14208;
constexpr int SM_B = SM_CH + 5 * CH, BP = 1168;
constexpr int SM_CAND = SM_B + 8 * BP, SM_PROG = SM_CAND + 256, SM_DUMP = SM_PROG + 128;
constexpr int NRING = 12, SM_W = SM_B + 10240, SM_FIN = SM_W + NRING * 8192, SM_TOTAL = 232448;
static_assert(SM_W % 1024 == 0 && SM_FIN + 8192 <= SM_TOTAL && SM_TOTAL - 18432 >= SM_W + 10 * 8192, "smem");

struct Tune { int t_tile, stag, c256, win5, win4, t_rows, da, t_pf, t_mma, zero; };

struct Scratch {
    uint32_t h[8 * 2304];
    uint2 stat[2048];
    uint32_t ep[NCTA * 8];
};
__device__ __align__(1024) Scratch g_s;

struct Hot {
    const __nv_bfloat16* u;
    int bre, bim, cre, cim, are, aim, logdt, dskip, wr, ep;
    Scratch* s;
    __nv_bfloat16* out;
    const __nv_bfloat16* wg;
    Tune tn;
};
struct Maps { CUtensorMap w[3], u; };

__device__ __forceinline__ uint32_t smem_u32(const void* p) { return (uint32_t)__cvta_generic_to_shared(p); }
__device__ __forceinline__ void mbar_init(uint32_t b, int c) { asm volatile("mbarrier.init.shared::cta.b64 [%0], %1;" ::"r"(b), "r"(c) : "memory"); }
__device__ __forceinline__ void mbar_expect(uint32_t b, int bytes) { asm volatile("mbarrier.arrive.expect_tx.shared::cta.b64 _, [%0], %1;" ::"r"(b), "r"(bytes) : "memory"); }
__device__ __forceinline__ void mbar_arrive(uint32_t b) { asm volatile("mbarrier.arrive.shared::cta.b64 _, [%0];" ::"r"(b) : "memory"); }
__device__ __forceinline__ bool elect() { uint32_t d; asm volatile("{.reg .pred p; elect.sync _|p, 0xffffffff; selp.u32 %0,1,0,p;}" : "=r"(d)); return d; }
__device__ __forceinline__ void mbar_wait(uint32_t b, int par) {
    asm volatile("{\n.reg .pred p;\nLW:\nmbarrier.try_wait.parity.shared::cta.b64 p, [%0], %1, 2000;\n@!p bra LW;\n}" ::"r"(b), "r"(par) : "memory");
}
__device__ __forceinline__ void mbar_wait_short(uint32_t b) {
    asm volatile("{\n.reg .pred p;\nLW:\nmbarrier.try_wait.parity.shared::cta.b64 p, [%0], 0;\n@!p bra LW;\n}" ::"r"(b) : "memory");
}
__device__ __forceinline__ uint32_t mapa(uint32_t a, uint32_t rank) { uint32_t d; asm("mapa.shared::cluster.u32 %0, %1, %2;" : "=r"(d) : "r"(a), "r"(rank)); return d; }
__device__ __forceinline__ void tma2d(uint32_t dst, const CUtensorMap* m, int c0, int c1, uint32_t bar) {
    asm volatile("cp.async.bulk.tensor.2d.shared::cluster.global.mbarrier::complete_tx::bytes [%0], [%1, {%3, %4}], [%2];" ::"r"(dst), "l"(m), "r"(bar), "r"(c0), "r"(c1) : "memory");
}
__device__ __forceinline__ void bulk_g2s(uint32_t dst, const void* src, int bytes, uint32_t bar) {
    asm volatile("cp.async.bulk.shared::cluster.global.mbarrier::complete_tx::bytes [%0], [%1], %2, [%3];" ::"r"(dst), "l"(src), "r"(bytes), "r"(bar) : "memory");
}
__device__ __forceinline__ void bulk_mc(uint32_t dst, const void* src, int bytes, uint32_t bar) {
    asm volatile("cp.async.bulk.shared::cluster.global.mbarrier::complete_tx::bytes.multicast::cluster [%0], [%1], %2, [%3], %4;"
                 ::"r"(dst), "l"(src), "r"(bytes), "r"(bar), "h"((uint16_t)255) : "memory");
}
__device__ __forceinline__ void bar_sync(int id, int n) { asm volatile("bar.sync %0, %1;" ::"r"(id), "r"(n) : "memory"); }
__device__ __forceinline__ void bar_arrive(int id, int n) { asm volatile("bar.arrive %0, %1;" ::"r"(id), "r"(n) : "memory"); }
__device__ __forceinline__ uint4 ld_rlx4(const void* p) { uint4 v; asm volatile("ld.relaxed.gpu.global.v4.u32 {%0,%1,%2,%3}, [%4];" : "=r"(v.x), "=r"(v.y), "=r"(v.z), "=r"(v.w) : "l"(p) : "memory"); return v; }
__device__ __forceinline__ uint2 ld_rlx2(const void* p) { uint2 v; asm volatile("ld.relaxed.gpu.global.v2.u32 {%0,%1}, [%2];" : "=r"(v.x), "=r"(v.y) : "l"(p) : "memory"); return v; }
__device__ __forceinline__ uint32_t ld_rlx(const void* p) { uint32_t v; asm volatile("ld.relaxed.gpu.global.u32 %0, [%1];" : "=r"(v) : "l"(p) : "memory"); return v; }
__device__ __forceinline__ void st_rlx(void* p, uint32_t v) { asm volatile("st.relaxed.gpu.global.u32 [%0], %1;" ::"l"(p), "r"(v) : "memory"); }
__device__ __forceinline__ void st_rlx2(void* p, uint32_t x, uint32_t y) { asm volatile("st.relaxed.gpu.global.v2.u32 [%0], {%1,%2};" ::"l"(p), "r"(x), "r"(y) : "memory"); }
__device__ __forceinline__ uint4 ldg4(const void* p) { uint4 v; asm volatile("ld.global.nc.v4.u32 {%0,%1,%2,%3}, [%4];" : "=r"(v.x), "=r"(v.y), "=r"(v.z), "=r"(v.w) : "l"(p)); return v; }
__device__ __forceinline__ uint32_t ldg1(const void* p) { uint32_t v; asm volatile("ld.global.nc.u32 %0, [%1];" : "=r"(v) : "l"(p)); return v; }
__device__ __forceinline__ uint32_t ldg16(const void* p) { uint16_t v; asm volatile("ld.global.nc.u16 %0, [%1];" : "=h"(v) : "l"(p)); return v; }
__device__ __forceinline__ const void* at256(const void* b, int o) { const void* r; asm("mad.wide.s32 %0, %1, 256, %2;" : "=l"(r) : "r"(o), "l"(b)); return r; }
__device__ __forceinline__ int laneid() { int v; asm volatile("mov.u32 %0, %%laneid;" : "=r"(v)); return v; }
__device__ __forceinline__ uint32_t keep(uint32_t v) { return __shfl_xor_sync(~0u, v, 0); }
__device__ __forceinline__ int ctaid() { int v; asm volatile("mov.u32 %0, %%ctaid.x;" : "=r"(v)); return v; }
__device__ __forceinline__ uint32_t lds32(uint32_t a) { uint32_t v; asm volatile("ld.shared.u32 %0, [%1];" : "=r"(v) : "r"(a) : "memory"); return v; }
__device__ __forceinline__ uint32_t lds32v(uint32_t a) { uint32_t v; asm volatile("ld.volatile.shared.u32 %0, [%1];" : "=r"(v) : "r"(a) : "memory"); return v; }
__device__ __forceinline__ uint32_t lds16(uint32_t a) { uint16_t v; asm volatile("ld.shared.u16 %0, [%1];" : "=h"(v) : "r"(a) : "memory"); return v; }
__device__ __forceinline__ uint2 lds64(uint32_t a) { uint2 v; asm volatile("ld.shared.v2.u32 {%0,%1}, [%2];" : "=r"(v.x), "=r"(v.y) : "r"(a) : "memory"); return v; }
__device__ __forceinline__ uint4 lds128(uint32_t a) { uint4 v; asm volatile("ld.shared.v4.u32 {%0,%1,%2,%3}, [%4];" : "=r"(v.x), "=r"(v.y), "=r"(v.z), "=r"(v.w) : "r"(a) : "memory"); return v; }
__device__ __forceinline__ void sts16(uint32_t a, uint32_t v) { asm volatile("st.shared.u16 [%0], %1;" ::"r"(a), "h"((uint16_t)v) : "memory"); }
__device__ __forceinline__ void sts32(uint32_t a, uint32_t v) { asm volatile("st.shared.u32 [%0], %1;" ::"r"(a), "r"(v) : "memory"); }
__device__ __forceinline__ void sts32v(uint32_t a, uint32_t v) { asm volatile("st.volatile.shared.u32 [%0], %1;" ::"r"(a), "r"(v) : "memory"); }
__device__ __forceinline__ void sts64(uint32_t a, uint32_t x, uint32_t y) { asm volatile("st.shared.v2.u32 [%0], {%1,%2};" ::"r"(a), "r"(x), "r"(y) : "memory"); }
__device__ __forceinline__ void sts128(uint32_t a, uint32_t x, uint32_t y, uint32_t z, uint32_t w) { asm volatile("st.shared.v4.u32 [%0], {%1,%2,%3,%4};" ::"r"(a), "r"(x), "r"(y), "r"(z), "r"(w) : "memory"); }
__device__ __forceinline__ void sts128v(uint32_t a, uint32_t x, uint32_t y, uint32_t z, uint32_t w) { asm volatile("st.volatile.shared.v4.u32 [%0], {%1,%2,%3,%4};" ::"r"(a), "r"(x), "r"(y), "r"(z), "r"(w) : "memory"); }
__device__ __forceinline__ void sts128f(uint32_t a, float x, float y, float z, float w) { asm volatile("st.shared.v4.f32 [%0], {%1,%2,%3,%4};" ::"r"(a), "f"(x), "f"(y), "f"(z), "f"(w) : "memory"); }
__device__ __forceinline__ void st_async4(uint32_t a, uint32_t x, uint32_t y, uint32_t z, uint32_t w, uint32_t bar) {
    asm volatile("st.async.shared::cluster.mbarrier::complete_tx::bytes.v4.b32 [%0], {%1,%2,%3,%4}, [%5];" ::"r"(a), "r"(x), "r"(y), "r"(z), "r"(w), "r"(bar) : "memory");
}
__device__ __forceinline__ void st_async2(uint32_t a, uint32_t x, uint32_t y, uint32_t bar) {
    asm volatile("st.async.shared::cluster.mbarrier::complete_tx::bytes.v2.b32 [%0], {%1,%2}, [%3];" ::"r"(a), "r"(x), "r"(y), "r"(bar) : "memory");
}
__device__ __forceinline__ void st_async2f(uint32_t a, float x, float y, uint32_t bar) {
    asm volatile("st.async.shared::cluster.mbarrier::complete_tx::bytes.v2.f32 [%0], {%1,%2}, [%3];" ::"r"(a), "f"(x), "f"(y), "r"(bar) : "memory");
}
__device__ __forceinline__ void ldm4(uint32_t a, uint32_t& r0, uint32_t& r1, uint32_t& r2, uint32_t& r3) {
    asm volatile("ldmatrix.sync.aligned.m8n8.x4.shared.b16 {%0,%1,%2,%3}, [%4];" : "=r"(r0), "=r"(r1), "=r"(r2), "=r"(r3) : "r"(a) : "memory");
}
__device__ __forceinline__ void ldm4t(uint32_t a, uint32_t (&r)[4]) {
    asm volatile("ldmatrix.sync.aligned.m8n8.x4.trans.shared.b16 {%0,%1,%2,%3}, [%4];" : "=r"(r[0]), "=r"(r[1]), "=r"(r[2]), "=r"(r[3]) : "r"(a) : "memory");
}
__device__ __forceinline__ void ldm2(uint32_t a, uint32_t& r0, uint32_t& r1) {
    asm volatile("ldmatrix.sync.aligned.m8n8.x2.shared.b16 {%0,%1}, [%2];" : "=r"(r0), "=r"(r1) : "r"(a) : "memory");
}
__device__ __forceinline__ void ldm2t(uint32_t a, uint32_t& r0, uint32_t& r1) {
    asm volatile("ldmatrix.sync.aligned.m8n8.x2.trans.shared.b16 {%0,%1}, [%2];" : "=r"(r0), "=r"(r1) : "r"(a) : "memory");
}
__device__ __forceinline__ void stm4(uint32_t a, uint32_t r0, uint32_t r1, uint32_t r2, uint32_t r3) {
    asm volatile("stmatrix.sync.aligned.m8n8.x4.shared.b16 [%0], {%1,%2,%3,%4};" ::"r"(a), "r"(r0), "r"(r1), "r"(r2), "r"(r3) : "memory");
}
__device__ __forceinline__ void stm4t(uint32_t a, uint32_t r0, uint32_t r1, uint32_t r2, uint32_t r3) {
    asm volatile("stmatrix.sync.aligned.m8n8.x4.trans.shared.b16 [%0], {%1,%2,%3,%4};" ::"r"(a), "r"(r0), "r"(r1), "r"(r2), "r"(r3) : "memory");
}
__device__ __forceinline__ void stm2t(uint32_t a, uint32_t r0, uint32_t r1) {
    asm volatile("stmatrix.sync.aligned.m8n8.x2.trans.shared.b16 [%0], {%1,%2};" ::"r"(a), "r"(r0), "r"(r1) : "memory");
}
__device__ __forceinline__ uint32_t movm(uint32_t a) { uint32_t d; asm volatile("movmatrix.sync.aligned.m8n8.trans.b16 %0, %1;" : "=r"(d) : "r"(a)); return d; }
__device__ __forceinline__ void mma_bf(float (&c)[4], uint32_t a0, uint32_t a1, uint32_t a2, uint32_t a3, uint32_t b0, uint32_t b1) {
    asm volatile("mma.sync.aligned.m16n8k16.row.col.f32.bf16.bf16.f32 {%0,%1,%2,%3},{%4,%5,%6,%7},{%8,%9},{%0,%1,%2,%3};"
                 : "+f"(c[0]), "+f"(c[1]), "+f"(c[2]), "+f"(c[3]) : "r"(a0), "r"(a1), "r"(a2), "r"(a3), "r"(b0), "r"(b1));
}
__device__ __forceinline__ void mma_bf8(float (&c)[4], uint32_t a0, uint32_t a1, uint32_t b0) {
    asm volatile("mma.sync.aligned.m16n8k8.row.col.f32.bf16.bf16.f32 {%0,%1,%2,%3},{%4,%5},{%6},{%0,%1,%2,%3};"
                 : "+f"(c[0]), "+f"(c[1]), "+f"(c[2]), "+f"(c[3]) : "r"(a0), "r"(a1), "r"(b0));
}
__device__ __forceinline__ void mma_h(float (&c)[4], uint32_t a0, uint32_t a1, uint32_t a2, uint32_t a3, uint32_t b0, uint32_t b1) {
    asm volatile("mma.sync.aligned.m16n8k16.row.col.f32.f16.f16.f32 {%0,%1,%2,%3},{%4,%5,%6,%7},{%8,%9},{%0,%1,%2,%3};"
                 : "+f"(c[0]), "+f"(c[1]), "+f"(c[2]), "+f"(c[3]) : "r"(a0), "r"(a1), "r"(a2), "r"(a3), "r"(b0), "r"(b1));
}
__device__ __forceinline__ void mma_h8(float (&c)[4], uint32_t a0, uint32_t a1, uint32_t b0) {
    asm volatile("mma.sync.aligned.m16n8k8.row.col.f32.f16.f16.f32 {%0,%1,%2,%3},{%4,%5},{%6},{%0,%1,%2,%3};"
                 : "+f"(c[0]), "+f"(c[1]), "+f"(c[2]), "+f"(c[3]) : "r"(a0), "r"(a1), "r"(b0));
}
template <int LIM>
__device__ __forceinline__ void mma_hp(int n, float (&d)[4], const float (&c)[4], uint32_t a0, uint32_t a1, uint32_t a2, uint32_t a3, uint32_t b0, uint32_t b1) {
    asm volatile("{.reg .pred p; setp.gt.s32 p, %14, %15;\n"
                 "@p mma.sync.aligned.m16n8k16.row.col.f32.f16.f16.f32 {%0,%1,%2,%3},{%4,%5,%6,%7},{%8,%9},{%10,%11,%12,%13};}"
                 : "+f"(d[0]), "+f"(d[1]), "+f"(d[2]), "+f"(d[3])
                 : "r"(a0), "r"(a1), "r"(a2), "r"(a3), "r"(b0), "r"(b1), "f"(c[0]), "f"(c[1]), "f"(c[2]), "f"(c[3]), "r"(n), "n"(LIM));
}
template <int LIM>
__device__ __forceinline__ void mma_hq(int n, float (&d)[4], uint32_t a0, uint32_t a1, uint32_t a2, uint32_t a3, uint32_t b0, uint32_t b1) {
    asm volatile("{.reg .pred p; setp.gt.s32 p, %10, %11;\n"
                 "@p mma.sync.aligned.m16n8k16.row.col.f32.f16.f16.f32 {%0,%1,%2,%3},{%4,%5,%6,%7},{%8,%9},{%0,%1,%2,%3};}"
                 : "+f"(d[0]), "+f"(d[1]), "+f"(d[2]), "+f"(d[3]) : "r"(a0), "r"(a1), "r"(a2), "r"(a3), "r"(b0), "r"(b1), "r"(n), "n"(LIM));
}
__device__ __forceinline__ void mma_hc(float (&d)[4], const float (&c)[4], uint32_t a0, uint32_t a1, uint32_t a2, uint32_t a3, uint32_t b0, uint32_t b1) {
    asm volatile("mma.sync.aligned.m16n8k16.row.col.f32.f16.f16.f32 {%0,%1,%2,%3},{%4,%5,%6,%7},{%8,%9},{%10,%11,%12,%13};"
                 : "=f"(d[0]), "=f"(d[1]), "=f"(d[2]), "=f"(d[3]) : "r"(a0), "r"(a1), "r"(a2), "r"(a3), "r"(b0), "r"(b1), "f"(c[0]), "f"(c[1]), "f"(c[2]), "f"(c[3]));
}
__device__ __forceinline__ uint32_t pack_bf(float lo, float hi) { uint32_t r; asm("cvt.rn.bf16x2.f32 %0, %1, %2;" : "=r"(r) : "f"(hi), "f"(lo)); return r; }
__device__ __forceinline__ uint32_t pack_h(float lo, float hi) { uint32_t r; asm("cvt.rn.f16x2.f32 %0, %1, %2;" : "=r"(r) : "f"(hi), "f"(lo)); return r; }
__device__ __forceinline__ float bf_lo(uint32_t w) { return __uint_as_float(w << 16); }
__device__ __forceinline__ float bf_hi(uint32_t w) { return __uint_as_float(w & 0xFFFF0000u); }
__device__ __forceinline__ float bf_round(float x) { return __uint_as_float(pack_bf(0.f, x)); }
__device__ __forceinline__ uint32_t badd(uint32_t a, uint32_t b) { uint32_t r; asm("add.rn.bf16x2 %0, %1, %2;" : "=r"(r) : "r"(a), "r"(b)); return r; }
__device__ __forceinline__ uint32_t bsub(uint32_t a, uint32_t b) { uint32_t r; asm("sub.rn.bf16x2 %0, %1, %2;" : "=r"(r) : "r"(a), "r"(b)); return r; }
__device__ __forceinline__ uint32_t bmul(uint32_t a, uint32_t b) { uint32_t r; asm("mul.rn.bf16x2 %0, %1, %2;" : "=r"(r) : "r"(a), "r"(b)); return r; }
__device__ __forceinline__ uint32_t bfma(uint32_t a, uint32_t b, uint32_t c) { uint32_t r; asm("fma.rn.bf16x2 %0, %1, %2, %3;" : "=r"(r) : "r"(a), "r"(b), "r"(c)); return r; }
__device__ __forceinline__ uint32_t hadd(uint32_t a, uint32_t b) { uint32_t r; asm("add.rn.f16x2 %0, %1, %2;" : "=r"(r) : "r"(a), "r"(b)); return r; }
__device__ __forceinline__ uint32_t prmt(uint32_t a, uint32_t b, uint32_t s) { uint32_t r; asm("prmt.b32 %0, %1, %2, %3;" : "=r"(r) : "r"(a), "r"(b), "r"(s)); return r; }
__device__ __forceinline__ uint32_t lop_ne(uint32_t a, uint32_t b, uint32_t c) { uint32_t r; asm("lop3.b32 %0, %1, %2, %3, 0x7E;" : "=r"(r) : "r"(a), "r"(b), "r"(c)); return r; }
__device__ __forceinline__ float ex2f(float x) { float r; asm("ex2.approx.ftz.f32 %0, %1;" : "=f"(r) : "f"(x)); return r; }
__device__ __forceinline__ float rcpf(float x) { float r; asm("rcp.approx.ftz.f32 %0, %1;" : "=f"(r) : "f"(x)); return r; }
__device__ __forceinline__ float sqrt_ap(float x) { float r; asm("sqrt.approx.ftz.f32 %0, %1;" : "=f"(r) : "f"(x)); return r; }
__device__ __forceinline__ float tanh_ap(float x) { float r; asm("tanh.approx.f32 %0, %1;" : "=f"(r) : "f"(x)); return r; }
__device__ __forceinline__ float sigm(float x) { return rcpf(1.f + ex2f(-1.4426950408889634f * x)); }
__device__ __forceinline__ float silu_half(float h) { return fmaf(h, tanh_ap(h), h); }
__device__ __forceinline__ uint32_t clk32() { uint32_t c; asm volatile("mov.u32 %0, %%clock;" : "=r"(c)); return c; }
__device__ __forceinline__ void spin_until(uint32_t t0, int dt) {
#pragma unroll 1
    while ((int)(clk32() - t0) < dt) __nanosleep(32);
}
__device__ __forceinline__ void cp16(uint32_t dst, const void* src) { asm volatile("cp.async.cg.shared.global [%0], [%1], 16;" ::"r"(dst), "l"(src) : "memory"); }

__device__ __forceinline__ uint32_t xslot(int s, int h) { return XX + 32 * (s & ~1) + 16 * ((2 * h + (s & 1)) ^ ((s >> 1) & 2)); }

struct cf { float x, y; };
__device__ __forceinline__ cf cmul(cf a, cf b) { return {a.x * b.x - a.y * b.y, a.x * b.y + a.y * b.x}; }
__device__ __forceinline__ cf csq(cf a) {
    float y;
    asm("{.reg .f32 t; mul.ftz.f32 t, %1, %2; mul.ftz.f32 %0, t, 0f40000000;}" : "=f"(y) : "f"(a.x), "f"(a.y));
    return {a.x * a.x - a.y * a.y, y};
}
__device__ __forceinline__ cf cpow_direct(float zr2, float zi, float l) {
    const float mag = ex2f(zr2 * l), th = zi * l;
    return {mag * __cosf(th), mag * __sinf(th)};
}
struct hp { uint32_t re, im; };
struct hm { __half2 v; };
__device__ __forceinline__ __half2 as_h2(uint32_t v) { return *reinterpret_cast<__half2*>(&v); }
__device__ __forceinline__ uint32_t as_u32(__half2 v) { return *reinterpret_cast<uint32_t*>(&v); }
__device__ __forceinline__ hp mk2(cf a, cf b) { return {pack_h(a.x, b.x), pack_h(a.y, b.y)}; }
__device__ __forceinline__ hm mk1(cf a) { return {as_h2(pack_h(a.x, a.y))}; }
__device__ __forceinline__ hp his(hp a, hp b) { return {prmt(a.re, b.re, 0x7632), prmt(a.im, b.im, 0x7632)}; }
__device__ __forceinline__ hp operator*(hp a, hm b) {
    const __half2 c = __low2half2(b.v), s = __high2half2(b.v), x = as_h2(a.re), y = as_h2(a.im);
    return {as_u32(__hfma2(x, c, __hneg2(__hmul2_rn(y, s)))), as_u32(__hfma2(x, s, __hmul2_rn(y, c)))};
}
__device__ __forceinline__ hp operator*(hp a, hp b) {
    const __half2 c = as_h2(b.re), s = as_h2(b.im), x = as_h2(a.re), y = as_h2(a.im);
    return {as_u32(__hfma2(x, c, __hneg2(__hmul2_rn(y, s)))), as_u32(__hfma2(x, s, __hmul2_rn(y, c)))};
}
struct KParams { uint32_t are, aim, bre, bim, cre, cim, ldt, dsk, sa, la, lb, sb, sm, lm, l3, l4; };

__device__ __forceinline__ void kgen_addr(KParams& kp, uint32_t scr, int lane) {
    const int g = lane >> 2, t = lane & 3, mi = lane >> 3, j = lane & 7;
    kp.sa = keep(scr + 16 * lane);
    kp.sb = keep(scr + 128 * t + 16 * (g ^ (2 * t)));
    kp.la = keep(scr + 512 * (mi & 1) + 128 * (mi >> 1) + 16 * (j ^ (mi & 2)));
    kp.lb = keep((kp.la ^ 64) + 256);
    kp.sm = keep(scr + 2048 + 144 * mi + 16 * j);
    kp.lm = keep(scr + 2048 + 16 * mi);
    kp.l3 = keep(kp.lm + 144 * (j & 1));
    kp.l4 = keep(kp.lm + 288 - 72 * (j & 2));
}

__device__ __forceinline__ uint32_t kgen(KParams kp, uint32_t scr, uint32_t oth, int bar, int lane, float (&d)[5][4], float& k0, int nc, uint32_t pause, uint32_t zero) {
    const float dt = bf_round(ex2f(bf_lo(kp.ldt) * 1.4426950408889634f));
    cf w = cmul({bf_lo(kp.cre), bf_lo(kp.cim)}, {dt * bf_lo(kp.bre), dt * bf_lo(kp.bim)});
    cf w1 = cmul({bf_hi(kp.cre), bf_hi(kp.cim)}, {dt * bf_hi(kp.bre), dt * bf_hi(kp.bim)});
    const float dk = bf_lo(kp.dsk), dt2 = dt * 1.4426950408889634f;
    uint32_t z = prmt(kp.are, kp.aim, 0x5410), z1 = prmt(kp.are, kp.aim, 0x7632);
    uint32_t eb = __reduce_max_sync(~0u, __float_as_uint(fmaxf(fmaxf(fmaxf(fabsf(w.x), fabsf(w.y)), fmaxf(fabsf(w1.x), fabsf(w1.y))), fabsf(dk) * 0x1p-20f)));
    k0 = w.x + w1.x;
    const uint32_t sa = kp.sa, la = kp.la, lb = kp.lb;
    sts128(oth + 2048 + 16 * lane, __float_as_uint(w1.x), __float_as_uint(w1.y), z1, __float_as_uint(k0));
    sts32(oth + 2560, eb);
    const uint32_t sb = kp.sb, sm = kp.sm, lm = kp.lm, l3 = kp.l3, l4 = kp.l4;
    hp u[4], v[4];
    uint32_t m[6];
    cf a1, a2;
    hm m4, m8;
    auto powers = [&](uint32_t z) {
        const float zr2 = dt2 * bf_lo(z), zi = dt * bf_hi(z);
        a1 = cpow_direct(zr2, zi, 1.f); a2 = csq(a1);
        const cf a256 = cpow_direct(zr2, zi, 256.f), b1 = cpow_direct(-zr2, zi, -16.f);
        const cf b2 = csq(b1), b4 = csq(b2), a4 = csq(a2), a512 = csq(a256), a514 = cmul(a512, a2);
        const hm n4 = mk1(b4);
        m4 = mk1(a4); m8 = mk1(csq(a4));
        u[0] = mk2({1.f, 0.f}, b1); u[1] = u[0] * mk1(b2); u[2] = u[0] * n4; u[3] = u[1] * n4;
        m[0] = as_u32(mk1(cmul(a514, a256)).v); m[1] = as_u32(mk1(a512).v); m[2] = as_u32(mk1(csq(a514)).v); m[3] = as_u32(mk1(a256).v);
        m[4] = as_u32(mk1(csq(b4)).v); m[5] = as_u32(mk1(a1).v);
    };
    float sc;
    auto weights = [&](cf w) {
        const cf c1 = cmul({w.x * sc, w.y * sc}, a1);
        v[0] = mk2(c1, cmul(c1, a2)); v[1] = v[0] * m4; v[2] = v[0] * m8; v[3] = v[1] * m8;
    };
    auto store = [&]() {
        __syncwarp();
        stm4t(sm, m[0], m[1], m[2], m[3]);
        stm2t(sm + 576, m[4], m[5]);
        sts128(sb, u[0].re, u[1].re, u[2].re, u[3].re); sts128(sb + 512, u[0].im, u[1].im, u[2].im, u[3].im);
        sts128(sb + 1024, v[0].re, v[1].re, v[2].re, v[3].re); sts128(sb + 1536, v[0].im, v[1].im, v[2].im, v[3].im);
        __syncwarp();
    };
    auto sums = [&](int h) {
        if (h && pause) { mbar_wait(pause, 0); pause = 0; }
        uint32_t a[4], b[4], q[5][4];
        ldm4t(h ? lb : la, a);
        ldm4t((h ? lb : la) + 1024, b);
#pragma unroll
        for (int e = 0; e < 5; e++) ldm4((e == 3 ? l3 : (e == 4 ? l4 : lm + (e == 2 ? 432 : 576 + 144 * e))) + 64 * h, q[e][0], q[e][1], q[e][2], q[e][3]);
#pragma unroll
        for (int e = 0; e < 4; e += 2) {
            auto mul = [&](int i) { return hp{q[i][e], q[i][e + 1]}; };
            const hp y0 = {b[e], b[e + 1]}, y1 = y0 * mul(1), y2 = y1 * mul(2), y3 = y1 * mul(3), y4 = y3 * mul(4), x1 = hp{a[e], a[e + 1]} * mul(0);
            const uint32_t a0 = a[e] | zero, a2 = a[e + 1] | zero;
            mma_h(d[0], a0, x1.re, a2, x1.im, y0.re, y0.im);
            mma_h(d[1], a0, x1.re, a2, x1.im, y1.re, y1.im);
            mma_h(d[2], a0, x1.re, a2, x1.im, y2.re, y2.im);
            mma_h(d[3], a0, x1.re, a2, x1.im, y3.re, y3.im);
            mma_h(d[4], a0, x1.re, a2, x1.im, y4.re, y4.im);
        }
    };
    powers(z);
    bar_sync(bar | (u[3].re & m[0] & m[2] & zero), 64);
    const uint4 ov = lds128(sa + 2048);
    eb = min(max(max(eb, lds32(scr + 2560)) & 0x7F800000u, 0x00800000u), 0x7A000000u);
    sc = __uint_as_float(0x7B000000u - eb);
    weights(w);
    k0 = fmaf(dk, sc, 0x1p-28f * __reduce_add_sync(~0u, __float2int_rn((k0 + __uint_as_float(ov.w)) * sc * 0x1p28f)));
#pragma unroll
    for (int i = 0; i < 5; i++) d[i][0] = d[i][1] = d[i][2] = d[i][3] = 0.f;
#pragma unroll 1
    while (--nc) {
        store();
        sums(0);
        sums(1);
        powers(z1);
        weights(w1);
        z1 = ov.z; w1 = {__uint_as_float(ov.x), __uint_as_float(ov.y)};
    }
    store();
    sums(0);
    sums(1);
    return eb;
}

__device__ __forceinline__ void near_lags(uint32_t S, int k, uint32_t yo, uint32_t eb, const uint32_t (&xa)[8], uint32_t step  ) {
    const int lane = threadIdx.x & 31, g = lane >> 2, t = lane & 3, mi = lane >> 3, j = lane & 7, warp = k;
    const uint32_t cb = S + SM_CH + k * CH;
    uint32_t R[66];
    float w[5][4];
#pragma unroll
    for (int i = 0; i < 5; i++) w[i][0] = w[i][1] = w[i][2] = w[i][3] = 0.f;
    uint32_t xo = cb;
    auto loadr = [&](int i0, int i1) {
#pragma unroll
        for (int i = i0; i < i1; i++) {
            const int e = i < 64 ? 14 - 2 * (i >> 3) + 16 * ((i >> 1) & 3) + (i & 1) : i;
            R[e] = lds32(cb + TAB + 4 * (7 + g - 2 * t) + 32 * e);
        }
    };
    loadr(0, 66);
    uint32_t fa = xa[0], idm = 0;
    uint32_t ya[2], yb[2];
#pragma unroll
    for (int e = 0; e < 2; e++) {
        yb[e] = mapa(S + B_Y * 8, 4 * e + (g >> 1));
        ya[e] = yb[e] - B_Y * 8 + SM_CH + k * CH + YIN + (yo ^ (8 * j));
    }
    const uint32_t sc = prmt(eb + 0x04800000u, 0, 0x3232);
    uint32_t z = lds32(cb + XX + 4 * lane);
    mbar_wait(S + B_X * 8, 0);
    uint32_t A[3][4], x[5];
    ldm2(xo + xa[0], x[1], x[2]);
    x[0] = z;
    ldm2(xo + xa[1], x[3], x[4]);
    loadr(66, 66);
    auto send = [&](int e) { st_async2(ya[e], bmul(pack_bf(w[0][0], w[0][1]), sc), bmul(pack_bf(w[0][2], w[0][3]), sc), yb[e]); };
    auto tile = [&](auto nj, auto l4, auto par) {
        constexpr int NJ = decltype(nj)::value, L4 = decltype(l4)::value, P = decltype(par)::value;
        asm volatile("" : "+r"(z), "+r"(xo));
        uint32_t f0, f1;
        if (P < 2) ldm2(xo + fa, f0, f1);
        if (P < 2) send(P);
#pragma unroll
        for (int q = 1; q <= 8; q++) {
            const uint32_t ad = xo + xa[(q + 1) & 7] + 32 * ((q + 1) & 8);
            if (!L4) {
                A[0][0] = x[1]; A[0][1] = x[2]; A[0][2] = x[0] | z; A[0][3] = x[1] | z;
                x[0] = x[2]; x[1] = x[3]; x[2] = x[4];
                ldm2(ad, x[3], x[4]);
            } else {
                ldm4(ad, A[2][0], A[2][1], A[2][2], A[2][3]);
            }
            const float zero[4] = {0.f, 0.f, 0.f, 0.f};
#pragma unroll
            for (int i = 0; i < (NJ < 4 ? NJ : 4); i++) {
                const int s = 16 * i + 16 - 2 * q;
                if (q == 1) mma_hc(w[i], w[i + 1], A[0][0], A[0][1], A[0][2], A[0][3], R[s], R[s + 1]);
                else mma_h(w[i], A[0][0], A[0][1], A[0][2], A[0][3], R[s], R[s + 1]);
            }
            if (q == 4 && P < 2) mma_h8(w[1], f0, f1, idm);
            if (q == 7 && P < 2) {
                const uint32_t zz = A[0][0] & z;
                ya[P & 1] += 512 + zz; yb[P & 1] += 8 + zz;
            }
            if (q == 8 && NJ == 5) mma_hc(w[4], zero, A[0][0], A[0][1], A[0][2], A[0][3], R[64], R[65]);
#pragma unroll
            for (int e = 0; e < 4 * L4; e++) { A[0][e] = A[1][e]; A[1][e] = A[2][e]; }
        }
        xo += step;
    };
    tile(Int<5>(), Int<0>(), Int<2>());
    bar_arrive(1 + k, 64);
    int n = 17, c = 1;
#pragma unroll 1
    do {
#pragma unroll 1
        do {
            tile(Int<5>(), Int<0>(), Int<0>());
            tile(Int<5>(), Int<0>(), Int<1>());
        } while (--c);
        n -= 4; c = 2;
        const int lane = laneid(), g = lane >> 2, t = lane & 3;
        fa = TAB - 768 + 16 * (lane & 15);
        idm = g == 2 * t ? 0x3C00u : (g == 2 * t + 1 ? 0x3C000000u : 0u);
#pragma unroll 1
        while (lds32v(S + SM_PROG + 4 * k) >= n) __nanosleep(40);
    } while (n > 5);
    ldm4(xo + xa[0], A[0][0], A[0][1], A[0][2], A[0][3]);
    ldm4(xo + xa[1], A[1][0], A[1][1], A[1][2], A[1][3]);
    tile(Int<5>(), Int<1>(), Int<0>());
    tile(Int<4>(), Int<1>(), Int<1>());
    tile(Int<3>(), Int<1>(), Int<0>());
    {
        uint32_t B[16][4], f0, f1;
        ldm2(xo + fa, f0, f1);
        send(1);
#pragma unroll
        for (int e = 0; e < 4; e++) { B[0][e] = A[0][e]; B[1][e] = A[1][e]; }
        const uint32_t x2 = xo + step;
#pragma unroll
        for (int q = 0; q < 8; q++) {
            ldm4(x2 + xa[q], B[8 + q][0], B[8 + q][1], B[8 + q][2], B[8 + q][3]);
            if (q < 6) ldm4(xo + xa[q + 2], B[q + 2][0], B[q + 2][1], B[q + 2][2], B[q + 2][3]);
        }
        w[3][0] = w[3][1] = w[3][2] = w[3][3] = 0.f;
        mma_h8(w[3], f0, f1, idm);
#pragma unroll
        for (int q = 0; q < 8; q++) {
            mma_h(w[1], B[q][0], B[q][1], B[q][2], B[q][3], R[14 - 2 * q], R[15 - 2 * q]);
            mma_h(w[2], B[q][0], B[q][1], B[q][2], B[q][3], R[30 - 2 * q], R[31 - 2 * q]);
            mma_h(w[3], B[8 + q][0], B[8 + q][1], B[8 + q][2], B[8 + q][3], R[14 - 2 * q], R[15 - 2 * q]);
        }
        ya[1] += 512; yb[1] += 8;
#pragma unroll
        for (int e = 0; e < 4; e++) w[0][e] = w[1][e];
        send(0);
#pragma unroll
        for (int e = 0; e < 4; e++) w[0][e] = w[2][e] + w[3][e];
        send(1);
    }
}

__global__ void __cluster_dims__(8, 1, 1) __launch_bounds__(NTHREADS, 1) fused_kernel(const __grid_constant__ Hot p, const __grid_constant__ Maps m) {
    extern __shared__ __align__(1024) char smem[];
    const uint32_t t0 = clk32();
    const int tid = threadIdx.x, lane = tid & 31, bx = blockIdx.x;
    {
        const uint32_t a = min(tid >> 5, 5), ln = 10 * bx + lane;
        const void* pa = at256(p.u + ln * 64, (&p.bre)[a]);
        asm volatile("{.reg .pred p; setp.lt.u32 p, %1, 10; setp.lt.and.u32 p, %2, 192, p; setp.lt.and.u32 p, %3, 1152, p;\n@p prefetch.global.L2 [%0];}"
                     ::"l"(pa), "r"(lane), "r"(tid), "r"(ln) : "memory");
    }
    const int g = lane >> 2, t = lane & 3, mi = lane >> 3, j = lane & 7;
    const uint32_t role = __shfl_sync(~0u, (tid >> 5) | ((uint32_t)((bx < 24 ? 0x5776666632103210ull : 0x5436666621043210ull) >> ((tid >> 3) & 60)) & 15) << 8 |
                                               max(4 * (bx >> 3), 5 * (bx >> 3) - 3) << 16 | bx << 24, 0);
    const int warp = role & 255, k = (role >> 8) & 255, cbase = (role >> 13) & 0x7F8, bid = role >> 24, r = bid & 7, cl = role >> 27;
    const int pair = cl > 2, nch = 4 + pair;
    uint32_t S = smem_u32(smem);
    asm volatile("" : "+r"(S));

    const int half = warp >= nch;
    const bool two = cl == 1 || cl == 2, extra = two && k == 7, svcwarp = (warp >> 2) == 2;
    KParams kp;
    uint32_t epoch, pre[8];
    if (k < nch) {
        const uint32_t ch = cbase + 8 * k + r;
        const char* pb = (const char*)p.u + (ch * 256 + half * 128 + lane * 4);
        kp.bre = ldg1(at256(pb, p.bre)); kp.bim = ldg1(at256(pb, p.bim));
        kp.cre = ldg1(at256(pb, p.cre)); kp.cim = ldg1(at256(pb, p.cim));
        kp.ldt = ldg16(at256(p.u + ch, lane & 1 ? p.dskip : p.logdt));
        kp.are = ldg1(at256(pb, p.are)); kp.aim = ldg1(at256(pb, p.aim));
        sts128(S + SM_CH + k * CH + 16 * lane + (half ? FT : (lane < 2 ? TAB : (lane < 8 ? TAB + 2048 : FT + 384))), 0u, 0u, 0u, 0u);
        sts32(S + SM_PROG + 4 * k, 13);
        kgen_addr(kp, S + SM_CH + k * CH + BOX + 3072 * half, lane);
        if (half) {
            const uint32_t a0 = BOX + 16 + 576 * (j & 1) + 16 * (j >> 1);
            pre[0] = keep(a0 + (mi == 1 ? 1152 : (mi == 2 ? 1136 : 0)));
            pre[1] = keep(a0 + 2304 + 1152 * (mi & 1) + 64 * (mi >> 1));
            pre[2] = keep(BOX + 16 + 4608 + 576 * (mi & 1) + 128 * (mi >> 1) + 16 * j);
            pre[3] = keep(BOX + 16 + (lane < 2 ? 1152 + 576 * lane : 2896));
            pre[4] = keep(xslot(8 + lane, 0));
            pre[5] = keep(xslot(7 + lane, 0));
            pre[6] = keep(FT + 504 - 128 * (t & 1) + 4 * g + (t & 2));
            pre[7] = keep(g == 2 * t ? 0x4432 : (g == 2 * t + 1 ? 0x3244 : 0x4444));
        } else {
            const uint32_t v = xslot(lane & 15, lane >> 4);
#pragma unroll
            for (int i = 0; i < 8; i++) pre[i] = __shfl_sync(~0u, v, j + i + (mi == 1 ? 17 : (mi == 2 ? 16 : 1)));
        }
    } else if (warp == 12) {
        if (elect()) {
            mbar_init(S + B_WR * 8, 1);
            mbar_init(S + B_ROWS * 8, 1);
            mbar_expect(S + B_WR * 8, 1152);
            bulk_g2s(S + SM_B + 2048, (const char*)p.u + p.wr * 256ll, 1152, S + B_WR * 8);
            while ((int)(clk32() - t0) < (pair ? p.tn.t_rows : 0)) {}
            mbar_expect(S + B_ROWS * 8, two ? 36864 : 18432);
            const __nv_bfloat16* src = p.u + (8 * ((cl + pair) & 14) + 2 * r + ((cl + pair) & 1)) * 9216;
            bulk_g2s(S + SM_TOTAL - 18432, src, 18432, S + B_ROWS * 8);
            if (two) bulk_g2s(S + SM_CH + 4 * CH - 128, p.u + (17 + 2 * r) * 9216, 18432, S + B_ROWS * 8);
        }
    } else if (svcwarp) {
        if (elect()) {
#pragma unroll
            for (int i = 0; i < 16; i++) mbar_init(S + (warp & 3) * 128 + i * 8, warp > (i < 14 ? 10 : 9) ? 4 : 1);
            asm volatile("fence.mbarrier_init.release.cluster;" ::: "memory");
        }
        __syncwarp();
        sts128(S + SM_B + 16 * tid, 0x3F803F80u, 0x3F803F80u, 0x3F803F80u, 0x3F803F80u);
        if (tid < 272) mbar_expect(S + lane * 8, lane < B_TOP ? (512 << mi) * nch : (lane < B_XS ? 128 : (lane == B_XS ? 9216 : 1024)));
    }
    const bool early = warp == 13 || warp == 14;
    if (svcwarp || extra) epoch = ld_rlx(at256(p.u + bid * 16, p.ep));
    __syncthreads();
    asm volatile("barrier.cluster.arrive.relaxed.aligned;" ::: "memory");
    const uint2* sp = &p.s->stat[256 * r + 2 * (tid & 127)];
    uint4 sw;
    if (svcwarp) sw = ld_rlx4(sp);
    if (svcwarp || extra) {
        const uint32_t tag = ~epoch & 1;
        const int tile = extra ? 3 : cl + pair, wj = extra ? warp + 2 * cl - 15 : warp & 3;
        float d2[4] = {0, 0, 0, 0}, d3[4] = {0, 0, 0, 0}, d4[4] = {0, 0, 0, 0}, d5[4] = {0, 0, 0, 0}, d6[4] = {0, 0, 0, 0}, d7[4] = {0, 0, 0, 0};
        const uint32_t xa = S + (extra ? SM_CH + 4 * CH - 128 : SM_TOTAL - 18432) + (8 * (mi >> 1) + 2 * wj + (mi & 1)) * 1152 + 16 * j;
        const uint32_t wa = S + SM_B + 4104 - 2056 * (g & 1) + 64 * (g >> 2) + 16 * t + 2 * (g & 2), ones = 0x3F803F80u;
        uint32_t wv[18];
        mbar_wait_short(S + B_WR * 8);
#pragma unroll
        for (int i = 0; i < 18; i++) wv[i] = lds32(wa + 128 * (i >> 1) + 8 * (i & 1));
        spin_until(t0, p.tn.t_mma);
#pragma unroll
        for (int i = 0; i < 9; i++) mma_bf(d5, ones, ones, ones, ones, wv[2 * i], wv[2 * i + 1]);
        float wsum = d5[1] + __shfl_xor_sync(~0u, d5[1], 1);
        wsum += __shfl_xor_sync(~0u, wsum, 2);
        mbar_wait_short((S + B_ROWS * 8) | (__float_as_uint(wsum) & p.tn.zero));
        __syncwarp();
#pragma unroll
        for (int i = 0; i < 9; i++) {
            const uint4 x = lds128(xa + 128 * i);
            mma_bf8(d3, x.x, x.y, x.x);
            mma_bf8(d4, x.x, x.y, x.y);
            mma_bf8(d6, x.z, x.w, x.z);
            mma_bf8(d7, x.z, x.w, x.w);
            mma_bf(d2, x.x, x.y, x.z, x.w, wv[2 * i], wv[2 * i + 1]);
        }
        float sx = d2[0] + d2[2], sq = (g & 1) ? (d3[1] + d4[3]) + (d6[1] + d7[3]) : (d3[0] + d4[2]) + (d6[0] + d7[2]);
        float dot = (t & 1) ? d2[3] : d2[1];
        sx += __shfl_xor_sync(~0u, sx, 4);
        sq = __shfl_sync(~0u, sq, 9 * mi) + __shfl_sync(~0u, sq, 9 * mi + 4);
        dot += __shfl_xor_sync(~0u, dot, 1);
        dot += __shfl_xor_sync(~0u, dot, 6);
        const float mean = sx * (1.f / 576.f), var = fmaxf(sq * (1.f / 576.f) - mean * mean, 0.f);
        const float mu = bf_round(mean), sd = bf_round(sqrt_ap(bf_round(bf_round(var) + 1e-5f)));
        const uint32_t idx = 2047 - (128 * (tile & 14) + 32 * r + 16 * (tile & 1) + 8 * (mi >> 1) + 2 * wj + (mi & 1));
        const uint32_t rb = pack_bf(0.f, (dot - mu * wsum) * rcpf(sd));
        uint2 v = make_uint2((__float_as_uint(mu) >> 16) | __float_as_uint(sd), (((rb ^ (((int)rb >> 31) | 0x80000000u)) >> 1) & 0x7FFF8000u) | (tag << 31) | idx);
        uint2* const dst = &p.s->stat[256 * r + 16 * tile];
        if (extra) {
            if (j == 0) st_rlx2(dst + 4 * wj + mi, v.x, v.y);
        } else {
        const uint32_t ga = S + SM_B + 3200 + 32 * wj;
        if (j == 0) sts64(ga + 8 * mi, v.x, v.y);
        bar_sync(15, 128);
        if (tid < 272) {
            v = lds64(ga + 8 * lane);
            st_rlx2(dst + lane, v.x, v.y);
        }
        if (lane == 0) mbar_arrive(S + (B_EMPTY + 10) * 8);
        }
    }

    auto first = [&]() {
        const int q = warp - 13;
        const uint32_t epoch = ld_rlx(&p.s->ep[bid * 8]);
        const uint2* sp = &p.s->stat[256 * r + 32 * q + lane];
        const uint32_t xb = mapa(S, g), xd = xb + SM_CH + xslot(8 + 2 * r + (t >> 1), t & 1) + 512 * q;
        asm volatile("barrier.cluster.wait.aligned;" ::: "memory");
        mbar_wait_short(S + B_RAW * 8);
        uint32_t a[5][4];
#pragma unroll
        for (int n = 0; n < 5; n++) ldm4t(S + SM_RAW + (64 * mi + j + 8 * q) * PITCH + 16 * n, a[n]);
        uint2 v;
#pragma unroll 1
        for (int it = 0; it < SPIN_LIMIT; it++) {
            v = ld_rlx2(sp);
            if ((int)(v.y ^ (epoch << 31)) < 0) break;
        }
        bar_arrive(13, 224);
        const float ri = 0.5f * rcpf(bf_hi(v.x));
        sts64(S + SM_ST + 256 * q + 16 * (lane & 12) + 2 * (lane & 16) + 8 * t, __float_as_uint(ri), __float_as_uint(-bf_lo(v.x) * ri));
        __syncwarp();
        uint4 s[4];
#pragma unroll
        for (int e = 0; e < 4; e++) s[e] = lds128(S + SM_ST + 256 * q + 16 * t + 64 * e);
#pragma unroll
        for (int n = 0; n < 5; n++) {
            if (n == nch) break;
#pragma unroll
            for (int e = 0; e < 4; e++)
                a[n][e] = pack_h(fmaf(bf_lo(a[n][e]), __uint_as_float(s[e].x), __uint_as_float(s[e].y)), fmaf(bf_hi(a[n][e]), __uint_as_float(s[e].z), __uint_as_float(s[e].w)));
            st_async4(xd + n * CH, a[n][0], a[n][1], a[n][2], a[n][3], xb + B_X * 8);
        }
    };
    if (k < nch) {
        const uint32_t cb = S + SM_CH + k * CH, scr = cb + BOX + 3072 * half, oth = cb + BOX + 3072 - 3072 * half;
        float d[5][4], k0;
        kp.dsk = __shfl_sync(~0u, kp.ldt, 1);
        kp.ldt = __shfl_sync(~0u, kp.ldt, 0);
        const uint32_t eb = kgen(kp, scr, oth, 1 + k, lane, d, k0, k > 7 - nch ? 3 - 2 * half : 2, ((p.tn.stag >> (warp + 16 - 16 * pair)) & 1) ? S + (B_EMPTY + 10) * 8 : 0, p.tn.zero);
        __syncwarp();
#pragma unroll
        for (int i = 0; i < 5; i++)
            if (half == (i < 3)) sts128f(kp.sa + i * 512, d[i][0], d[i][1], d[i][2], d[i][3]);
        auto both = [&](int i) {
            const uint4 v = lds128(oth + i * 512 + lane * 16);
            d[i][0] += __uint_as_float(v.x); d[i][1] += __uint_as_float(v.y); d[i][2] += __uint_as_float(v.z); d[i][3] += __uint_as_float(v.w);
        };
        if (half) {
            bar_arrive(1 + k, 64);
            if (early) first();
            bar_sync(6 + k, 64);
            both(3); both(4);
            const uint32_t o = cb + FT + 56 + 2 * lane, q = cb + pre[6];
#pragma unroll
            for (int e = 0; e < 2; e++) {
                const uint32_t a = pack_h(d[3][e], d[3][2 + e]), b = pack_h(d[4][e], d[4][2 + e]);
                sts16(o + 128 - 128 * e, a); sts16(o + 192 - 128 * e, a >> 16);
                sts16(q + 64 - 64 * e, b); sts16(q + 96 - 64 * e, b >> 16);
            }
            __syncwarp();
        } else {
            {
                bar_sync(1 + k, 64);
                both(0); both(1); both(2);
                const uint32_t a[2] = {pack_h(d[0][0], d[1][0]), pack_h(d[0][2], d[1][2])}, b[2] = {pack_h(d[0][1], d[1][1]), pack_h(d[0][3], d[1][3])};
                const uint32_t c[2] = {pack_h(d[2][0], d[2][1]), pack_h(d[2][2], d[2][3])};
                bar_arrive(6 + k, 64);
                uint32_t last = pack_h(k0, k0);
                const uint32_t o = cb + TAB + 32 + 16 * lane;
                sts16(cb + TAB + 28, last);
#pragma unroll
                for (int h = 0; h < 4; h++) {
                    const uint32_t e = h < 2 ? b[h] : c[h - 2], pv = __shfl_sync(~0u, lane == 31 ? last : e, lane - 1);
                    if (h < 2) sts128(o + 512 * h, prmt(a[h], pv, 0x7610), prmt(a[h], 0, 0x1032), prmt(e, a[h], 0x7610), prmt(e, 0, 0x1032));
                    else sts128(o + 512 * h, prmt(pv, 0, 0x3232), prmt(e, pv, 0x7610), prmt(e, 0, 0x1032), prmt(e, 0, 0x3232));
                    last = e;
                }
                if (lane == 31) sts128(o + 1552, prmt(last, 0, 0x3232), prmt(last, 0, 0x3232), last & 0xFFFF0000u, 0u);
                __syncwarp();
            }
            near_lags(S, k, 64 * r + 16 * ((2 * k + (cbase >> 2) + (r >> 2)) & 3), eb, pre, p.tn.c256);
            return;
        }
    }

    const int ph0 = pair & ~r, f0 = pair ? 32 * (bid & ~1) + 768 : 64 * bid;
    if (k == 7) {
        first();
        spin_until(t0, p.tn.t_pf);
#pragma unroll 1
        for (int e = tid - 224; e < 576; e += 64) {
            asm volatile("prefetch.global.L2 [%0];" ::"l"(p.wg + e * F_ + f0) : "memory");
            __nanosleep(100);
        }
        return;
    }
    if (warp == 12) {
        if (lane < 27) mbar_expect(S + (B_FULL + lane) * 8, lane < 18 - 9 * pair ? 8192 : 128 * 40);
        __syncwarp();
        if (elect()) {
            asm volatile("prefetch.tensormap [%0];" ::"l"(m.w + ph0) : "memory");
            asm volatile("prefetch.tensormap [%0];" ::"l"(&m.u) : "memory");
            spin_until(t0, p.tn.t_tile);
            auto raw = [&]() {
                mbar_expect(S + B_RAW * 8, 256 * PITCH);
                asm volatile("cp.async.bulk.tensor.5d.shared::cluster.global.mbarrier::complete_tx::bytes [%0], [%1, {%3, 0, %4, 0, 0}], [%2];"
                             ::"r"(S + SM_RAW), "l"(&m.u), "r"(S + B_RAW * 8), "r"(cbase), "r"(4 * r) : "memory");
            };
            raw();
            uint32_t bar = S + B_FULL * 8, dst = S + SM_W, em = 0x1249400u, wm = pair ? p.tn.win5 : p.tn.win4, wb = bar;
#pragma unroll 1
            for (int ph = ph0; ph < 3; ph += 1 + (pair & r)) {
                const int c0 = ph < 2 ? f0 : cbase, c1 = ph < 2 ? 0 : 576 * r;
#pragma unroll 1
                for (int n = 0; n < 576; n += 64) {
                    if (em & 1) mbar_wait(bar + 8 * (B_EMPTY - B_FULL), 0);
                    wb += 8 * (wm & 3);
                    if (wm & 3) mbar_wait(wb - 8, 0);
                    tma2d(dst, m.w + ph, c0, c1 + n, bar);
                    bar += 8; em >>= 1; wm = wm >> 2 | 0x40000000u;
                    dst = dst == S + SM_W + (NRING - 1) * 8192 ? S + SM_W : dst + 8192;
                }
            }
        }
        return;
    }

    if (warp == 15) {
        asm volatile("barrier.cluster.wait.aligned;" ::: "memory");
        sts32(S + SM_SKIP + 4 * j, 0u);
        const uint32_t ob = mapa(S, g);
        bar_sync(13, 224);
        const uint4 ka = lds128(S + SM_B + 256 + 16 * lane), kb = lds128(S + SM_B + 768 + 16 * lane);
        uint32_t k0 = ka.x, k1 = ka.y, mine = 0, c = 0;
        int rank = lane;
#pragma unroll 1
        for (int pass = 0;; pass++) {
#pragma unroll 1
            for (int n = 0; n < (pass < 2 ? 4 : 8); n++) {
                const uint32_t a = __viaddmin_u32(k0, c, __viaddmin_u32(k1, c, ka.z + c)), b = __viaddmin_u32(ka.w, c, __viaddmin_u32(kb.x, c, kb.y + c));
                c += ~__reduce_min_sync(~0u, __vimin3_u32(a, b, __viaddmin_u32(kb.z, c, kb.w + c)));
                if ((pass < 2 ? t : j) == n) mine = c;
            }
            if (pass == 2) break;
            asm volatile("st.async.shared::cluster.mbarrier::complete_tx::bytes.b32 [%0], %1, [%2];" ::"r"(ob + SM_CAND + 128 * pass + 16 * r + 4 * t), "r"(~mine), "r"(ob + (B_TOP + pass) * 8) : "memory");
            mbar_wait_short(S + (B_TOP + pass) * 8);
            const uint32_t v = lds32(S + SM_CAND + 4 * lane);
            if (pass) {
                k0 = v; k1 = lds32(S + SM_CAND + 128 + 4 * lane); c = 0;
            } else {
                uint32_t cn[4] = {0, 0, 0, 0};
#pragma unroll 4
                for (int e = 0; e < 128; e += 16) {
                    const uint4 o = lds128(S + SM_CAND + e);
                    cn[0] += (o.x - v) >> 31; cn[1] += (o.y - v) >> 31; cn[2] += (o.z - v) >> 31; cn[3] += (o.w - v) >> 31;
                }
                const int rk = (cn[0] + cn[1]) + (cn[2] + cn[3]);
                if (!__any_sync(~0u, t == 3 && rk < 8)) { rank = rk; mine = ~v; break; }
            }
        }
        const uint32_t row = ~mine & 2047, ix = (row & 0xE0) * 8 + ((row >> 3) & 0xE0) + (row & 0x11) + ((row >> 2) & 2) + (row & 6) * 2;
        const uint32_t mr = __reduce_or_sync(~0u, rank == r ? row : 0u);
        if (elect()) {
            bulk_mc(S + SM_B + BP * r, p.u + mr * D_, 1152, S + B_XS * 8);
        }
        const bool own = rank < 8 && (ix >> 8) == r;
        const uint32_t m2 = 2 * mine, rb = (m2 ^ ((~(int)m2 >> 31) | 0x80000000u)) & 0xFFFF0000u;
        if (rank < 8) sts64(S + SM_SEL + 8 * rank, ix | rb, row | ((row & 0x700) + 32 * (row & 6) + 2 * (row & 24) + 8 * (row & 1)) << 16);
        if (own) asm volatile("red.shared.or.b32 [%0], %1;" ::"r"(S + SM_SKIP + 4 * (ix & 7)), "r"(1u << ((ix >> 3) & 31)) : "memory");
        const int no = __popc(__ballot_sync(~0u, own));
        if (lane < 2) mbar_expect(S + (B_FIN + lane) * 8, lane ? 0 : no * (nch - 2) * 256);
        __syncwarp();
        const uint2 sv = lds64(S + SM_SEL + 8 * j);
        float sa, sb;
        asm volatile("ld.shared::cluster.v2.f32 {%0, %1}, [%2];" : "=f"(sa), "=f"(sb) : "r"(mapa(S + SM_ST + (sv.y >> 16), (sv.x >> 8) & 7)) : "memory");
        const float m1 = -sb * rcpf(sa);
        sts32(S + SM_PROG + 32 + 4 * (lane & 15), mi & 1 ? pack_bf(m1, m1) : __float_as_uint(sa + sa));
        bar_arrive(14, 160);
    }

    if (svcwarp) {
        const uint32_t tag = ~epoch & 1;
        const int fw = warp & 3, i = tid & 127;
        uint32_t xbar = mapa(S + B_X * 8 + 8, g), xd = keep(xbar - B_X * 8 - 8 + SM_CH + xslot(8 + 2 * r + (t >> 1), t & 1) + 256 * (fw & 2) + 1024);
        uint32_t ra = keep(S + SM_RAW + (64 * mi + j + 4 * (fw & 2) + 16) * PITCH), sa = keep(S + SM_ST + 16 * t + 128 * (fw & 2) + 512);
        const uint32_t ta = keep(S + SM_ST + 16 * (i & 0x71) + 32 * (i & 6) + 4 * (i & 8));
        asm volatile("barrier.cluster.wait.aligned;" ::: "memory");
        mbar_wait_short(S + B_RAW * 8);
#pragma unroll 1
        for (int it = 0; it < SPIN_LIMIT && (int)((sw.y ^ -tag) | (sw.w ^ -tag)) < 0; it++) sw = ld_rlx4(sp);
        sts64(S + SM_B + 256 + 8 * i, ~sw.y, ~sw.w);
        {
            const float r0 = 0.5f * rcpf(bf_hi(sw.x)), r1 = 0.5f * rcpf(bf_hi(sw.z));
            sts128f(ta, r0, -bf_lo(sw.x) * r0, r1, -bf_lo(sw.z) * r1);
        }
        bar_sync(13, 224);
        {
#pragma unroll 1
            for (int u = fw; u < fw + 3; u++) {
                uint4 s[4];
#pragma unroll
                for (int e = 0; e < 4; e++) s[e] = lds128(sa + 64 * e);
#pragma unroll 1
                for (int n = u & 1; n < nch; n += 2) {
                    uint32_t a[4];
                    ldm4t(ra + 16 * n, a);
#pragma unroll
                    for (int e = 0; e < 4; e++)
                        a[e] = pack_h(fmaf(bf_lo(a[e]), __uint_as_float(s[e].x), __uint_as_float(s[e].y)), fmaf(bf_hi(a[e]), __uint_as_float(s[e].z), __uint_as_float(s[e].w)));
                    st_async4(xd + n * CH, a[0], a[1], a[2], a[3], xbar);
                }
                xd += 1024; ra += 16 * PITCH; sa += 512; xbar += 8;
            }
        }
        if (i == 0) st_rlx(&p.s->ep[bid * 8], epoch + 1);
        const int mt = (fw + 3) & 3;
        const uint32_t aa = keep(S + SM_W + 2048 * fw + (8 * (mi >> 1) + j) * 128 + (((mi & 1) ^ j) << 4)), rd = S + SM_B + 16 * lane;
        uint32_t bar = keep(S + B_FULL * 8 + 8 * min(lane, 2)), of = 0, b[18], k0, k1;
        auto fetch = [&](auto nt, uint32_t (&a)[12][4]) {
            mbar_wait(bar, 0);
            __syncwarp();
#pragma unroll
            for (int e = 0; e < 3 * nt.value; e++) ldm4t((aa ^ (32 * (e % nt.value))) + of + 8192 * (e / nt.value), a[e]);
            if (nt.value == 4 && lane == 0) mbar_arrive(min(bar + (B_EMPTY + NRING - B_FULL) * 8, S + 63 * 8) | (a[11][0] & p.tn.zero));
            bar += 24;
            of = of == 8192 * (NRING - 3) ? 0 : of + 24576;
        };
        float d[4][4];
        auto mul = [&](auto nt, int n, const uint32_t (&a)[12][4]) {
#pragma unroll
            for (int e = 0; e < 3 * nt.value; e++) mma_bf(d[e % nt.value], a[e][0], a[e][1], a[e][2], a[e][3], b[6 * n + 2 * (e / nt.value)], b[6 * n + 2 * (e / nt.value) + 1]);
        };
        auto sum = [&](auto nt, float r0, float r1) {
            bar_sync(15, 128);
#pragma unroll
            for (int e = 0; e < nt.value; e++) sts128f(rd + 2048 * e + 512 * fw, d[e][0], d[e][1], d[e][2], d[e][3]);
            bar_sync(15, 128);
            uint4 v[4];
#pragma unroll
            for (int e = 0; e < 4; e++) v[e] = lds128(rd + 2048 * mt + 512 * e);
#define F4(c) ((__uint_as_float(v[0].c) + __uint_as_float(v[1].c)) + (__uint_as_float(v[2].c) + __uint_as_float(v[3].c)))
            k0 = pack_bf(F4(x) * r0, F4(y) * r1); k1 = pack_bf(F4(z) * r0, F4(w) * r1);
        };
        uint32_t a0[12][4], a1[12][4];
        fetch(Int<4>(), a0);
        bar_sync(14, 160);
        const uint2 sv = lds64(S + SM_SEL + 8 * j);
        {
            const uint32_t mu = lds32(S + SM_PROG + 64 + 4 * g), ba = S + SM_B + BP * j + 32 * fw + 16 * (mi & 1) + 128 * (mi >> 1);
            mbar_wait_short(S + B_XS * 8);
#pragma unroll
            for (int e = 0; e < 4; e++) ldm4(ba + 256 * e, b[4 * e], b[4 * e + 1], b[4 * e + 2], b[4 * e + 3]);
            ldm2(ba + 1024, b[16], b[17]);
#pragma unroll
            for (int e = 0; e < 18; e++) b[e] = bsub(b[e], mu);
        }
        const uint32_t tx = clk32();
#pragma unroll 1
        for (int ph = ph0;; ph++) {
#pragma unroll
            for (int e = 0; e < 4; e++) d[0][e] = d[1][e] = d[2][e] = d[3][e] = 0.f;
            mul(Int<4>(), 0, a0);
            fetch(Int<4>(), a0);
            mul(Int<4>(), 1, a0);
            fetch(Int<4>(), a0);
            mul(Int<4>(), 2, a0);
            if (!pair && !ph) fetch(Int<4>(), a0);
            const uint2 ri = lds64(S + SM_PROG + 32 + 8 * t);
            sum(Int<4>(), __uint_as_float(ri.x), __uint_as_float(ri.y));
            const uint32_t ea = SM_FIN + 6144 + 8 * i, eb = B_UP * 8;
            if (ph == 0) {
                const uint32_t ob = mapa(S, r & ~pair);
                st_async2(ob + ea, k0, k1, ob + eb);
                if (pair) break;
            } else {
                k0 = pack_bf(silu_half(0.5f * bf_lo(k0)), silu_half(0.5f * bf_hi(k0))); k1 = pack_bf(silu_half(0.5f * bf_lo(k1)), silu_half(0.5f * bf_hi(k1)));
                mbar_wait_short((S + eb) | (k0 & k1 & p.tn.zero));
                const uint2 v = lds64(S + ea);
                __syncwarp();
                st_rlx2(p.s->h + 4 * f0 + 64 * mt + 2 * lane, (movm(bmul(k0, v.x)) & ~1u) | tag, movm(bmul(k1, v.y)));
                break;
            }
        }
        {
            fetch(Int<3>(), a0);
            fetch(Int<3>(), a1);
            spin_until(tx, p.tn.da);
            const uint32_t* const hp = p.s->h + 2304 * r + 2 * i;
#pragma unroll 1
            for (int it = 0; it < SPIN_LIMIT; it++) {
#pragma unroll
                for (int e = 0; e < 9; e++) { const uint2 v = ld_rlx2(hp + 256 * e); b[2 * e] = v.x; b[2 * e + 1] = v.y; }
                const uint32_t tm = -tag;
                if (!(((lop_ne(b[0], b[2], tm) | lop_ne(b[4], b[6], tm) | lop_ne(b[8], b[10], tm)) | lop_ne(b[12], b[14], tm) | (b[16] ^ tm)) & 1)) break;
            }
            __syncwarp();
#pragma unroll
            for (int e = 0; e < 4; e++) d[0][e] = d[1][e] = d[2][e] = 0.f;
            mul(Int<3>(), 0, a0);
            fetch(Int<3>(), a0);
            mul(Int<3>(), 1, a1);
            mul(Int<3>(), 2, a0);
            sum(Int<3>(), 1.f, 1.f);
            if (mt < nch - 2) {
                const uint32_t ob = mapa(S, (__shfl_sync(~0u, sv.x, g) >> 8) & 7);
                st_async2(ob + SM_FIN + 768 * g + 96 * r + 32 * mt + 8 * t, movm(k0), movm(k1), ob + B_FIN * 8);
            }
        }
        const int l = min(lane, 4 * nch - 1);
        int n = fw;
#pragma unroll 1
        for (uint32_t own = __ballot_sync(~0u, ((sv.x >> 8) & 7) == r) & 255; own; own &= own - 1) {
            if (n-- & 3) continue;
            const int tk = __ffs(own) - 1;
            const uint2 e = lds64(S + SM_SEL + 8 * tk), st = lds64(S + SM_ST + (e.y >> 16));
            const uint32_t ix = e.x, x = lds32(S + SM_RAW + (16 * (ix & 12) + ((ix >> 2) & 60) + (ix & 3)) * PITCH + 4 * l);
            const uint32_t yb = S + SM_CH + YIN + (l >> 2) * CH + 16 * (ix & 0xE0) + 128 * (l & 3) + 16 * (((ix >> 3) ^ ((l >> 1) + (cbase >> 2))) & 3) + 2 * (ix & 7);
            const float sg = 0.5f * sigm(bf_hi(ix));
            const uint32_t hx = pack_bf(fmaf(bf_lo(x), __uint_as_float(st.x), __uint_as_float(st.y)), fmaf(bf_hi(x), __uint_as_float(st.x), __uint_as_float(st.y))), sg2 = pack_bf(sg, sg);
            mbar_wait((S + B_FIN * 8) | (hx & sg2 & p.tn.zero), 0);
            float a[2] = {0.f, 0.f}, b[2] = {0.f, 0.f};
#pragma unroll
            for (int q = 0; q < 8; q++) {
                const uint32_t v = lds32(S + SM_FIN + 768 * tk + 96 * q + 4 * (l & 24) + 8 * (l & 3) + (l & 4));
                a[q & 1] += bf_lo(v); b[q & 1] += bf_hi(v);
            }
            const uint32_t hv = badd(hx, bmul(pack_bf(a[0] + a[1], b[0] + b[1]), sg2)), gt = pack_bf(silu_half(bf_lo(hv)), silu_half(bf_hi(hv)));
            mbar_wait((S + B_Y * 8 + ((ix >> 2) & 56)) | (gt & p.tn.zero), 0);
            *(uint32_t*)(p.out + (e.y & 2047) * D_ + cbase + 2 * l) = bfma(lds16(yb) | (lds16(yb + 64) << 16), gt, x);
        }
        return;
    }

    mbar_wait(S + B_X * 8, 0);
    if (k < nch) {
        const uint32_t cb = S + SM_CH + k * CH, bx = cb + BOX + 16;
        float u[4][4], v[4][4], w[4][4];
#pragma unroll
        for (int i = 0; i < 4; i++) v[i][0] = v[i][1] = v[i][2] = v[i][3] = w[i][0] = w[i][1] = w[i][2] = w[i][3] = 0.f;
        uint2 T4[10];
        const uint32_t ta = cb + FT + 4 * (g - t);
#pragma unroll
        for (int e = 0; e < 10; e++) T4[e] = lds64(ta + 24 + 32 * e + 4 * (g - t));
        const uint32_t tb = prmt(lds32(cb + FT + 308), 0, pre[7]);
        const uint32_t a4 = cb + pre[0], a8 = cb + pre[1], at = cb + pre[2], hb = cb + pre[3], o = bx + 16 * lane;
        uint32_t xi = cb + pre[4], xp = cb + pre[5], hs = cb + XX;
#pragma unroll 1
        for (int n = 9; n > 0; n -= 4) {
            {
                const uint4 hv = lds128(hs);
                hs = hb + 496;
                const uint2 v0 = lds64(xp + 8);
                const uint4 v1 = lds128(xp ^ 32), v2 = lds128(xi), v3 = lds128(xi ^ 32);
                xi += 1024; xp += 1024;
                __syncwarp();
                if (lane < 3) sts128(hb - 16, hv.x, hv.y, hv.z, hv.w);
                const uint32_t P[13] = {v0.x, v0.y, v1.x, v1.y, v1.z, v1.w, v2.x, v2.y, v2.z, v2.w, v3.x, v3.y, v3.z};
                uint32_t Q[12], s2[12], s4[10], b3[11], b5[9];
#pragma unroll
                for (int e = 0; e < 12; e++) { Q[e] = prmt(P[e], P[e + 1], 0x5432); s2[e] = hadd(P[e], Q[e]); }
#pragma unroll
                for (int e = 0; e < 11; e++) b3[e] = hadd(Q[e], s2[e + 1]);
#pragma unroll
                for (int e = 0; e < 10; e++) s4[e] = hadd(s2[e], s2[e + 1]);
#pragma unroll
                for (int e = 0; e < 9; e++) b5[e] = hadd(s4[e + 1], P[e + 3]);
                sts128(o, b3[3], b3[4], b3[5], b3[6]);
                sts128(o + 1152, b3[7], b3[8], b3[9], b3[10]);
                sts128(o + 576, b5[0], b5[1], b5[2], b5[3]);
                sts128(o + 1728, b5[4], b5[5], b5[6], b5[7]);
                if (n > 4) {
                    sts128(o + 4608, s2[4], s2[5], s2[6], s2[7]);
                    sts128(o + 5184, s2[8], s2[9], s2[10], s2[11]);
                    sts128(o + 2304, hadd(b3[0], s4[2]), hadd(b3[1], s4[3]), hadd(b3[2], s4[4]), hadd(b3[3], s4[5]));
                    sts128(o + 3456, hadd(b3[4], s4[6]), hadd(b3[5], s4[7]), hadd(b3[6], s4[8]), hadd(b3[7], s4[9]));
                    sts128(o + 4032, hadd(s4[0], b5[1]), hadd(s4[1], b5[2]), hadd(s4[2], b5[3]), hadd(s4[3], b5[4]));
                    sts128(o + 2896, hadd(s4[4], b5[5]), hadd(s4[5], b5[6]), hadd(s4[6], b5[7]), hadd(s4[7], b5[8]));
                }
                __syncwarp();
            }
            uint32_t A[8][4];
#pragma unroll
            for (int e = 0; e < 8; e++) ldm4t(a4 + 64 * e, A[e]);
#pragma unroll
            for (int e = 0; e < 8; e++)
#pragma unroll
                for (int b = 3; b >= e / 2; b--) {
                    const uint2 T = T4[2 * (b - e / 2) + 1 - (e & 1)];
                    if (e == 0) mma_hc(u[b], v[b], A[e][0], A[e][1], A[e][2], A[e][3], T.x, T.y);
                    else mma_h(u[b], A[e][0], A[e][1], A[e][2], A[e][3], T.x, T.y);
                }
            mbar_wait_short(S + (B_X + 3) * 8 - 2 * (n - 1));
            if (n == 9) bar_sync(1 + k, 64);
#pragma unroll
            for (int e = 0; e < 2; e++)
                stm4t(cb + TAB + 2304 - 256 * n + 512 * e + 16 * lane, pack_h(u[2 * e][0], u[2 * e][1]), pack_h(u[2 * e][2], u[2 * e][3]),
                      pack_h(u[2 * e + 1][0], u[2 * e + 1][1]), pack_h(u[2 * e + 1][2], u[2 * e + 1][3]));
            __syncwarp();
            sts32v(S + SM_PROG + 4 * k, n);
            if (n == 1) break;
            uint32_t C[4][4], E[2][4], T8[16];
#pragma unroll
            for (int e = 0; e < 4; e++) ldm4t(a8 + 128 * e, C[e]);
#pragma unroll
            for (int e = 0; e < 2; e++) ldm4t(at + 256 * e, E[e]);
#pragma unroll
            for (int e = 0; e < 8; e++) T8[e] = lds32(ta + 376 + 32 * (e >> 1) - 16 * (e & 1));
#pragma unroll
            for (int e = 7; e >= 0; e--)
#pragma unroll
                for (int b = 0; b <= e / 2; b++) {
                    const uint2 T = T4[2 * (4 + b - e / 2) + 1 - (e & 1)];
                    if (e == 7) mma_hc(v[b], w[b], A[e][0], A[e][1], A[e][2], A[e][3], T.x, T.y);
                    else mma_h(v[b], A[e][0], A[e][1], A[e][2], A[e][3], T.x, T.y);
                }
#pragma unroll
            for (int e = 3; e >= 0; e--) {
                mma_h8(v[e], E[e >> 1][2 * (e & 1)], E[e >> 1][2 * (e & 1) + 1], tb);
#pragma unroll
                for (int b = 3; b >= e; b--) mma_h(v[b], C[e][0], C[e][1], C[e][2], C[e][3], T8[2 * (b - e)], T8[2 * (b - e) + 1]);
            }
            if (n == 9) {
#pragma unroll
                for (int e = 8; e < 16; e++) T8[e] = lds32(ta + 376 + 32 * (e >> 1) - 16 * (e & 1));
#pragma unroll
                for (int e = 3; e >= 0; e--)
#pragma unroll
                    for (int b = 0; b < 4; b++) mma_h(w[b], C[e][0], C[e][1], C[e][2], C[e][3], T8[2 * (4 + b - e)], T8[2 * (4 + b - e) + 1]);
            }
        }
    }

  {
    int lane;
    asm volatile("mov.u32 %0, %%laneid;" : "=r"(lane));
    const int g = lane >> 2, t = lane & 3, mi = lane >> 3, j = lane & 7, sh = (cbase >> 3) & 1;
    mbar_wait_short(S + B_SEL * 8);
    if (k < nch - 2 || k == 5) {
        const int one = k == 2, st = k == 5 ? 1 : 2, kk = one ? 4 - 4 * sh : sh + 2 * st - 2;
        const int q0 = k == 1, qx = q0 + (one & (t >> 1)), cx = 16 * kk + 8 * (one ? t & 1 : t);
        uint32_t xa = S + SM_RAW + (16 * (g & 4) + (g & 3) + 8 * qx) * PITCH + cx, sa = S + SM_ST + 16 * (g & 4) + 8 * (g & 3) + 256 * qx, bar = S + (B_Y + qx) * 8;
        uint32_t ya = S + SM_CH + YIN + kk * CH + (j >> 2) * (one ? 512 : CH) + 128 * (j & 2) + 128 * (mi & 1) + 64 * (j & 1) + 512 * q0 +
                      16 * ((mi >> 1) ^ (one ? 2 * sh + ((j >> 1) & 1) : j >> 1));
        uint32_t sk = lds32(S + SM_SKIP + 4 * g) >> (4 * qx);
        const uint32_t y2 = ya ^ 32;
        char* const o0 = (char*)p.out + ((256 * qx + 32 * r + 4 * (g & 2) + 2 * (g >> 2) + (g & 1)) * D_ + cbase) * 2 + cx;
#pragma unroll 1
        for (uint32_t n = 0; n < 8; n += st) {
            asm volatile("" : "+r"(n));
            char* const o = o0 + n * (512 * D_);
            uint2 x[4];
            uint32_t gt[8], y[2][4];
#pragma unroll
            for (int e = 0; e < 4; e++) {
                x[e] = lds64(xa + 8 * PITCH * n + (128 * (e & 1) + 2 * (e & 2)) * PITCH);
                const uint2 s = lds64(sa + 256 * n + 128 * (e & 1) + 16 * (e & 2));
                const float a = __uint_as_float(s.x), b = __uint_as_float(s.y);
                gt[2 * e] = pack_bf(silu_half(fmaf(bf_lo(x[e].x), a, b)), silu_half(fmaf(bf_hi(x[e].x), a, b)));
                gt[2 * e + 1] = pack_bf(silu_half(fmaf(bf_lo(x[e].y), a, b)), silu_half(fmaf(bf_hi(x[e].y), a, b)));
            }
            mbar_wait((bar + 8 * n) | (((gt[0] | gt[1] | gt[2]) | (gt[3] | gt[4] | gt[5]) | (gt[6] | gt[7])) & p.tn.zero), 0);
            __syncwarp();
            ldm4t(ya + 512 * n, y[0]);
            ldm4t(y2 + 512 * n, y[1]);
#pragma unroll
            for (int e = 0; e < 4; e++)
                asm volatile("{.reg .pred p; setp.eq.u32 p, %3, 0;\n@p st.global.v2.u32 [%0], {%1, %2};}" ::"l"(o + (8 * (e & 1) + 16 * (e & 2)) * D_),
                             "r"(bfma(y[e >> 1][2 * (e & 1)], gt[2 * e], x[e].x)), "r"(bfma(y[e >> 1][2 * (e & 1) + 1], gt[2 * e + 1], x[e].y)), "r"((sk >> (4 * n)) & (1 << e)) : "memory");
        }
    }
  }
}

typedef CUresult (*EncodeFn)(CUtensorMap*, CUtensorMapDataType, cuuint32_t, void*, const cuuint64_t*, const cuuint64_t*, const cuuint32_t*,
                             const cuuint32_t*, CUtensorMapInterleave, CUtensorMapSwizzle, CUtensorMapL2promotion, CUtensorMapFloatOOBfill);

static void make2d(EncodeFn enc, CUtensorMap* m, const void* base, uint64_t cols, uint64_t rows, uint32_t bc = 64) {
    cuuint64_t gd[2] = {cols, rows};
    cuuint64_t gs[1] = {cols * 2};
    cuuint32_t bd[2] = {bc, 64}, es[2] = {1, 1};
    enc(m, CU_TENSOR_MAP_DATA_TYPE_BFLOAT16, 2, const_cast<void*>(base), gd, gs, bd, es, CU_TENSOR_MAP_INTERLEAVE_NONE, CU_TENSOR_MAP_SWIZZLE_128B,
        cols == D_ ? CU_TENSOR_MAP_L2_PROMOTION_NONE : CU_TENSOR_MAP_L2_PROMOTION_L2_128B, CU_TENSOR_MAP_FLOAT_OOB_FILL_NONE);
}

static void make5d(EncodeFn enc, CUtensorMap* m, const void* base, uint32_t cols, CUtensorMapSwizzle sw) {
    cuuint64_t gd[5] = {D_, 2, 32, 8, 4};
    cuuint64_t gs[4] = {D_ * 2, D_ * 16, D_ * 512, D_ * 4};
    cuuint32_t bd[5] = {cols, 2, 4, 8, 4}, es[5] = {1, 1, 1, 1, 1};
    enc(m, CU_TENSOR_MAP_DATA_TYPE_BFLOAT16, 5, const_cast<void*>(base), gd, gs, bd, es, CU_TENSOR_MAP_INTERLEAVE_NONE, sw,
        CU_TENSOR_MAP_L2_PROMOTION_NONE, CU_TENSOR_MAP_FLOAT_OOB_FILL_NONE);
}

static Tune g_tune = {2000, 0xFF00E0, 256, 1431654480, 1431635200, 1000, 3900, 4000, 1800, 0};

static int max_clusters() {
    cudaFuncSetAttribute(fused_kernel, cudaFuncAttributeMaxDynamicSharedMemorySize, SM_TOTAL);
    cudaLaunchConfig_t cfg = {};
    cudaLaunchAttribute at[1];
    at[0].id = cudaLaunchAttributeClusterDimension;
    at[0].val.clusterDim.x = 8; at[0].val.clusterDim.y = 1; at[0].val.clusterDim.z = 1;
    cfg.gridDim = dim3(NCTA); cfg.blockDim = dim3(NTHREADS); cfg.dynamicSmemBytes = SM_TOTAL; cfg.attrs = at; cfg.numAttrs = 1;
    int n = 0;
    if (cudaOccupancyMaxActiveClusters(&n, fused_kernel, &cfg) != cudaSuccess) { cudaGetLastError(); n = 0; }
    return n;
}

static bool launch(void* const* d_in, void* d_out) {
    static EncodeFn enc = nullptr;
    static Scratch* gs = nullptr;
    if (!enc) {
        void* fn = nullptr;
        cudaDriverEntryPointQueryResult qr;
        cudaGetDriverEntryPoint("cuTensorMapEncodeTiled", &fn, cudaEnableDefault, &qr);
        enc = (EncodeFn)fn;
        cudaFuncSetAttribute(fused_kernel, cudaFuncAttributeMaxDynamicSharedMemorySize, SM_TOTAL);
        cudaGetSymbolAddress((void**)&gs, g_s);
    }
    Hot p;
    Maps m;
    auto in = [&](int i) { return (const __nv_bfloat16*)d_in[i]; };
    bool ok = true;
    auto off = [&](const void* q) {
        const long long d = (const char*)q - (const char*)d_in[0];
        ok = ok && d / 256 * 256 == d && (int)(d / 256) == d / 256;
        return (int)(d / 256);
    };
    p.u = in(0); p.are = off(in(1)); p.aim = off(in(2)); p.bre = off(in(3)); p.bim = off(in(4)); p.cre = off(in(5)); p.cim = off(in(6));
    p.logdt = off(in(7)); p.dskip = off(in(8)); p.wr = off(in(10)); p.ep = off(gs->ep);
    if (!ok) return false;
    p.out = (__nv_bfloat16*)d_out;
    p.wg = in(11);
    p.tn = g_tune;
    p.s = gs;
    make2d(enc, &m.w[0], in(12), F_, D_);
    make2d(enc, &m.w[1], in(11), F_, D_);
    make2d(enc, &m.w[2], in(13), D_, F_, 40);
    make5d(enc, &m.u, in(0), 40, CU_TENSOR_MAP_SWIZZLE_NONE);
    fused_kernel<<<NCTA, NTHREADS, SM_TOTAL>>>(p, m);
    return true;
}

}

namespace v2 {

constexpr int L_ = 2048, D_ = 576, F_ = 4608;
constexpr int NDOWN = 72, NMAIN = 128, NCTA = 132, NTHREADS = 512;
constexpr int SPIN_LIMIT = 1 << 16;
constexpr uint32_t SLOT_FREE = 0x7FFFABCDu;

constexpr int SM_PART = 544;
constexpr int SM_RED = SM_PART;
constexpr int SM_STA = 2080;
constexpr int SM_ONES = 2176;
constexpr int SM_KINF = 2192;
constexpr int SM_RP = 2272;
constexpr int SM_XS = 2704;
constexpr int KR_STRIDE = 1296;
constexpr int SM_X0 = 12080, X0_STRIDE = 4512, X0_ODD = 2240;
constexpr int SM_KT = 30128, KT_STRIDE = 3584, KT_P4 = 2144, KT_P8 = 2896;
constexpr int SM_FAR = 44544, FAR_STRIDE = 11328;
constexpr int FB5 = 0, FB3 = 3328, FB9E = 6656, FB9O = 7824, FB7E = 8992, FB7O = 10160;
constexpr int SM_ROWS = SM_FAR, ROW_STRIDE = 1168;
constexpr int SM_STG = SM_FAR + 19968;
constexpr int KG_SCR = 3072;
constexpr int SM_EX = 89856;
constexpr int EX_KT = SM_EX + X0_STRIDE, EX_FAR = EX_KT + KT_STRIDE, EX_HAND = 109312;
constexpr int SM_W_DOWN = 90112, SM_W_BIG = 121856, STAGE = 6144;
constexpr int SM_W_LAST = 12288;
constexpr int SM_TOTAL = 232448;
constexpr int SM_EPOCH = 2528, SM_SKIP = 2536;
static_assert(SM_STG + 8 * KG_SCR <= SM_EX && SM_STG % 128 == 0 && EX_HAND % 128 == 0 && EX_FAR + FAR_STRIDE <= EX_HAND && EX_HAND + 12288 <= SM_W_BIG, "scratch");

enum { B_ROWS = 0, B_KG, B_X0, B_X1, B_BOX  , B_TAB, B_EM = 6, B_SP = 10, B_OUT = 14, B_H = 15, B_RED = 16, B_TAB1 = 17, B_XS = 18, B_GX = 19, B_YIN = 22, B_P1 = 26, B_FD, B_GU = 28, B_W = 34, B_COUNT = 58 };

struct Tune { short f_start, f_t3, w2, w2b, w3, t_xs, t_svc, t_marg, f_t2, w1, zero, pad; };

struct Scratch {
    uint32_t x[144 * 4096];
    uint32_t y[128 * 4608];
    uint32_t h[2][F_ * 4];
    uint32_t key[L_];
    uint32_t stat[L_];
    uint32_t sel[4][32];
    uint32_t cnt[17 * 32];
};
__device__ __align__(1024) Scratch g_s;

struct Hot {
    const __nv_bfloat16* u;
    Scratch* s;
    const __nv_bfloat16 *wr, *are, *aim, *bre, *bim, *cre, *cim, *logdt;
    Tune tn;
    const __nv_bfloat16 *dskip, *pwg, *pwu, *pwd;
    __nv_bfloat16* out;
};
struct Maps { CUtensorMap wg, wu, wd; };

__device__ __forceinline__ uint32_t smem_u32(const void* p) { return (uint32_t)__cvta_generic_to_shared(p); }
__device__ __forceinline__ void mbar_init(uint32_t b, int c) { asm volatile("mbarrier.init.shared::cta.b64 [%0], %1;" ::"r"(b), "r"(c) : "memory"); }
__device__ __forceinline__ void mbar_expect(uint32_t b, int bytes) { asm volatile("mbarrier.arrive.expect_tx.shared::cta.b64 _, [%0], %1;" ::"r"(b), "r"(bytes) : "memory"); }
__device__ __forceinline__ void mbar_arrive(uint32_t b) { asm volatile("mbarrier.arrive.shared::cta.b64 _, [%0];" ::"r"(b) : "memory"); }
__device__ __forceinline__ bool elect() { uint32_t d; asm volatile("{.reg .pred p; elect.sync _|p, 0xffffffff; selp.u32 %0,1,0,p;}" : "=r"(d)); return d; }
__device__ __forceinline__ bool mbar_test(uint32_t b, int par) {
    uint32_t d;
    asm volatile("{.reg .pred p; mbarrier.test_wait.parity.shared::cta.b64 p, [%1], %2; selp.u32 %0,1,0,p;}" : "=r"(d) : "r"(b), "r"(par) : "memory");
    return d;
}
#define WAIT_LOOP(ins) "{\n.reg .pred p;\n.reg .u32 n;\nmov.u32 n, 0;\nLW:\n" ins " p, [%0], %1;\n@p bra LD;\nadd.u32 n, n, 1;\nsetp.lt.u32 p, n, 16384;\n@p bra LW;\nLD:\n}"
__device__ __forceinline__ void mbar_wait(uint32_t b, int par) { asm volatile(WAIT_LOOP("mbarrier.try_wait.parity.shared::cta.b64")::"r"(b), "r"(par) : "memory"); }
__device__ __forceinline__ uint32_t mapa(uint32_t a, uint32_t rank) { uint32_t d; asm("mapa.shared::cluster.u32 %0, %1, %2;" : "=r"(d) : "r"(a), "r"(rank)); return d; }
__device__ __forceinline__ void bulk_g2s(uint32_t dst, const void* src, int bytes, uint32_t bar) {
    asm volatile("cp.async.bulk.shared::cluster.global.mbarrier::complete_tx::bytes [%0], [%1], %2, [%3];" ::"r"(dst), "l"(src), "r"(bytes), "r"(bar) : "memory");
}
__device__ __forceinline__ void tma2d(uint32_t dst, const CUtensorMap* m, int c0, int c1, uint32_t bar) {
    asm volatile("cp.async.bulk.tensor.2d.shared::cluster.global.mbarrier::complete_tx::bytes [%0], [%1, {%3, %4}], [%2];" ::"r"(dst), "l"(m), "r"(bar), "r"(c0), "r"(c1) : "memory");
}
__device__ __forceinline__ void pf_tmap(const CUtensorMap* m) { asm volatile("prefetch.tensormap [%0];" ::"l"(m) : "memory"); }
__device__ __forceinline__ void bar_sync(int id, int n) { asm volatile("bar.sync %0, %1;" ::"r"(id), "r"(n) : "memory"); }
__device__ __forceinline__ uint4 ld_rlx4(const void* p) { uint4 v; asm volatile("ld.relaxed.gpu.global.v4.u32 {%0,%1,%2,%3}, [%4];" : "=r"(v.x), "=r"(v.y), "=r"(v.z), "=r"(v.w) : "l"(p) : "memory"); return v; }
__device__ __forceinline__ uint32_t ld_rlx(const void* p) { uint32_t v; asm volatile("ld.relaxed.gpu.global.u32 %0, [%1];" : "=r"(v) : "l"(p) : "memory"); return v; }
__device__ __forceinline__ void st_rlx(void* p, uint32_t v) { asm volatile("st.relaxed.gpu.global.u32 [%0], %1;" ::"l"(p), "r"(v) : "memory"); }
__device__ __forceinline__ uint32_t lds32(uint32_t a) { uint32_t v; asm volatile("ld.shared.u32 %0, [%1];" : "=r"(v) : "r"(a) : "memory"); return v; }
__device__ __forceinline__ uint32_t lds32v(uint32_t a) { uint32_t v; asm volatile("ld.volatile.shared.u32 %0, [%1];" : "=r"(v) : "r"(a) : "memory"); return v; }
__device__ __forceinline__ uint4 lds128v(uint32_t a) { uint4 v; asm volatile("ld.volatile.shared.v4.u32 {%0,%1,%2,%3}, [%4];" : "=r"(v.x), "=r"(v.y), "=r"(v.z), "=r"(v.w) : "r"(a) : "memory"); return v; }
__device__ __forceinline__ uint32_t lds16(uint32_t a) { uint16_t v; asm volatile("ld.shared.u16 %0, [%1];" : "=h"(v) : "r"(a) : "memory"); return v; }
__device__ __forceinline__ uint2 lds64(uint32_t a) { uint2 v; asm volatile("ld.shared.v2.u32 {%0,%1}, [%2];" : "=r"(v.x), "=r"(v.y) : "r"(a) : "memory"); return v; }
__device__ __forceinline__ uint4 lds128(uint32_t a) { uint4 v; asm volatile("ld.shared.v4.u32 {%0,%1,%2,%3}, [%4];" : "=r"(v.x), "=r"(v.y), "=r"(v.z), "=r"(v.w) : "r"(a) : "memory"); return v; }
__device__ __forceinline__ void sts16(uint32_t a, uint32_t v) { asm volatile("st.shared.u16 [%0], %1;" ::"r"(a), "h"((uint16_t)v) : "memory"); }
__device__ __forceinline__ void sts32(uint32_t a, uint32_t v) { asm volatile("st.shared.u32 [%0], %1;" ::"r"(a), "r"(v) : "memory"); }
__device__ __forceinline__ void sts64(uint32_t a, uint32_t x, uint32_t y) { asm volatile("st.shared.v2.u32 [%0], {%1,%2};" ::"r"(a), "r"(x), "r"(y) : "memory"); }
__device__ __forceinline__ void sts128(uint32_t a, uint32_t x, uint32_t y, uint32_t z, uint32_t w) { asm volatile("st.shared.v4.u32 [%0], {%1,%2,%3,%4};" ::"r"(a), "r"(x), "r"(y), "r"(z), "r"(w) : "memory"); }
__device__ __forceinline__ void st_async32(uint32_t a, uint32_t v, uint32_t bar) {
    asm volatile("st.async.shared::cluster.mbarrier::complete_tx::bytes.b32 [%0], %1, [%2];" ::"r"(a), "r"(v), "r"(bar) : "memory");
}
__device__ __forceinline__ void ldm4(uint32_t a, uint32_t& r0, uint32_t& r1, uint32_t& r2, uint32_t& r3) {
    asm volatile("ldmatrix.sync.aligned.m8n8.x4.shared.b16 {%0,%1,%2,%3}, [%4];" : "=r"(r0), "=r"(r1), "=r"(r2), "=r"(r3) : "r"(a) : "memory");
}
__device__ __forceinline__ void ldm4t(uint32_t a, uint32_t& r0, uint32_t& r1, uint32_t& r2, uint32_t& r3) {
    asm volatile("ldmatrix.sync.aligned.m8n8.x4.trans.shared.b16 {%0,%1,%2,%3}, [%4];" : "=r"(r0), "=r"(r1), "=r"(r2), "=r"(r3) : "r"(a) : "memory");
}
__device__ __forceinline__ void ldm2(uint32_t a, uint32_t& r0, uint32_t& r1) {
    asm volatile("ldmatrix.sync.aligned.m8n8.x2.shared.b16 {%0,%1}, [%2];" : "=r"(r0), "=r"(r1) : "r"(a) : "memory");
}
__device__ __forceinline__ void stm4(uint32_t a, uint32_t r0, uint32_t r1, uint32_t r2, uint32_t r3) {
    asm volatile("stmatrix.sync.aligned.m8n8.x4.shared.b16 [%0], {%1,%2,%3,%4};" ::"r"(a), "r"(r0), "r"(r1), "r"(r2), "r"(r3) : "memory");
}
__device__ __forceinline__ void mma_bf(float& c0, float& c1, float& c2, float& c3, uint32_t a0, uint32_t a1, uint32_t a2, uint32_t a3, uint32_t b0, uint32_t b1) {
    asm volatile("mma.sync.aligned.m16n8k16.row.col.f32.bf16.bf16.f32 {%0,%1,%2,%3},{%4,%5,%6,%7},{%8,%9},{%0,%1,%2,%3};"
                 : "+f"(c0), "+f"(c1), "+f"(c2), "+f"(c3) : "r"(a0), "r"(a1), "r"(a2), "r"(a3), "r"(b0), "r"(b1));
}
__device__ __forceinline__ void mma_bf(float (&c)[4], uint32_t a0, uint32_t a1, uint32_t a2, uint32_t a3, uint32_t b0, uint32_t b1) { mma_bf(c[0], c[1], c[2], c[3], a0, a1, a2, a3, b0, b1); }
__device__ __forceinline__ void mma_h(float (&c)[4], uint32_t a0, uint32_t a1, uint32_t a2, uint32_t a3, uint32_t b0, uint32_t b1) {
    asm volatile("mma.sync.aligned.m16n8k16.row.col.f32.f16.f16.f32 {%0,%1,%2,%3},{%4,%5,%6,%7},{%8,%9},{%0,%1,%2,%3};"
                 : "+f"(c[0]), "+f"(c[1]), "+f"(c[2]), "+f"(c[3]) : "r"(a0), "r"(a1), "r"(a2), "r"(a3), "r"(b0), "r"(b1));
}
__device__ __forceinline__ void mma_bf8(float (&c)[4], uint32_t a0, uint32_t a1, uint32_t b0) {
    asm volatile("mma.sync.aligned.m16n8k8.row.col.f32.bf16.bf16.f32 {%0,%1,%2,%3},{%4,%5},{%6},{%0,%1,%2,%3};"
                 : "+f"(c[0]), "+f"(c[1]), "+f"(c[2]), "+f"(c[3]) : "r"(a0), "r"(a1), "r"(b0));
}
__device__ __forceinline__ uint32_t pack_bf(float lo, float hi) { uint32_t r; asm("cvt.rn.bf16x2.f32 %0, %1, %2;" : "=r"(r) : "f"(hi), "f"(lo)); return r; }
__device__ __forceinline__ uint32_t pack_h(float lo, float hi) { uint32_t r; asm("cvt.rn.f16x2.f32 %0, %1, %2;" : "=r"(r) : "f"(hi), "f"(lo)); return r; }
__device__ __forceinline__ float bf_lo(uint32_t w) { return __uint_as_float(w << 16); }
__device__ __forceinline__ float bf_hi(uint32_t w) { return __uint_as_float(w & 0xFFFF0000u); }
__device__ __forceinline__ float bf_round(float x) { return bf_lo(pack_bf(x, 0.f)); }
__device__ __forceinline__ uint32_t badd(uint32_t a, uint32_t b) { uint32_t r; asm("add.rn.bf16x2 %0, %1, %2;" : "=r"(r) : "r"(a), "r"(b)); return r; }
__device__ __forceinline__ uint32_t bsub(uint32_t a, uint32_t b) { uint32_t r; asm("sub.rn.bf16x2 %0, %1, %2;" : "=r"(r) : "r"(a), "r"(b)); return r; }
__device__ __forceinline__ uint32_t bmul(uint32_t a, uint32_t b) { uint32_t r; asm("mul.rn.bf16x2 %0, %1, %2;" : "=r"(r) : "r"(a), "r"(b)); return r; }
__device__ __forceinline__ uint32_t bfma(uint32_t a, uint32_t b, uint32_t c) { uint32_t r; asm("fma.rn.bf16x2 %0, %1, %2, %3;" : "=r"(r) : "r"(a), "r"(b), "r"(c)); return r; }
__device__ __forceinline__ uint32_t prmt(uint32_t a, uint32_t b, uint32_t s) { uint32_t r; asm("prmt.b32 %0, %1, %2, %3;" : "=r"(r) : "r"(a), "r"(b), "r"(s)); return r; }
__device__ __forceinline__ float ex2f(float x) { float r; asm("ex2.approx.ftz.f32 %0, %1;" : "=f"(r) : "f"(x)); return r; }
__device__ __forceinline__ float rcpf(float x) { float r; asm("rcp.approx.ftz.f32 %0, %1;" : "=f"(r) : "f"(x)); return r; }
__device__ __forceinline__ float silu_f(float x) { return x * rcpf(1.f + ex2f(-1.4426950408889634f * x)); }
__device__ __forceinline__ uint32_t norm2(uint32_t x, uint32_t m, uint32_t hi, uint32_t lo) { uint32_t d = bsub(x, m); return bfma(d, hi, bmul(d, lo)); }
__device__ __forceinline__ uint32_t clk32() { uint32_t c; asm volatile("mov.u32 %0, %%clock;" : "=r"(c)); return c; }
__device__ __forceinline__ void spin_until(uint32_t t0, int dt) {
#pragma unroll 1
    while ((int)(clk32() - t0) < dt) __nanosleep(32);
}
__device__ __forceinline__ float sqrt_ap(float x) { float r; asm("sqrt.approx.ftz.f32 %0, %1;" : "=f"(r) : "f"(x)); return r; }

__device__ __forceinline__ void cp16(uint32_t dst, const void* src) { asm volatile("cp.async.cg.shared.global [%0], [%1], 16;" ::"r"(dst), "l"(src) : "memory"); }
__device__ __forceinline__ void pf_l2(const void* p) { asm volatile("cp.async.bulk.prefetch.L2.global [%0], 16;" ::"l"(p) : "memory"); }
__device__ __forceinline__ void bulk_s2g(void* dst, uint32_t src, int bytes) {
    asm volatile("cp.async.bulk.global.shared::cta.bulk_group [%0], [%1], %2;" ::"l"(dst), "r"(src), "r"(bytes) : "memory");
}
__device__ __forceinline__ uint32_t ld_acq(const void* p) { uint32_t v; asm volatile("ld.acquire.gpu.global.u32 %0, [%1];" : "=r"(v) : "l"(p) : "memory"); return v; }
__device__ __forceinline__ void red_add(void* p) { asm volatile("red.relaxed.gpu.global.add.u32 [%0], 1;" ::"l"(p) : "memory"); }
__device__ __forceinline__ void fence_async() { asm volatile("fence.proxy.async.shared::cta;" ::: "memory"); }
__device__ __forceinline__ void fence_async_g() { asm volatile("fence.proxy.async.global;" ::: "memory"); }
__device__ __forceinline__ void red_rel(void* p) { asm volatile("red.release.gpu.global.add.u32 [%0], 1;" ::"l"(p) : "memory"); }
__device__ __forceinline__ void wait_count(const uint32_t* p, uint32_t want) {
#pragma unroll 1
    for (int it = 0; it < SPIN_LIMIT && ld_rlx(p) != want; it++) __nanosleep(20);
}
__device__ __forceinline__ uint32_t ld_stat(const uint32_t* p, uint32_t tag) {
    uint32_t v = 0;
#pragma unroll 1
    for (int it = 0; it < SPIN_LIMIT; it++) {
        v = ld_rlx(p);
        if ((v >> 31) == tag) break;
    }
    return v & 0x7FFFFFFFu;
}
__device__ __forceinline__ uint32_t hadd(uint32_t a, uint32_t b) { uint32_t r; asm("add.rn.f16x2 %0, %1, %2;" : "=r"(r) : "r"(a), "r"(b)); return r; }
__device__ __forceinline__ float h_lo(uint32_t w) { return __half2float(__ushort_as_half((unsigned short)w)); }
__device__ __forceinline__ float h_hi(uint32_t w) { return __half2float(__ushort_as_half((unsigned short)(w >> 16))); }
__device__ __forceinline__ uint32_t x0_chunk(uint32_t xb, int c) { return xb + ((c & 1) ? X0_ODD + 120 : 128) + 8 * c; }

struct cf { float x, y; };
__device__ __forceinline__ cf cmul(cf a, cf b) { return {a.x * b.x - a.y * b.y, a.x * b.y + a.y * b.x}; }
__device__ __forceinline__ cf csq(cf a) { return {a.x * a.x - a.y * a.y, (a.x + a.x) * a.y}; }
__device__ __forceinline__ cf cpow_direct(float zr2, float zi, float l) {
    const float mag = ex2f(zr2 * l), th = zi * l;
    return {mag * __cosf(th), mag * __sinf(th)};
}
__device__ __forceinline__ __half2 as_h2(uint32_t v) { return *reinterpret_cast<__half2*>(&v); }
__device__ __forceinline__ uint32_t as_u32(__half2 v) { return *reinterpret_cast<uint32_t*>(&v); }
struct hm { uint32_t v, s; };
__device__ __forceinline__ hm mk_hm(cf a) {
    const uint32_t v = pack_h(a.x, a.y);
    return {v, prmt(v, v, 0x1032) ^ 0x8000u};
}
__device__ __forceinline__ uint32_t hcmul(uint32_t x, hm y) {
    const __half2 xx = as_h2(x);
    return as_u32(__hfma2(__high2half2(xx), as_h2(y.s), __hmul2(__low2half2(xx), as_h2(y.v))));
}

struct KParams { uint32_t are, aim, bre, bim, cre, cim, ldt; };
__device__ __forceinline__ KParams kgen_load(const Hot& p, int ch, int half, int lane) {
    const uint32_t po = ch * 64 + half * 32 + lane;
    KParams k;
    k.are = __ldg((const uint32_t*)p.are + po); k.aim = __ldg((const uint32_t*)p.aim + po);
    k.bre = __ldg((const uint32_t*)p.bre + po); k.bim = __ldg((const uint32_t*)p.bim + po);
    k.cre = __ldg((const uint32_t*)p.cre + po); k.cim = __ldg((const uint32_t*)p.cim + po);
    k.ldt = __ldg((const uint16_t*)p.logdt + ch + (lane & p.tn.zero));
    return k;
}

__device__ __forceinline__ void kgen(KParams kp, uint32_t scr, uint32_t os, int c0, int c1, uint32_t pause) {
    const int lane = threadIdx.x & 31;
    const float dt = bf_round(ex2f(bf_lo(kp.ldt) * 1.4426950408889634f));
    const cf w0 = cmul({bf_lo(kp.cre), bf_lo(kp.cim)}, {dt * bf_lo(kp.bre), dt * bf_lo(kp.bim)});
    const cf w1 = cmul({bf_hi(kp.cre), bf_hi(kp.cim)}, {dt * bf_hi(kp.bre), dt * bf_hi(kp.bim)});
    uint32_t eb = __reduce_max_sync(~0u, __float_as_uint(fmaxf(fmaxf(fabsf(w0.x), fabsf(w0.y)), fmaxf(fabsf(w1.x), fabsf(w1.y))))) & 0x7F800000u;
    eb = min(max(eb, 0x00800000u), 0x7E800000u);
    const float sc = __uint_as_float(0x7F000000u - eb);
    float k0 = c0 ? 0.f : w0.x + w1.x;
#pragma unroll
    for (int o = 16; o > 0; o >>= 1) k0 += __shfl_xor_sync(~0u, k0, o);
    float d[5][4];
#pragma unroll
    for (int i = 0; i < 5; i++) d[i][0] = d[i][1] = d[i][2] = d[i][3] = 0.f;
    const int mi = lane >> 3, j = lane & 7;
    const uint32_t st0 = scr + mi * 128 + ((j ^ mi) << 4), st1 = st0 ^ 64;
    const uint32_t la = scr + (lane & 15) * 128 + (((lane >> 4) ^ j) << 4), lb = scr + j * 128 + ((mi ^ j) << 4);
    auto st = [&](int row, uint32_t a, uint32_t b, uint32_t c, uint32_t e) { stm4(((row & 4) ? st1 : st0) + row * 128, a, b, c, e); };
#pragma unroll 1
    for (int c = c0; c < c1; c++) {
        if (c > c0 && pause) mbar_wait(pause, 0);
        const float zr2 = dt * (c ? bf_hi(kp.are) : bf_lo(kp.are)) * 1.4426950408889634f;
        const float zi = dt * (c ? bf_hi(kp.aim) : bf_lo(kp.aim));
        const cf w = {(c ? w1.x : w0.x) * sc, (c ? w1.y : w0.y) * sc};
        const cf a1 = cpow_direct(zr2, zi, 1.f), a256 = cpow_direct(zr2, zi, 256.f);
        uint32_t a[4][4];
        {
            const cf a16 = cpow_direct(-zr2, zi, -16.f);
            const cf a32 = csq(a16), a48 = cmul(a32, a16), a64 = csq(a32), a128 = csq(a64), a192 = cmul(a128, a64);
            const uint32_t p1 = pack_h(a16.x, a16.y), p2 = pack_h(a32.x, a32.y), p3 = pack_h(a48.x, a48.y);
            const hm q1 = mk_hm(a64), q2 = mk_hm(a128), q3 = mk_hm(a192);
            __syncwarp();
            st(0, 0x00003C00u, p1, p2, p3);
            st(4, q1.v, hcmul(p1, q1), hcmul(p2, q1), hcmul(p3, q1));
            st(8, q2.v, hcmul(p1, q2), hcmul(p2, q2), hcmul(p3, q2));
            st(12, q3.v, hcmul(p1, q3), hcmul(p2, q3), hcmul(p3, q3));
            __syncwarp();
#pragma unroll
            for (int k = 0; k < 4; k++) ldm4(la ^ (k * 32), a[k][0], a[k][1], a[k][2], a[k][3]);
        }
        auto tile = [&](int T, int row) {
#pragma unroll
            for (int kp2 = 0; kp2 < 2; kp2++) {
                uint32_t b0, b1, b2, b3;
                ldm4((lb ^ (kp2 * 64)) + row * 128, b0, b1, b2, b3);
                mma_h(d[T], a[2 * kp2][0], a[2 * kp2][1], a[2 * kp2][2], a[2 * kp2][3], b0, b1);
                mma_h(d[T], a[2 * kp2 + 1][0], a[2 * kp2 + 1][1], a[2 * kp2 + 1][2], a[2 * kp2 + 1][3], b2, b3);
            }
        };
        const cf a2 = csq(a1), a4 = csq(a2), a8 = csq(a4), a12 = cmul(a8, a4);
        const cf u1 = cmul(w, a1), u2 = cmul(w, a2), u3 = cmul(u2, a1), u4 = cmul(w, a4);
        uint32_t v[16];
        v[0] = pack_h(u1.x, u1.y); v[1] = pack_h(u2.x, u2.y); v[2] = pack_h(u3.x, u3.y); v[3] = pack_h(u4.x, u4.y);
        const hm m4 = mk_hm(a4), m8 = mk_hm(a8), m12 = mk_hm(a12);
#pragma unroll
        for (int i = 0; i < 4; i++) { v[4 + i] = hcmul(v[i], m4); v[8 + i] = hcmul(v[i], m8); v[12 + i] = hcmul(v[i], m12); }
        const hm m256 = mk_hm(a256);
        __syncwarp();
#pragma unroll
        for (int i = 0; i < 4; i++) st(4 * i, v[4 * i], v[4 * i + 1], v[4 * i + 2], v[4 * i + 3]);
        st(16, hcmul(v[1], m256), hcmul(v[3], m256), hcmul(v[5], m256), hcmul(v[7], m256));
        st(20, hcmul(v[9], m256), hcmul(v[11], m256), hcmul(v[13], m256), hcmul(v[15], m256));
        __syncwarp();
        tile(0, 0); tile(1, 8); tile(2, 16);
        const cf a512 = csq(a256), a768 = cmul(a512, a256), a1024 = csq(a512);
        const cf a1280 = cmul(a1024, a256), a1536 = csq(a768), a1792 = cmul(a1024, a768);
        const hm m512 = mk_hm(a512), m768 = mk_hm(a768);
        const hm n0 = mk_hm(a1024), n1 = mk_hm(a1280), n2 = mk_hm(a1536), n3 = mk_hm(a1792);
        __syncwarp();
        st(0, hcmul(v[3], m512), hcmul(v[7], m512), hcmul(v[11], m512), hcmul(v[15], m512));
        st(4, hcmul(v[3], m768), hcmul(v[7], m768), hcmul(v[11], m768), hcmul(v[15], m768));
        st(8, hcmul(v[7], n0), hcmul(v[15], n0), hcmul(v[7], n1), hcmul(v[15], n1));
        st(12, hcmul(v[7], n2), hcmul(v[15], n2), hcmul(v[7], n3), hcmul(v[15], n3));
        __syncwarp();
        tile(3, 0); tile(4, 8);
    }
    __syncwarp();
#pragma unroll
    for (int i = 0; i < 5; i++) sts128(os + i * 512 + lane * 16, __float_as_uint(d[i][0]), __float_as_uint(d[i][1]), __float_as_uint(d[i][2]), __float_as_uint(d[i][3]));
    sts64(os + 2560, eb, __float_as_uint(k0));
}

__device__ __forceinline__ void ktables(uint32_t os, int ostep, int np, uint32_t kr, uint32_t kt, uint32_t kinf, int part) {
    const int lane = threadIdx.x & 31, g = lane >> 2, t = lane & 3;
    uint32_t eb = 0;
    float k0 = 0.f, f[4];
#pragma unroll
    for (int q = 0; q < 4; q++) {
        uint2 v = make_uint2(0u, 0u);
        if (q < np) v = lds64(os + q * ostep + 2560);
        eb = max(eb, v.x);
        k0 += __uint_as_float(v.y);
        f[q] = __uint_as_float(v.x);
    }
    const float rs = __uint_as_float(0x7F000000u - eb);
#pragma unroll
    for (int q = 0; q < 4; q++) f[q] *= rs;
#pragma unroll 1
    for (int i = (part & 1) ? 0 : 2; i < ((part & 2) ? 5 : 3); i++) {
        float a0 = 0.f, a1 = 0.f, a2 = 0.f, a3 = 0.f;
        uint4 v[4];
#pragma unroll
        for (int q = 0; q < 4; q++) {
            v[q] = make_uint4(0u, 0u, 0u, 0u);
            if (q < np) v[q] = lds128(os + q * ostep + i * 512 + lane * 16);
        }
#pragma unroll
        for (int q = 0; q < 4; q++) { a0 += __uint_as_float(v[q].x) * f[q]; a1 += __uint_as_float(v[q].y) * f[q]; a2 += __uint_as_float(v[q].z) * f[q]; a3 += __uint_as_float(v[q].w) * f[q]; }
        const int sg = 32 >> max(i - 1, 0);
        const uint32_t o = kr + 4 + (i < 2 ? 16 * i : 256 * i) + sg * g + (i < 3 ? 8 : 128) * (t >> 1) + (i < 4 ? 4 : 64) * (t & 1);
        sts32(o, pack_h(a0, a1));
        sts32(o + 8 * sg, pack_h(a2, a3));
    }
    sts32(kr, pack_h(0.f, k0 * rs));
    __syncwarp();
    if (part & 1) {
        uint32_t w0[4], w1[4], a[2], b[2];
#pragma unroll
        for (int r = 0; r < 4; r++) { w0[r] = lds32(kr + 4 * lane + 128 * r); w1[r] = lds32(kr + 4 * lane + 128 * r + 4); }
#pragma unroll
        for (int r = 0; r < 2; r++) { a[r] = lds32(kr + 512 + 4 * lane + 128 * r); b[r] = lds32(kr + 516 + 4 * lane + 128 * r); }
#pragma unroll
        for (int r = 0; r < 4; r++) sts64(kt + 8 * lane + 256 * r + 32, prmt(w0[r], w0[r], 0x1032), prmt(w0[r], w1[r], 0x3254));
        if (lane == 31) b[1] = pack_h(h_lo(b[1]) - h_hi(b[1]), 0.f);
#pragma unroll
        for (int r = 0; r < 2; r++)
            sts128(kt + 4 * 264 + 16 * lane + 512 * r, prmt(a[r], a[r], (r == 0 && lane == 0) ? 0x1032 : 0x3232), prmt(a[r], a[r], 0x3232), prmt(a[r], b[r], 0x3254), prmt(b[r], b[r], 0x1032));
        if (lane < 24) sts32(kt + 4 * (lane < 8 ? lane : 512 + lane), 0u);
    }
    if (part & 2) {
        const uint32_t k512 = lds16(kr + 2 * 385), k1024 = lds16(kr + 2 * 513);
        if (lane == 0) {
            sts128(kinf, eb, __float_as_uint(h_lo(k512)), k1024, 0u);
            sts16(kr + 2 * 512, pack_h(h_lo(lds16(kr + 2 * 512)) - h_lo(k1024), 0.f));
        }
#pragma unroll
        for (int r = 0; r < 3; r++)
            if (r < 2 || lane < 26) sts128(kt + KT_P4 + 16 * lane + 512 * r, 0u, 0u, 0u, 0u);
        __syncwarp();
        uint32_t x0[5], x1[5], y0[5], y1[5];
#pragma unroll
        for (int r = 0; r < 5; r++) {
            const int m = min(126 + lane + 32 * r, 256);
            x0[r] = lds16(kr + 2 * (257 + m)); x1[r] = lds16(kr + 2 * (259 + m)); y0[r] = lds16(kr + 2 * (385 + m)); y1[r] = lds16(kr + 2 * (387 + m));
        }
#pragma unroll
        for (int r = 0; r < 5; r++) {
            const int m = 126 + lane + 32 * r;
            if (m < 128) x0[r] = y0[r] = 0;
            if (m > 253) x1[r] = 0;
            if (m > 254) y1[r] = 0;
            if (m < 256) sts32(kt + KT_P4 + 4 * (((m - 96) & ~3) | ((m & 1) << 1) | ((m >> 1) & 1)), x0[r] | (x1[r] << 16));
            if (m < 257) sts32(kt + KT_P8 + 4 * (m - 96), y0[r] | (y1[r] << 16));
        }
    }
    __syncwarp();
}

__device__ __forceinline__ void mma_hc(float (&d)[4], const float (&c)[4], uint32_t a0, uint32_t a1, uint32_t a2, uint32_t a3, uint32_t b0, uint32_t b1) {
    asm volatile("mma.sync.aligned.m16n8k16.row.col.f32.f16.f16.f32 {%0,%1,%2,%3},{%4,%5,%6,%7},{%8,%9},{%10,%11,%12,%13};"
                 : "=f"(d[0]), "=f"(d[1]), "=f"(d[2]), "=f"(d[3]) : "r"(a0), "r"(a1), "r"(a2), "r"(a3), "r"(b0), "r"(b1), "f"(c[0]), "f"(c[1]), "f"(c[2]), "f"(c[3]));
}
template <int Q0, int Q1>
__device__ __forceinline__ void sweep_steps(float (&w)[5][4], const uint32_t (&R)[66], uint32_t xa, uint32_t (&x)[5], uint32_t z) {
#pragma unroll
    for (int q = Q0; q <= Q1; q++) {
        uint32_t n0, n1;
        ldm2(xa + 16 * (q + 1), n0, n1);
        const uint32_t a2 = x[0] | z, a3 = x[1] | z;
#pragma unroll
        for (int j = 0; j < 4; j++) {
            const int s = 8 * j + 8 - q;
            if (q == 1) mma_hc(w[j], w[j + 1], x[1], x[2], a2, a3, R[2 * s], R[2 * s + 1]);
            else mma_h(w[j], x[1], x[2], a2, a3, R[2 * s], R[2 * s + 1]);
        }
        if (q == 8) {
            const float zero[4] = {0.f, 0.f, 0.f, 0.f};
            mma_hc(w[4], zero, x[1], x[2], a2, a3, R[64], R[65]);
        }
        x[0] = x[2]; x[1] = x[3]; x[2] = x[4]; x[3] = n0; x[4] = n1;
    }
}

__device__ __forceinline__ void box_round(uint32_t xb, uint32_t fa, int rho, int lane) {
    if (rho == 6) {
        const int a = lane >> 3, j = lane & 7;
        sts128(fa + 3328 * (lane >> 4) + 16 * ((lane & 15) < 15 ? (lane & 15) : 207), 0u, 0u, 0u, 0u);
        sts128(fa + FB9E + 1168 * a + 16 * (j < 7 ? j : 71 + (a & 1)), 0u, 0u, 0u, 0u);
        __syncwarp();
    }
    const int c = rho < 6 ? 32 * rho + lane : -1;
    const uint4 pv = lds128(x0_chunk(xb, c - 1)), ow = lds128(x0_chunk(xb, c));
    const uint2 nx = lds64(x0_chunk(xb, c + 1));
    const uint32_t P[9] = {pv.y, pv.z, pv.w, ow.x, ow.y, ow.z, ow.w, nx.x, nx.y};
    uint32_t Q[8], b3[6], b5[4];
#pragma unroll
    for (int k = 0; k < 8; k++) Q[k] = prmt(P[k], P[k + 1], 0x5432);
#pragma unroll
    for (int k = 0; k < 6; k++) b3[k] = hadd(hadd(Q[k], Q[k + 1]), P[k + 1]);
#pragma unroll
    for (int k = 0; k < 4; k++) b5[k] = hadd(b3[k + 2], hadd(P[k + 2], P[k + 4]));
    sts128(fa + FB5 + 240 + 16 * c, b5[0], b5[1], b5[2], b5[3]);
    sts128(fa + FB3 + 240 + 16 * c, b3[0], b3[1], b3[2], b3[3]);
    if (rho < 4 || rho == 6) {
        uint32_t b7[4], b9[4];
#pragma unroll
        for (int k = 0; k < 4; k++) {
            b7[k] = hadd(b5[k], hadd(Q[k + 1], Q[k + 4]));
            b9[k] = hadd(b7[k], hadd(P[k + 1], P[k + 5]));
        }
        const uint32_t ad = fa + ((c & 1) ? FB9O + 120 : FB9E + 112) + 8 * c;
        sts128(ad, b9[0], b9[1], b9[2], b9[3]);
        sts128(ad + (FB7E - FB9E), b7[0], b7[1], b7[2], b7[3]);
    }
}

__global__ void __cluster_dims__(2, 1, 1) __launch_bounds__(NTHREADS, 1) fused_kernel(const Hot p, const __grid_constant__ Maps m) {
    extern __shared__ __align__(1024) char smem[];
    const uint32_t t0 = clk32();
    const int tid = (threadIdx.x + 32 * 0) & (NTHREADS - 1), lane = tid & 31, warp = __shfl_sync(~0u, tid >> 5, 0), bid = blockIdx.x;
    const uint32_t S = smem_u32(smem), z = (uint32_t)p.tn.zero;
    const bool down = bid < NDOWN, rowcta = bid < NMAIN, big = rowcta && !down;
    const int xd = rowcta ? bid : 142 + ((bid - NMAIN) >> 1);
    const int slot = warp < 8 ? (warp & 3) : 4;
    const bool has = warp < 8 ? (rowcta || (slot >> 1) == (bid & 1)) : (big && warp < 12);
    const int ch = slot < 4 ? 4 * xd + slot : 512 + bid - NDOWN;
    KParams kp;
    if (has) kp = kgen_load(p, ch, warp < 8 ? warp >> 2 : (warp >> 1) & 1, lane);
    if (elect()) {
#pragma unroll 1
        for (int i = warp; i < B_COUNT; i += 16) {
            const uint32_t c = i < 16 ? (uint32_t)((big ? 0x1411115555412290ull : 0x1411114444412290ull) >> (4 * i)) & 15 : 1;
            mbar_init(S + i * 8, c ? c : NTHREADS);
        }
        asm volatile("fence.mbarrier_init.release.cluster;" ::: "memory");
    }
    if (rowcta) {
#pragma unroll 1
        for (int i = tid; i < 1224; i += NTHREADS)
            cp16(S + SM_ROWS + 16 * (i + min((i * 911) >> 16, 16)), i < 1152 ? (const uint4*)p.u + bid * 1152 + i : (const uint4*)p.wr + (i - 1152));
    }
    if (tid >= 256 && tid < 336) {
        const int i = tid - 256;
        if (i < 64 || big) sts128(S + (i < 64 ? SM_X0 + (i >> 4) * X0_STRIDE : SM_EX) + ((i & 8) ? X0_ODD : 0) + 16 * (i & 7), 0u, 0u, 0u, 0u);
    }
    if (tid == 447) sts128(S + SM_ONES, 0x3F803F80u, 0x3F803F80u, 0x3F803F80u, 0x3F803F80u);
    __syncthreads();
    if (rowcta) asm volatile("cp.async.mbarrier.arrive.noinc.shared::cta.b64 [%0];" ::"r"(S + B_ROWS * 8) : "memory");
    if (warp == 15 && lane < 4) mbar_expect(S + (lane < 3 ? B_GX + lane : B_RED) * 8, 256);
    asm volatile("barrier.cluster.arrive.relaxed.aligned;" ::: "memory");
    const int g = lane >> 2, t = lane & 3, mi = lane >> 3, j = lane & 7;
    const uint32_t SW = S + (down ? SM_W_DOWN : SM_W_BIG);
    const int pr = bid >> 1, r = bid & 1, nsl = pr >= 54 ? 3 : 2, sl0 = pr < 54 ? 2 * pr : 3 * pr - 54;

    if (warp == 12) {
        if (elect()) {
            const int ng = 6 * nsl, ns = down ? 24 : ng;
            const CUtensorMap* mg = r ? &m.wu : &m.wg;
            pf_tmap(mg);
            if (down) pf_tmap(&m.wd);
            const uint32_t epoch = ld_rlx(&p.s->cnt[16 * 32]) + 1;
            spin_until(t0, p.tn.f_start);
            int done = 0;
#pragma unroll 1
            for (int s = 0; s < ns; s++) {
                if (s == ng) spin_until(t0, p.tn.f_t3);
                #pragma unroll 1
                for (int it = 0; it < SPIN_LIMIT; it++) {
                    const int w = s >= ng ? p.tn.w3 : ((int)(clk32() - t0) < p.tn.f_t2 ? p.tn.w1 : (nsl == 3 ? p.tn.w2b : p.tn.w2));
                    if (s - done < w) break;
                    if (mbar_test(S + (B_W + done) * 8, 0)) done++;
                    else __nanosleep(32);
                }
                const uint32_t bar = S + (B_W + s) * 8;
                uint32_t dst = SW + s * STAGE;
                if (s == 23) { mbar_wait(S + B_EM * 8, 0); fence_async(); dst = S + SM_W_LAST; }
                mbar_expect(bar, STAGE);
                const int u = (s * 43) >> 8;
                if (s < ng) tma2d(dst, mg, 32 * (sl0 + u), 96 * (s - 6 * u), bar);
                else tma2d(dst, &m.wd, 16 * pr, r * 2304 + 192 * (s - 12), bar);
            }
            if (rowcta) {
                mbar_wait(S + B_FD * 8, 0);
                fence_async();
#pragma unroll 1
                for (int q = 0; q < 4; q++) {
                    wait_count(&p.s->cnt[(8 + q) * 32], epoch * (uint32_t)D_);
                    fence_async_g();
                    mbar_expect(S + (B_YIN + q) * 8, 4608);
                    bulk_g2s(S + SM_STG + q * 4608, p.s->y + (32 * q + (bid >> 2)) * 4608 + (bid & 3) * 1152, 4608, S + (B_YIN + q) * 8);
                }
            }
        }
        return;
    }

    uint32_t epoch = 0;
    if (warp >= 8 || !rowcta) epoch = ld_rlx(&p.s->cnt[16 * 32] + (lane & z)) + 1;
    const uint32_t tag = epoch & 1;
    const int hw = warp < 12 ? warp - 8 : warp - 9;

    if (rowcta && warp >= 8 && warp < 15) {
        const uint32_t ad = S + SM_ROWS + (lane & 15) * ROW_STRIDE + 192 * hw + 16 * (lane >> 4);
        uint32_t wd = j ? S + SM_ROWS + 16 * ROW_STRIDE + 192 * hw + 16 * mi : S + SM_ONES;
        const uint32_t wstep = j ? 64 : 0, ones = 0x3F803F80u | z;
        float d1[4] = {0, 0, 0, 0}, d2[4] = {0, 0, 0, 0}, d3[4] = {0, 0, 0, 0}, d4[4] = {0, 0, 0, 0};
        mbar_wait(S + B_ROWS * 8, 0);
#pragma unroll
        for (int kk = 0; kk < 3; kk++) {
            uint32_t w[4];
            ldm4(wd, w[0], w[1], w[2], w[3]);
            wd += wstep;
#pragma unroll
            for (int e = 0; e < 2; e++) {
                uint32_t a0, a1, a2, a3;
                ldm4(ad + 64 * kk + 32 * e, a0, a1, a2, a3);
                mma_bf(d1, a0, a1, a2, a3, w[2 * e], w[2 * e + 1]);
                mma_bf(d2, a0, a1, a2, a3, a0, a2);
                mma_bf(d3, a0, a1, a2, a3, a1, a3);
                mma_bf(d4, ones, ones ^ z, ones + z, ones - z, w[2 * e], w[2 * e + 1]);
            }
        }
        float* part = (float*)(smem + SM_PART + hw * 256) + g * 4;
        if (t == 0) {
            *(float2*)part = make_float2(d1[0], d1[1]);
            *(float2*)(part + 32) = make_float2(d1[2], d1[3]);
            part[3] = d4[1];
            part[35] = d4[1];
        }
        if (t == (g >> 1)) {
            part[2] = (g & 1) ? d2[1] : d2[0];
            part[34] = (g & 1) ? d3[3] : d3[2];
        }
        bar_sync(1, 192);
        if (hw == 0 && lane < 16) {
            float4 s = *(const float4*)(smem + SM_PART + lane * 16);
#pragma unroll
            for (int w = 1; w < 6; w++) {
                const float4 v = *(const float4*)(smem + SM_PART + w * 256 + lane * 16);
                s.x += v.x; s.y += v.y; s.z += v.z; s.w += v.w;
            }
            const float mean = s.x * (1.f / 576.f);
            const float var = fmaxf(s.z * (1.f / 576.f) - mean * mean, 0.f);
            const uint32_t mm = pack_bf(mean, mean);
            const float mu = bf_lo(mm), sd = bf_round(sqrt_ap(bf_round(bf_round(var) + 1e-5f))), ri = rcpf(sd);
            const uint32_t hi = pack_bf(ri, ri);
            const float rl = ri - bf_lo(hi);
            sts16(S + SM_STA + 2 * lane, mm); sts16(S + SM_STA + 32 + 2 * lane, hi); sts16(S + SM_STA + 64 + 2 * lane, pack_bf(rl, rl));
            const uint32_t rb = pack_bf(0.f, (s.y - mu * s.w) * ri);
            const int row = bid * 16 + lane;
            p.s->stat[row] = (mm & 0xFFFFu) | __float_as_uint(sd) | (tag << 31);
            p.s->key[row] = ((rb ^ (((int)rb >> 31) | 0x80000000u)) & 0xFFFF0000u) | (tag << 15) | (2047 - row);
        }
        bar_sync(1, 192);
        if (tid == 256) mbar_arrive(S + B_P1 * 8);
        {
            const uint2 sm = lds64(S + SM_STA + 8 * t), sh = lds64(S + SM_STA + 32 + 8 * t), sl = lds64(S + SM_STA + 64 + 8 * t);
            const uint32_t at = S + SM_ROWS + (4 * (j >> 1) + (j & 1) + 2 * (mi & 1)) * ROW_STRIDE + 32 * hw + 16 * (mi >> 1);
            uint2* dst = (uint2*)p.s->x + (4 * hw + (g >> 2)) * 2048 + bid * 16 + (g & 3) * 4 + t;
            uint32_t r4[6][4];
#pragma unroll
            for (int n = 5; n >= 0; n--) ldm4t(at + 192 * n, r4[n][0], r4[n][1], r4[n][2], r4[n][3]);
#pragma unroll
            for (int n = 5; n >= 0; n--) {
                uint32_t o[4];
#pragma unroll
                for (int e = 0; e < 4; e++) {
                    const uint32_t v = (e & 1) ? norm2(r4[n][e], sm.y, sh.y, sl.y) : norm2(r4[n][e], sm.x, sh.x, sl.x);
                    o[e] = pack_h(bf_lo(v), bf_hi(v));
                }
                dst[n * 49152] = make_uint2((o[0] & ~1u) | tag, o[1]);
                dst[n * 49152 + 4096] = make_uint2((o[2] & ~1u) | tag, o[3]);
            }
        }
        bar_sync(1, 192);
    }

    if (has) {
        asm volatile("" : "+r"(kp.ldt), "+r"(kp.are), "+r"(kp.aim), "+r"(kp.bre), "+r"(kp.bim), "+r"(kp.cre), "+r"(kp.cim));

        const uint32_t scr = warp < 8 ? S + SM_STG + warp * KG_SCR : S + EX_HAND + hw * KG_SCR;
        kgen(kp, scr, warp < 8 ? scr : S + EX_FAR + hw * 2576, warp < 8 ? 0 : warp & 1, warp < 8 ? 2 : (warp & 1) + 1, rowcta ? S + B_P1 * 8 : 0);
        if (warp >= 8) { __syncwarp(); if (lane == 0) mbar_arrive(S + B_TAB * 8); }
    }
    if (warp < 8 || warp == 15) {
        if (warp < 8 ? has : big) {
            if (warp < 8) bar_sync(4 + slot, 64); else mbar_wait(S + B_TAB * 8, 0);
            ktables(warp < 8 ? S + SM_STG + slot * KG_SCR : S + EX_FAR, warp < 8 ? 4 * KG_SCR : 2576, warp < 8 ? 2 : 4, S + SM_XS + slot * KR_STRIDE,
                    S + (warp < 8 ? SM_KT + slot * KT_STRIDE : EX_KT), S + SM_KINF + slot * 16, warp < 8 ? 1 + (warp >> 2) : 3);
        }
        if (lane == 0) { mbar_arrive(S + B_KG * 8); if (warp == 15) mbar_arrive(S + B_TAB1 * 8); }
    }

    if (!rowcta && warp < 8 && !has) {
        const int w4 = (warp >> 2) * 2 + (warp & 1), i = 32 * w4 + lane;
#pragma unroll 1
        for (int pass = 1; pass < 2; pass++) {
        uint4 k[4];
        if (pass) spin_until(t0, p.tn.t_svc - 1500);
#pragma unroll 1
        for (int it = 0; it < SPIN_LIMIT; it++) {
            if (!pass) {
#pragma unroll
                for (int q = 0; q < 4; q++) k[q] = make_uint4(16 * i + 4 * q, 16 * i + 4 * q + 1, 16 * i + 4 * q + 2, 16 * i + 4 * q + 3);
                break;
            }
            uint32_t bad = 0;
#pragma unroll
            for (int q = 0; q < 4; q++) k[q] = ld_rlx4(&p.s->key[4 * i + 512 * q]);
#pragma unroll
            for (int q = 0; q < 4; q++) bad |= tag ? ~(k[q].x & k[q].y & k[q].z & k[q].w) : (k[q].x | k[q].y | k[q].z | k[q].w);
            if (!(bad & 0x8000u)) break;
            __nanosleep(100);
        }
        const uint32_t sc = S + SM_XS + ((bid & 1) ? 0 : 2) * KR_STRIDE;
        auto pk = [](uint32_t v) { return ((v >> 16) << 11) | (v & 2047u); };
        auto gt = [](uint32_t a, uint32_t b) { return (b - a) >> 31; };
        uint32_t mx = 0;
#pragma unroll
        for (int q = 0; q < 4; q++) {
            k[q] = make_uint4(pk(k[q].x), pk(k[q].y), pk(k[q].z), pk(k[q].w));
            mx = max(max(mx, max(k[q].x, k[q].y)), max(k[q].z, k[q].w));
        }
        bar_sync(1, 128);
        sts32(sc + 4 * i, mx);
        if (i == 0) sts32(sc + 1024, 0u);
        bar_sync(1, 128);
        int rank;
        {
            int c[8] = {0, 0, 0, 0, 0, 0, 0, 0};
#pragma unroll 1
            for (int q = 0; q < 32; q += 4) {
                uint4 v[4];
#pragma unroll
                for (int e = 0; e < 4; e++) v[e] = lds128(sc + 16 * (q + e));
#pragma unroll
                for (int e = 0; e < 4; e++) {
                    c[(2 * e) & 7] += gt(v[e].x, mx); c[(2 * e + 1) & 7] += gt(v[e].y, mx);
                    c[(2 * e + 4) & 7] += gt(v[e].z, mx); c[(2 * e + 5) & 7] += gt(v[e].w, mx);
                }
            }
            rank = ((c[0] + c[1]) + (c[2] + c[3])) + ((c[4] + c[5]) + (c[6] + c[7]));
        }
        if (rank == 7) sts32(sc + 1028, mx);
        bar_sync(1, 128);
        if (rank < 8) {
            const uint32_t lb = lds32(sc + 1028);
            int cq[4];
#pragma unroll
            for (int q = 0; q < 4; q++) cq[q] = (gt(lb, k[q].x) + gt(lb, k[q].y)) + (gt(lb, k[q].z) + gt(lb, k[q].w));
            const int c = 16 - ((cq[0] + cq[1]) + (cq[2] + cq[3]));
            uint32_t pos;
            asm volatile("atom.shared.add.u32 %0, [%1], %2;" : "=r"(pos) : "r"(sc + 1024), "r"(c) : "memory");
            pos = sc + 512 + 4 * pos;
#pragma unroll
            for (int q = 0; q < 4; q++) {
                if (k[q].x >= lb) { sts32(pos, k[q].x); pos += 4; }
                if (k[q].y >= lb) { sts32(pos, k[q].y); pos += 4; }
                if (k[q].z >= lb) { sts32(pos, k[q].z); pos += 4; }
                if (k[q].w >= lb) { sts32(pos, k[q].w); pos += 4; }
            }
        }
        bar_sync(1, 128);
        const int n = lds32(sc + 1024);
        if (i < n) {
            const uint32_t mine = lds32(sc + 512 + 4 * i);
            rank = 0;
#pragma unroll 1
            for (int q = 0; q < n; q += 4) {
                const uint4 v = lds128(sc + 512 + 4 * q);
                rank += ((v.x > mine) + (q + 1 < n && v.y > mine)) + ((q + 2 < n && v.z > mine) + (q + 3 < n && v.w > mine));
            }
            const uint32_t k32 = (mine >> 11) << 16, rb = (k32 ^ ((~(int)k32 >> 31) | 0x80000000u)) & 0xFFFF0000u;
            if (rank < 8 && pass) st_rlx(&p.s->sel[bid - NMAIN][rank], (2047 - (mine & 2047)) | (tag << 15) | (pack_bf(rcpf(1.f + ex2f(-1.4426950408889634f * __uint_as_float(rb))), 0.f) << 16));
        }
        }
    }

    if (warp == 13 || warp == 14) {
        const int i = tid - 416;
        if (i == 0) sts32(S + SM_EPOCH, tag);
        if (rowcta) {
            if (p.tn.t_marg <= 600) {
                const uint32_t back = ld_rlx(p.s->x + 2 * ((4 * hw + 2 + (g >> 2)) * 2048 + bid * 16 + (g & 3) * 4 + t));
                if (back == 0xFFFFFFFFu) __nanosleep(20);
            }
            spin_until(clk32(), p.tn.t_marg);
        } else {
            spin_until(t0, p.tn.t_svc);
        }
        const uint4* xa = (const uint4*)p.s->x + xd * 1024 + i;
        const int e = bid - NDOWN;
        const uint4* xe = (const uint4*)p.s->x + (128 + (e >> 2)) * 1024 + (i >> 1) * 8 + (e & 3) * 2 + (i & 1);
        const uint32_t da = S + SM_X0 + ((i >> 1) & 3) * X0_STRIDE + ((i & 1) ? X0_ODD : 0) + 128 + 16 * (i >> 3);
        const uint32_t de = S + SM_EX + ((i & 1) ? X0_ODD : 0) + 128 + 16 * (i >> 1);
        uint4 v[2][10];
        auto fetch = [&](int half) {
#pragma unroll
            for (int k = 0; k < 10; k++) {
                v[half][k].x = v[half][k].z = tag;
                if (k < 8 || big) v[half][k] = ld_rlx4(k < 8 ? xa + 512 * half + 64 * k : xe + 512 * half + 256 * (k - 8));
            }
        };
        fetch(0); fetch(1);
#pragma unroll
        for (int half = 0; half < 2; half++) {
#pragma unroll 1
            for (int it = 0; it < SPIN_LIMIT; it++) {
                uint32_t bad = 0;
#pragma unroll
                for (int k = 0; k < 10; k++) bad |= (v[half][k].x ^ tag) | (v[half][k].z ^ tag);
                if (!(bad & 1)) break;
                __nanosleep(60);
                fetch(half);
            }
#pragma unroll
            for (int k = 0; k < 10; k++)
                if (k < 8 || big) sts128(k < 8 ? da + 1024 * half + 128 * k : de + 1024 * half + 512 * (k - 8), v[half][k].x & ~1u, v[half][k].y, v[half][k].z & ~1u, v[half][k].w);
            __syncwarp();
            if (lane == 0) mbar_arrive(S + (B_X0 + half) * 8);
        }
    }

    if (warp < 12) {
        const bool cw = warp >= 8;
        if (has) {
            const uint32_t xb = S + (cw ? SM_EX : SM_X0 + slot * X0_STRIDE), kt = S + (cw ? EX_KT : SM_KT + slot * KT_STRIDE);
            const int g0 = cw ? warp - 8 : 0, g1 = cw ? warp - 7 : 4;
            const uint32_t park = (cw ? S + EX_HAND + g0 * 2048 : kt) + lane * 16;
            if (cw) mbar_wait(S + B_TAB1 * 8, 0);
            const uint4 ki = lds128(S + SM_KINF + slot * 16);
            const float inv = __uint_as_float(ki.x);
            if (warp >= 4) {
                const uint32_t fa = S + (cw ? EX_FAR : SM_FAR + slot * FAR_STRIDE);
                mbar_wait(S + (cw ? B_X1 : B_X0) * 8, 0);
                mbar_wait(S + B_KG * 8, 0);
#pragma unroll 1
                for (int rho = cw ? g0 : 0; rho < (cw ? 7 : 4); rho += cw ? 4 : 1) box_round(xb, fa, (!cw && rho == 3) ? 6 : rho, lane);
                if (cw) bar_sync(2, 128); else __syncwarp();
                const int dd = g - 2 * t, gf = g0 ? g0 : 1;
                const uint32_t tb0 = dd == -5 ? ki.z : (dd == -4 ? ki.z << 16 : 0u), tb1 = dd == 3 ? ki.z : (dd == 4 ? ki.z << 16 : 0u);
                uint32_t tad = xb + (mi == 1 ? 144 : mi == 2 ? 128 : X0_ODD + 128) + 16 * j + 512 * gf - 1024;
                uint32_t ad8 = fa + (mi == 0 ? FB9E : mi == 1 ? FB7O : mi == 2 ? FB9O + 16 : FB7E) + 112 - 16 * j + 512 * gf - 768;
                uint32_t ad4 = fa + ((mi & 1) ? FB3 : FB5) + 240 + 16 * (8 * (mi >> 1) - j) + 1024 * gf - 640;
                const uint32_t p4 = kt + KT_P4 + 16 * (g + t), p8 = kt + KT_P8 + 8 * (g + 2 * t);
#pragma unroll 1
                for (int grp = gf; grp < g1; grp++) {
                    float a[4][4], e[2][4], o[2][4];
#pragma unroll
                    for (int k = 0; k < 4; k++) a[0][k] = a[1][k] = a[2][k] = a[3][k] = e[0][k] = e[1][k] = o[0][k] = o[1][k] = 0.f;
                    {
                        if (!cw && grp == 2) {
                            mbar_wait(S + B_X1 * 8, 0);
#pragma unroll 1
                            for (int rho = 3; rho < 6; rho++) box_round(xb, fa, rho, lane);
                            __syncwarp();
                        }
                        {
                            uint4 A4[10];
#pragma unroll
                            for (int s = 0; s < 10; s++) A4[s] = lds128(p4 + 64 * s);
                            auto s4 = [&](int m) {
                                uint32_t b[4];
                                ldm4t(ad4 - 256 * m, b[0], b[1], b[2], b[3]);
#pragma unroll
                                for (int h = 1; h >= 0; h--)
#pragma unroll
                                    for (int i = 0; i < 4; i++) {
                                        const int s = 2 * m - 2 + 2 * i + (1 - h), k = m + (i & 2);
                                        if (k <= 5 && k >= ((i & 1) ? 0 : 1) && !((i & 1) && k == 5)) mma_h(a[i], A4[s >= 0 && s < 10 ? s : 0].x, A4[s >= 0 && s < 10 ? s : 0].y, A4[s >= 0 && s < 10 ? s : 0].z, A4[s >= 0 && s < 10 ? s : 0].w, b[2 * h], b[2 * h + 1]);
                                    }
                            };
                            auto tap = [&](int i) {
                                uint32_t b[4];
                                ldm4(tad + 128 * i, b[0], b[1], b[2], b[3]);
                                mma_h(a[i], b[0], b[1], b[2], b[3], tb1, tb0);
                            };
                            s4(1); s4(0); s4(2); s4(-1); tap(3); s4(-2);
                            if (grp >= 2) { s4(3); tap(0); s4(4); tap(1); s4(5); tap(2); }
                        }
                        {
                            uint32_t A8[9][4];
#pragma unroll
                            for (int k = 0; k < 9; k++) { A8[k][0] = lds32(p8 + 64 * k); A8[k][1] = lds32(p8 + 64 * k + 64); A8[k][2] = lds32(p8 + 64 * k + 4); A8[k][3] = lds32(p8 + 64 * k + 68); }
                            auto s8 = [&](int m) {
                                uint32_t b[4];
                                ldm4t(ad8 - 128 * m, b[0], b[1], b[2], b[3]);
                                mma_h(e[1], A8[m + 2][0], A8[m + 2][1], A8[m + 2][2], A8[m + 2][3], b[0], b[1]);
                                mma_h(o[1], A8[m + 2][0], A8[m + 2][1], A8[m + 2][2], A8[m + 2][3], b[2], b[3]);
                                if (m >= 0) {
                                    mma_h(e[0], A8[m >= 0 ? m : 0][0], A8[m >= 0 ? m : 0][1], A8[m >= 0 ? m : 0][2], A8[m >= 0 ? m : 0][3], b[0], b[1]);
                                    mma_h(o[0], A8[m >= 0 ? m : 0][0], A8[m >= 0 ? m : 0][1], A8[m >= 0 ? m : 0][2], A8[m >= 0 ? m : 0][3], b[2], b[3]);
                                }
                            };
                            s8(-2);
                            if (grp >= 2) {
                                s8(-1); s8(0); s8(1); s8(2);
                                if (grp >= 3) { s8(3); s8(4); s8(5); s8(6); }
                            }
                        }
                    }
                    tad += 512; ad8 += 512; ad4 += 1024;
#pragma unroll
                    for (int pp = 0; pp < 2; pp++) {
                        if (!cw) {
#pragma unroll 1
                            for (int it = 0; it < SPIN_LIMIT && !__all_sync(~0u, lds32v(park + (2 * pp + 1) * 512) == SLOT_FREE); it++) __nanosleep(32);
                        }
#pragma unroll
                        for (int i = 0; i < 2; i++)
                            sts128(park + (2 * pp + i) * 512, __float_as_uint((a[2 * pp + i][0] + e[pp][2 * i]) * inv), __float_as_uint((a[2 * pp + i][1] + e[pp][2 * i + 1]) * inv),
                                   __float_as_uint((a[2 * pp + i][2] + o[pp][2 * i]) * inv), __float_as_uint((a[2 * pp + i][3] + o[pp][2 * i + 1]) * inv));
                    }
                }
            }
            if ((warp & 12) != 4) {
                uint32_t R[66], x[5];
#pragma unroll
                for (int i = 0; i < 66; i++) R[i] = lds32(kt + 4 * (8 + g - 2 * t) + 32 * i);
                float w[5][4];
#pragma unroll
                for (int i = 0; i < 5; i++) w[i][0] = w[i][1] = w[i][2] = w[i][3] = 0.f;
                uint32_t xa = xb + ((lane & 8) ? X0_ODD + 16 : 16) + 16 * j + 512 * g0;
                uint2* yo = (uint2*)p.s->y + (32 * g0 + g) * 2304 + ch * 4 + t;
                mbar_wait(S + B_X0 * 8, 0);
                const uint32_t ytag = lds32(S + SM_EPOCH);
                if (g0 == 0) {
                    const uint32_t x01 = lds32(xb + 128);
                    const float c0 = lane == 31 ? __uint_as_float(ki.y) * inv * h_lo(x01) : 0.f, c1 = lane == 31 ? c0 + __uint_as_float(ki.y) * inv * h_hi(x01) : 0.f;
                    __syncwarp();
#pragma unroll
                    for (int i = 0; i < 4; i++) sts128(park + i * 512, 0u, 0u, i == 3 ? __float_as_uint(c0) : 0u, i == 3 ? __float_as_uint(c1) : 0u);
                }
                ldm2(xa - 16, x[1], x[0]);
                ldm2(xa, x[1], x[2]);
                ldm2(xa + 16, x[3], x[4]);
                uint32_t zz = z, pk = park;
                float sc = inv;
                const bool direct = g0 == 0;
                uint32_t dir = direct;
                asm volatile("" : "+r"(pk));
#pragma unroll 1
                for (int gq = g0; gq < g1; gq++) {
                    uint32_t pa = pk;
#pragma unroll 1
                    for (int n = 4; n > 0; n--) {
                        asm volatile("" : "+r"(zz), "+f"(sc), "+r"(pa), "+r"(dir));
                        sweep_steps<1, 5>(w, R, xa, x, zz);
                        uint4 v = lds128v(pa | (x[4] & zz));
                        sweep_steps<6, 8>(w, R, xa, x, zz);
                        xa += 128;
                        if (__any_sync(~0u, v.x == SLOT_FREE)) {
#pragma unroll 1
                            for (int it = 0; it < SPIN_LIMIT; it++) {
                                v = lds128v(pa);
                                if (!__any_sync(~0u, v.x == SLOT_FREE)) break;
                            }
                        }
                        const float y0 = fmaf(w[0][0], sc, __uint_as_float(v.x)), y1 = fmaf(w[0][1], sc, __uint_as_float(v.y));
                        const float y2 = fmaf(w[0][2], sc, __uint_as_float(v.z)), y3 = fmaf(w[0][3], sc, __uint_as_float(v.w));
                        if (dir) {
                            *yo = make_uint2((pack_bf(y0, y1) & ~1u) | ytag, pack_bf(y2, y3));
                            sts32(pa, SLOT_FREE);
                        } else {
                            sts128(pa, __float_as_uint(y0), __float_as_uint(y1), __float_as_uint(y2), __float_as_uint(y3));
                        }
                        yo += 18432;
                        pa += 512;
                    }
                    if (direct && lane == 0) red_add(&p.s->cnt[(8 + gq) * 32]);
                }
                __syncwarp();
                if (lane == 0) mbar_arrive(S + (direct ? B_EM : B_SP + g0) * 8);
                if (cw && g0 < 3) {
                    mbar_wait(S + (B_SP + g0 + 1) * 8, 0);
#pragma unroll
                    for (int i = 0; i < 4; i++) {
                        const uint4 v = lds128(park + 2048 + i * 512);
                        yo[i * 18432] = make_uint2((pack_bf(fmaf(w[i + 1][0], inv, __uint_as_float(v.x)), fmaf(w[i + 1][1], inv, __uint_as_float(v.y))) & ~1u) | ytag,
                                                   pack_bf(fmaf(w[i + 1][2], inv, __uint_as_float(v.z)), fmaf(w[i + 1][3], inv, __uint_as_float(v.w))));
                    }
                    if (lane == 0) red_add(&p.s->cnt[(8 + g0 + 1) * 32]);
                }
            }
        }
        if (rowcta && (warp & 12) == 4) {
            bar_sync(10, 128);
            const int i = tid - 128, rb0 = 16 * (bid >> 2), c0 = 144 * (bid & 3);
            if (i == 0) mbar_arrive(S + B_FD * 8);
#pragma unroll 3
            for (int v = i; v < 1152; v += 128) {
                const int row = (v * 3641) >> 16, vv = v - 18 * row;
                cp16(S + SM_ROWS + row * 304 + 16 * vv, (const uint4*)(p.u + (size_t)(512 * (row >> 4) + rb0 + (row & 15)) * D_ + c0) + vv);
            }
            if (i < 64) {
                const uint32_t sw = ld_stat(&p.s->stat[512 * (i >> 4) + rb0 + (i & 15)], lds32(S + SM_EPOCH));
                const float ri = rcpf(bf_hi(sw));
                const uint32_t hi = pack_bf(ri, ri);
                const float rl = ri - bf_lo(hi);
                sts128(S + SM_KT + KT_P4 + 16 * i, prmt(sw, sw, 0x1010), hi, pack_bf(rl, rl), 0u);
            }
            asm volatile("cp.async.wait_all;" ::: "memory");
            __syncwarp();
            if (lane == 0) mbar_arrive(S + B_OUT * 8);
        }
        if (!rowcta) return;

        const int rb0 = 16 * (bid >> 2), c0 = 144 * (bid & 3);
        mbar_wait(S + B_OUT * 8, 0);
        mbar_wait(S + B_XS * 8, 0);
        const uint32_t otag = lds32(S + SM_EPOCH) * 0x00010001u;
        const uint2 skip = lds64(S + SM_SKIP);
        const int pi_g = (g & 1) + 8 * ((g >> 1) & 1) + 2 * (g >> 2), pi_j = (j & 1) + 8 * ((j >> 1) & 1) + 2 * (j >> 2);
#pragma unroll 1
        for (int un = warp; un < 36; un += 12) {
            const int q = (un * 57) >> 9, cu = un - 9 * q;
            const uint32_t rw = S + SM_ROWS + 16 * q * 304 + 32 * cu;
            const uint32_t ad = rw + (pi_j + 4 * (mi & 1)) * 304 + 16 * (mi >> 1);
            const uint32_t dk0 = __ldg((const uint32_t*)p.dskip + (c0 >> 1) + 8 * cu + t), dk1 = __ldg((const uint32_t*)p.dskip + (c0 >> 1) + 8 * cu + 4 + t);
            const uint4 sa = lds128(S + SM_KT + KT_P4 + 16 * (16 * q + pi_g)), sb = lds128(S + SM_KT + KT_P4 + 16 * (16 * q + 4 + pi_g));
            uint32_t x[4], tt[4], gt[4], y[4];
            ldm4(ad, x[0], x[1], x[2], x[3]);
#pragma unroll
            for (int e = 0; e < 4; e++) {
                const uint4 s = (e & 1) ? sb : sa;
                const uint32_t xn = norm2(x[e], s.x, s.y, s.z);
                tt[e] = bmul(xn, e < 2 ? dk0 : dk1);
                gt[e] = pack_bf(silu_f(bf_lo(xn)), silu_f(bf_hi(xn)));
            }
            mbar_wait(S + (B_YIN + q) * 8, 0);
            const uint32_t yb = S + SM_STG + q * 4608 + 512 * cu;
#pragma unroll 1
            for (int it = 0; it < SPIN_LIMIT; it++) {
                ldm4t(yb + (8 * (mi >> 1) + j) * 32 + 16 * (mi & 1), y[0], y[1], y[2], y[3]);
                const uint32_t bad = ((y[0] ^ otag) | (y[1] ^ otag) | (y[2] ^ otag) | (y[3] ^ otag)) & 0x00010001u;
                if (!__any_sync(~0u, (g & 3) == 0 && bad)) break;
                const uint4 v = ld_rlx4((const uint4*)(p.s->y + (32 * q + (bid >> 2)) * 4608 + (bid & 3) * 1152 + 128 * cu) + lane);
                __syncwarp();
                sts128(yb + 16 * lane, v.x, v.y, v.z, v.w);
                __syncwarp();
            }
#pragma unroll
            for (int e = 0; e < 4; e++) y[e] = badd(x[e], bmul(badd(y[e], tt[e]), gt[e]));
            stm4(ad, y[0], y[1], y[2], y[3]);
            __syncwarp();
            const int row = lane >> 1;
            const uint4 o = lds128(rw + row * 304 + 16 * (lane & 1));
            if (!((((q & 2) ? skip.y : skip.x) >> (16 * (q & 1) + row)) & 1))
                *((uint4*)(p.out + (size_t)(512 * q + rb0 + row) * D_ + c0 + 16 * cu) + (lane & 1)) = o;
        }
        return;
    }

    {
        const int fw = warp - 13;
        if (fw < nsl) {
            st_rlx(&p.s->h[tag ^ 1][(32 * (sl0 + fw) + 16 * r) * 4 + lane], 0u);
            st_rlx(&p.s->h[tag ^ 1][(32 * (sl0 + fw) + 16 * r) * 4 + 32 + lane], 0u);
        }
        if (fw == 2) {
            spin_until(t0, p.tn.t_xs);
            uint32_t sv = 0;
#pragma unroll 1
            for (int it = 0; it < SPIN_LIMIT; it++) {
                sv = ld_rlx(&p.s->sel[bid & 3][j]);
                if (__all_sync(~0u, ((sv >> 15) & 1) == tag)) break;
                __nanosleep(40);
            }
            mbar_wait(S + B_KG * 8, 0);
            if (lane == 0) { fence_async(); mbar_expect(S + B_BOX * 8, 8 * 1152); }
            __syncwarp();
            if (lane < 8) bulk_g2s(S + SM_XS + lane * ROW_STRIDE, p.u + (size_t)(sv & 2047) * D_, 1152, S + B_BOX * 8);
            const uint32_t st = ld_stat(&p.s->stat[sv & 2047], tag);
            const float ri = rcpf(bf_hi(st));
            const uint32_t hi = pack_bf(ri, ri);
            const float rl = ri - bf_lo(hi);
            if (lane == 0) sts64(S + SM_SKIP, 0u, 0u);
            __syncwarp();
            if (lane < 8) {
                const int row = sv & 2047;
                if (((row >> 4) & 31) == (bid >> 2)) asm volatile("red.shared.or.b32 [%0], %1;" ::"r"(S + SM_SKIP + 4 * (row >> 10)), "r"(1u << (16 * ((row >> 9) & 1) + (row & 15))) : "memory");
                sts32(S + SM_XS + 8 * ROW_STRIDE + 4 * lane, sv);
                sts128(S + SM_RP + 16 * lane, prmt(st, st, 0x1010), hi, pack_bf(rl, rl), 0u);
            }
        }
        asm volatile("barrier.cluster.wait.aligned;" ::: "memory");
        bar_sync(9, 96);
        mbar_wait(S + B_BOX * 8, 0);
#pragma unroll
        for (int k = 0; k < 6; k++) {
            const int v = tid - 416 + 96 * k, tk = (v * 911) >> 16;
            const uint4 x = lds128(S + SM_XS + 16 * (v + tk)), st = lds128(S + SM_RP + 16 * tk);
            sts128(S + SM_XS + 16 * (v + tk), norm2(x.x, st.x, st.y, st.z), norm2(x.y, st.x, st.y, st.z), norm2(x.z, st.x, st.y, st.z), norm2(x.w, st.x, st.y, st.z));
        }
        bar_sync(9, 96);
        if (tid == 416) mbar_arrive(S + B_XS * 8);
        const uint32_t ob = mapa(S, r ^ 1);
        if (fw == 2) {
            if (elect()) {
#pragma unroll 1
                for (int st = 0; st < (down ? 24 : 6 * nsl); st++) {
                    if (st == 12 && down) break;
                    mbar_wait(S + (B_W + st) * 8, 0);
                    if (st % 3 == 2) mbar_arrive(S + (B_GU + st / 3) * 8);
                }
            }
            __syncwarp();
        }
        if (fw < 2) {
            const uint32_t bad = S + SM_XS + j * ROW_STRIDE + mi * 16;
            uint32_t aad = (SW + (8 * (mi >> 1) + j) * 64 + 16 * ((mi & 1) ^ (j >> 1))) ^ ((r ^ fw) * 32);
            uint32_t b[18][4];
#pragma unroll
            for (int k = 0; k < 18; k++) ldm4(bad + 64 * k, b[k][0], b[k][1], b[k][2], b[k][3]);
#pragma unroll 1
            for (int u = 0; u < nsl; u++) {
                float d[4][4];
#pragma unroll
                for (int i = 0; i < 4; i++) d[i][0] = d[i][1] = d[i][2] = d[i][3] = 0.f;
#pragma unroll
                for (int hf = 0; hf < 2; hf++) {
                    mbar_wait(S + (B_GU + 2 * u + hf) * 8, 0);
#pragma unroll
                    for (int sub = 0; sub < 3; sub++) {
                        uint32_t a[6][4];
#pragma unroll
                        for (int k = 0; k < 6; k++) ldm4t(aad + 1024 * k, a[k][0], a[k][1], a[k][2], a[k][3]);
#pragma unroll
                        for (int k = 0; k < 6; k++) {
                            const int kb = 9 * hf + 3 * sub + (k >> 1);
                            mma_bf(d[k & 3], a[k][0], a[k][1], a[k][2], a[k][3], b[kb][2 * (k & 1)], b[kb][2 * (k & 1) + 1]);
                        }
                        aad += STAGE;
                    }
                }
                const uint32_t k0 = pack_bf((d[0][0] + d[1][0]) + (d[2][0] + d[3][0]), (d[0][1] + d[1][1]) + (d[2][1] + d[3][1]));
                const uint32_t k1 = pack_bf((d[0][2] + d[1][2]) + (d[2][2] + d[3][2]), (d[0][3] + d[1][3]) + (d[2][3] + d[3][3]));
                if (fw == 1) {
                    asm volatile("st.async.shared::cluster.mbarrier::complete_tx::bytes.v2.b32 [%0], {%1, %2}, [%3];" ::"r"(ob + SM_PART + u * 256 + lane * 8), "r"(k0), "r"(k1), "r"(ob + (B_GX + u) * 8) : "memory");
                } else {
                    mbar_wait(S + (B_GX + u) * 8, 0);
                    const uint2 o = lds64(S + SM_PART + u * 256 + lane * 8);
#pragma unroll
                    for (int i = 0; i < 2; i++) {
                        const uint32_t mine = i ? k1 : k0, other = i ? o.y : o.x, gb = r ? other : mine, ub = r ? mine : other;
                        uint32_t hv = bmul(pack_bf(silu_f(bf_lo(gb)), silu_f(bf_hi(gb))), ub);
                        if ((hv & 0xFFFFu) == 0) hv |= 0x8000u;
                        if ((hv >> 16) == 0) hv |= 0x80000000u;
                        st_rlx(&p.s->h[tag][(32 * (sl0 + u) + 16 * r) * 4 + 32 * i + lane], hv);
                    }
                    __syncwarp();
                    if (lane < 8) red_add(&p.s->cnt[lane * 32]);
                }
            }
        }
        if (!down) return;

        const int fi = 32 * fw + lane, tok = 4 * r + ((fi >> 4) & 3), cc = 16 * pr + (fi & 15);
        const uint32_t sel = lds32(S + SM_XS + 8 * ROW_STRIDE + 4 * tok);
        const int row = sel & 2047;
        const uint32_t* ya = p.s->y + (row >> 4) * 4608 + cc * 8 + (row & 6);
        const float xraw = __bfloat162float(p.u[(size_t)row * D_ + cc]), dsk = __bfloat162float(p.dskip[cc]);
        const float xn = bf_lo(lds16(S + SM_XS + tok * ROW_STRIDE + 2 * cc));
        if (fw == 0) {
#pragma unroll 1
            for (int st = 12; st < 24; st++) mbar_wait(S + (B_W + st) * 8, 0);
        }
        if (fw == 2 && elect()) wait_count(&p.s->cnt[(bid & 7) * 32], epoch * 288u);
        bar_sync(9, 96);
        float dn[4][4];
        uint2 yv2 = make_uint2(tag ^ 1, 0u);
#pragma unroll 1
        for (int ph = 0; ph < 64; ph++) {
            if (fw == 2 && elect()) {
                fence_async();
                fence_async_g();
                mbar_expect(S + B_H * 8, 36864);
                bulk_g2s(SW, (const char*)p.s->h[tag] + r * 36864, 36864, S + B_H * 8);
            }
            asm volatile("ld.relaxed.gpu.global.v2.u32 {%0,%1}, [%2];" : "=r"(yv2.x), "=r"(yv2.y) : "l"(ya) : "memory");
            mbar_wait(S + B_H * 8, ph & 1);
#pragma unroll
            for (int i = 0; i < 4; i++) dn[i][0] = dn[i][1] = dn[i][2] = dn[i][3] = 0.f;
            uint32_t bq[4] = {~0u, ~0u, ~0u, ~0u};
            const int fr = j + 8 * (mi >> 1);
            uint32_t wa = SW + 12 * STAGE + fw * 2048 + fr * 32 + (((mi & 1) ^ ((fr >> 2) & 1)) << 4), ha = SW + fw * 1024 + lane * 16;
#pragma unroll 1
            for (int s0 = 0; s0 < 12; s0 += 3) {
                uint32_t a[6][8], b[6][4];
#pragma unroll
                for (int s = 0; s < 3; s++) {
                    if (s == 2 && s0 == 9) wa += S + SM_W_LAST - (SW + 23 * STAGE);
#pragma unroll
                    for (int e = 0; e < 2; e++) {
                        ldm4t(ha + e * 512, b[2 * s + e][0], b[2 * s + e][1], b[2 * s + e][2], b[2 * s + e][3]);
                        ldm4t(wa + e * 1024, a[2 * s + e][0], a[2 * s + e][1], a[2 * s + e][2], a[2 * s + e][3]);
                        ldm4t(wa + e * 1024 + 512, a[2 * s + e][4], a[2 * s + e][5], a[2 * s + e][6], a[2 * s + e][7]);
                    }
                    wa += STAGE; ha += 3072;
                }
#pragma unroll
                for (int k = 0; k < 6; k++) {
                    mma_bf(dn[2 * (k & 1)], a[k][0], a[k][1], a[k][2], a[k][3], b[k][0], b[k][1]);
                    mma_bf(dn[2 * (k & 1) + 1], a[k][4], a[k][5], a[k][6], a[k][7], b[k][2], b[k][3]);
#pragma unroll
                    for (int q = 0; q < 4; q++) bq[q] = __vminu2(bq[q], b[k][q]);
                }
            }
            const uint32_t bm = __vminu2(__vminu2(bq[0], bq[1]), __vminu2(bq[2], bq[3])), bd = (bm - 0x00010001u) & ~bm;
            uint32_t anybad;
            asm volatile("{.reg .pred p, q; setp.ne.u32 p, %1, 0; bar.red.or.pred q, 9, 96, p; selp.u32 %0, 1, 0, q;}" : "=r"(anybad) : "r"(bd & 0x80008000u) : "memory");
            if (!anybad) break;
        }
        float* red = (float*)(smem + SM_RED + fw * 512);
        red[(2 * t) * 16 + g] = (dn[0][0] + dn[1][0]) + (dn[2][0] + dn[3][0]);
        red[(2 * t + 1) * 16 + g] = (dn[0][1] + dn[1][1]) + (dn[2][1] + dn[3][1]);
        red[(2 * t) * 16 + g + 8] = (dn[0][2] + dn[1][2]) + (dn[2][2] + dn[3][2]);
        red[(2 * t + 1) * 16 + g + 8] = (dn[0][3] + dn[1][3]) + (dn[2][3] + dn[3][3]);
        bar_sync(9, 96);
        if (fw < 2) {
            const float* rs = (const float*)(smem + SM_RED);
            const int mine = 64 * r + fi, other = mine ^ 64;
            st_async32(ob + SM_RP + 4 * fi, __float_as_uint(rs[other] + rs[128 + other] + rs[256 + other]), ob + B_RED * 8);
            const float s = rs[mine] + rs[128 + mine] + rs[256 + mine];
#pragma unroll 1
            for (int it = 0; it < SPIN_LIMIT && (yv2.x & 1) != tag; it++)
                asm volatile("ld.relaxed.gpu.global.v2.u32 {%0,%1}, [%2];" : "=r"(yv2.x), "=r"(yv2.y) : "l"(ya) : "memory");
            const uint32_t yw = (row & 8) ? yv2.y : yv2.x;
            const float sg = bf_round(((row & 1) ? bf_hi(yw) : bf_lo(yw)) + bf_round(xn * dsk));
            mbar_wait(S + B_RED * 8, 0);
            const float o = *(const float*)(smem + SM_RP + 4 * fi);
            const float yv = bf_round(bf_round(r == 0 ? s + o : o + s) * bf_hi(sel));
            p.out[(size_t)row * D_ + cc] = __float2bfloat16(xraw + bf_round(sg * bf_round(silu_f(bf_round(xn + yv)))));
            if (bid == 0 && fi == 0) st_rlx(&p.s->cnt[16 * 32], epoch);
        }
    }
}

typedef CUresult (*EncodeFn)(CUtensorMap*, CUtensorMapDataType, cuuint32_t, void*, const cuuint64_t*, const cuuint64_t*, const cuuint32_t*,
                             const cuuint32_t*, CUtensorMapInterleave, CUtensorMapSwizzle, CUtensorMapL2promotion, CUtensorMapFloatOOBfill);

static void make2d(EncodeFn enc, CUtensorMap* m, const void* base, uint64_t cols, uint64_t rows, uint32_t bc, uint32_t br, CUtensorMapSwizzle sw) {
    cuuint64_t gd[2] = {cols, rows};
    cuuint64_t gs[1] = {cols * 2};
    cuuint32_t bd[2] = {bc, br}, es[2] = {1, 1};
    enc(m, CU_TENSOR_MAP_DATA_TYPE_BFLOAT16, 2, const_cast<void*>(base), gd, gs, bd, es, CU_TENSOR_MAP_INTERLEAVE_NONE, sw,
        CU_TENSOR_MAP_L2_PROMOTION_L2_128B, CU_TENSOR_MAP_FLOAT_OOB_FILL_NONE);
}

static Tune g_tune = {2000, 9000, 3, 5, 8, 5000, 7500, 0, 9000, 1, 0, 0};


static void launch(void* const* d_in, void* d_out) {
    static EncodeFn enc = nullptr;
    static Scratch* gs = nullptr;
    if (!enc) {
        void* fn = nullptr;
        cudaDriverEntryPointQueryResult qr;
        cudaGetDriverEntryPoint("cuTensorMapEncodeTiled", &fn, cudaEnableDefault, &qr);
        enc = (EncodeFn)fn;
        cudaFuncSetAttribute(fused_kernel, cudaFuncAttributeMaxDynamicSharedMemorySize, SM_TOTAL);
        cudaGetSymbolAddress((void**)&gs, g_s);
    }
    Hot p;
    Maps m;
    auto in = [&](int i) { return (const __nv_bfloat16*)d_in[i]; };
    p.u = in(0); p.are = in(1); p.aim = in(2); p.bre = in(3); p.bim = in(4); p.cre = in(5); p.cim = in(6);
    p.logdt = in(7); p.dskip = in(8); p.wr = in(10); p.pwg = in(11); p.pwu = in(12); p.pwd = in(13);
    p.out = (__nv_bfloat16*)d_out;
    p.tn = g_tune;
    p.s = gs;
    make2d(enc, &m.wg, p.pwg, F_, D_, 32, 96, CU_TENSOR_MAP_SWIZZLE_64B);
    make2d(enc, &m.wu, p.pwu, F_, D_, 32, 96, CU_TENSOR_MAP_SWIZZLE_64B);
    make2d(enc, &m.wd, p.pwd, D_, F_, 16, 192, CU_TENSOR_MAP_SWIZZLE_32B);
    fused_kernel<<<NCTA, NTHREADS, SM_TOTAL>>>(p, m);
}

}

extern "C" void kernel_launch(void* const* d_in, const int* in_sizes, int n_in, void* d_out, int out_size) {
    static int clusters = -1;
    if (clusters < 0) clusters = v3::max_clusters();
    if (clusters < 15 || !v3::launch(d_in, d_out)) v2::launch(d_in, d_out);
}
```
